```python
import torch

def _softmax(x, axis=-1):
    return torch.softmax(x, dim=axis)
def _gelu(x):
    return torch.nn.functional.gelu(x, approximate="tanh")
def _silu(x):
    return torch.nn.functional.silu(x)
def _sigmoid(x):
    return torch.sigmoid(x)
def _layernorm(x, axis=-1, eps=1e-5):
    m = x.mean(dim=axis, keepdim=True)
    v = x.var(dim=axis, keepdim=True, unbiased=False)
    return (x - m) / torch.sqrt(v + eps)
def _scatter_add(tgt, idx, src, axis=0):
    return tgt.clone().index_add_(axis, idx, src)
def _segment_sum(src, seg, n):
    out = torch.zeros((n,) + src.shape[1:], dtype=src.dtype)
    return out.index_add_(0, seg, src)
def _pad(x, pw):
    flat = tuple(v for pair in reversed(pw) for v in pair)
    return torch.nn.functional.pad(x, flat)

kernel_name = 'gated_mix__spectral_fnet__moe_arch_mod__prompt'

def setup_inputs():

    _w = (lambda a: (lambda t: t.to(torch.bfloat16) if t.is_floating_point() else t)(torch.as_tensor(a)))
    def _A_setup():
        B, S, D = 1, 2048, 512
        ns = torch.arange(S)[:, None] * torch.arange(S)[None, :]
        nd = torch.arange(D)[:, None] * torch.arange(D)[None, :]
        Ws_re = torch.cos(-2.0 * torch.pi * ns / S).to(float)
        Ws_im = torch.sin(-2.0 * torch.pi * ns / S).to(float)
        Wd_re = torch.cos(-2.0 * torch.pi * nd / D).to(float)
        Wd_im = torch.sin(-2.0 * torch.pi * nd / D).to(float)
        return {
            "x": _w((lambda *s: torch.randn(*s, dtype=torch.bfloat16) * 0.05)(B, S, D)),
            "dft_seq_re": _w(Ws_re),
            "dft_seq_im": _w(Ws_im),
            "dft_hid_re": _w(Wd_re),
            "dft_hid_im": _w(Wd_im),
        }
    _A_in = _A_setup()

    def _B_setup():
        B, S, D, F, C = 1, 2048, 512, 1792, 1
        return {
            "x": _w((lambda *s: torch.randn(*s, dtype=torch.bfloat16) * 0.05)(B, S, D)),
            "w_r": _w((lambda *s: torch.randn(*s, dtype=torch.bfloat16) * 1.6)(D)),
            "w_gate": _w((lambda *s: torch.randn(*s, dtype=torch.bfloat16) * 1.6)(D, F)),
            "w_up": _w((lambda *s: torch.randn(*s, dtype=torch.bfloat16) * 1.6)(D, F)),
            "w_down": _w((lambda *s: torch.randn(*s, dtype=torch.bfloat16) * 1.6)(F, D)),
        }
    _B_in = _B_setup()

    return {
        "A_x": _A_in["x"],
        "A_dft_seq_re": _A_in["dft_seq_re"],
        "A_dft_seq_im": _A_in["dft_seq_im"],
        "A_dft_hid_re": _A_in["dft_hid_re"],
        "A_dft_hid_im": _A_in["dft_hid_im"],
        "B_x": _B_in["x"],
        "B_w_r": _B_in["w_r"],
        "B_w_gate": _B_in["w_gate"],
        "B_w_up": _B_in["w_up"],
        "B_w_down": _B_in["w_down"],
        "gate_w": _w((lambda *s: torch.randn(*s, dtype=torch.bfloat16) * 0.05)(512) * 16.0),
    }

def reference(A_x, A_dft_seq_re, A_dft_seq_im, A_dft_hid_re, A_dft_hid_im, B_x, B_w_r, B_w_gate, B_w_up, B_w_down, gate_w):
    def _A_ref(x, dft_seq_re, dft_seq_im, dft_hid_re, dft_hid_im):
        a = torch.einsum("bsd,ed->bse", x, dft_hid_re)
        b = torch.einsum("bsd,ed->bse", x, dft_hid_im)
        y = torch.einsum("ts,bse->bte", dft_seq_re, a) - torch.einsum("ts,bse->bte", dft_seq_im, b)
        return y

    def _B_ref(x, w_r, w_gate, w_up, w_down):
        B, S, D = x.shape
        C = 1
        r = x @ w_r
        idx = torch.argsort(-r, axis=-1)[:, :C]
        idx_e = (lambda x, n, axis: torch.repeat_interleave(x, n, dim=axis))(idx.reshape(B, C, 1), D, axis=2)
        x_sel = (lambda x, i, axis: torch.take_along_dim(x, i, dim=axis))(x, idx_e, axis=1)
        g = _silu(x_sel @ w_gate)
        u = x_sel @ w_up
        y = (g * u) @ w_down
        r_sel = _sigmoid((lambda x, i, axis: torch.take_along_dim(x, i, dim=axis))(r, idx, axis=1))
        y = y * r_sel.reshape(B, C, 1)
        b_off = (torch.arange(B) * S).reshape(B, 1)
        flat_idx = (idx + b_off).reshape(B * C)
        zero = (x * 0.0).reshape(B * S, D)
        upd = _scatter_add(zero, flat_idx, y.reshape(B * C, D), axis=0)
        return x + upd.reshape(B, S, D)

    x = A_x
    g = _sigmoid((x * gate_w).sum(-1, keepdims=True))
    a = _A_ref(x, A_dft_seq_re, A_dft_seq_im, A_dft_hid_re, A_dft_hid_im)
    b = _B_ref(x, B_w_r, B_w_gate, B_w_up, B_w_down)
    return g * a + (1 - g) * b
```

```cpp
#include <cuda_runtime.h>
#include <cuda.h>
#include <cuda_bf16.h>
#include <stdint.h>

typedef __nv_bfloat16 bf16;

#define PACE 0
#define PE 0
#define OLS 1
#define HINT_AT 400
#define PRIO 0
#define SK 5
#define PF_T0 4800
#define PF_DT 1700
#define FFN_S0 8
#define FFN_S1 12
#define NI0 0
#define INIT_T0 0
#define INIT_DT 450
#define W1FIRST 0
#define THR 1
#define TSD 1500
#define KC 0
#define PAUSE 0
#define PFA_T 0
#define PFA_S 0
#define HINTM 5
#define GOK 1
#define PFX 1
#define ROT 0
#define LOWP 1
#define PFL 0
#define TRED 1
#define RSW 1
#define ESTG 5
#define XL_AT 7
#define PD0 500
#define PD1 200
#define OL_T0 0
#define OL_DT 450
#define RS1 0
#define RSPLIT 1
#define GO_LATE 0
#define SUM_T0 15000
#define ROUTER_C 4
#define SHUF 1
#define POLL_NS 100

constexpr int S_ = 2048, D_ = 512, F_ = 1792;
constexpr int NCTA = 128;
constexpr int NTHREADS = 512;
constexpr int NSTAGE = 6;
constexpr int REGION = 32768;
constexpr int FFN_CTAS = F_ / 16;
constexpr uint32_t SPIN_LIMIT = 1u << 22;

constexpr int OFF_MISC = 7 * REGION;
constexpr int B_F = OFF_MISC;
constexpr int B_G0 = B_F + 64;
constexpr int B_G1 = B_G0 + 8;
constexpr int B_XE = B_G1 + 8;
constexpr int B_GO1 = B_XE + 8;
constexpr int B_SKEW0 = B_GO1 + 8;
constexpr int B_EPOCH = B_SKEW0 + 8;
constexpr int B_RETRY = B_EPOCH + 8;
constexpr int B_INIT = B_RETRY + 8;
constexpr int B_FULL = B_INIT + 8;
constexpr int B_EMPTY = B_FULL + 48;
constexpr int B_PUBI = B_EMPTY + 48;
constexpr int B_FREE = B_PUBI + 8;
constexpr int B_VD = B_FREE + 16;
constexpr int B_BL = B_VD + 8;
constexpr int B_TAIL = B_BL + 48;
constexpr int B_HX = B_TAIL + 8;
constexpr int B_FFN = B_HX + 8;
constexpr int B_ROLE = B_FFN + 40;
constexpr int B_SEEN = B_ROLE + 8;
constexpr int B_GATE = B_SEEN + 16;
constexpr int M_EPOCH = B_GATE + 8;
constexpr int M_ROLE = M_EPOCH + 4;
constexpr int M_RED = OFF_MISC + 400;
constexpr int M_HX = OFF_MISC + 512;
constexpr int M_G = M_HX + 1024;
constexpr int M_UPD = M_G + 512;
constexpr int M_PROF = M_UPD + 512;
constexpr int SMEM_BYTES = 232448;
static_assert(M_ROLE + 4 <= M_RED && M_UPD + 512 <= SMEM_BYTES, "smem");

struct Scratch {
    unsigned char ab[8 * 32 * 16384];
    unsigned int hint[8 * 8 * 32];
    unsigned int ready[8 * 32];
    unsigned int gate[S_];
    unsigned int part[FFN_CTAS / 2 * D_];
    unsigned int phint[4 * 16 * 8];
    unsigned int keys[8 * NCTA];
    unsigned int epoch[NCTA + 4];
};
__device__ __align__(1024) Scratch g_s;

struct Params {
    Scratch* s;
    bf16* out;
    const bf16 *x, *gate_w, *w_r, *wg, *wu, *wd;
    CUtensorMap mDre, mDim, mX1, mX2, mCre, mCim, mAB, mOut, mWg, mWu, mWd;
};

__device__ __forceinline__ uint32_t smem_u32(const void* p) { return (uint32_t)__cvta_generic_to_shared(p); }
#define PROFL(i) do {} while (0)
#define PROFIF(slot, pred) do {} while (0)
#define PROF(slot) do {} while (0)
#define PROFG(slot) do {} while (0)

__device__ __forceinline__ void mbar_init(uint32_t bar, uint32_t cnt) {
    asm volatile("mbarrier.init.shared::cta.b64 [%0], %1;" ::"r"(bar), "r"(cnt) : "memory");
}
__device__ __forceinline__ void mbar_expect_tx(uint32_t bar, uint32_t bytes) {
    asm volatile("mbarrier.arrive.expect_tx.shared::cta.b64 _, [%0], %1;" ::"r"(bar), "r"(bytes) : "memory");
}
__device__ __forceinline__ void mbar_arrive(uint32_t bar) {
    asm volatile("mbarrier.arrive.shared::cta.b64 _, [%0];" ::"r"(bar) : "memory");
}
__device__ __forceinline__ void mbar_arrive_if(uint32_t bar, bool pred) {
    asm volatile("{.reg .pred p; setp.ne.b32 p, %1, 0; @p mbarrier.arrive.shared::cta.b64 _, [%0];}" ::"r"(bar), "r"((int)pred) : "memory");
}
__device__ __forceinline__ void mbar_arrive_warp(uint32_t bar) {
    __syncwarp();
    mbar_arrive_if(bar, (threadIdx.x & 31) == 0);
}
__device__ __forceinline__ void mbar_arrive_cluster_if(uint32_t bar, bool pred) {
    asm volatile("{.reg .pred p; setp.ne.b32 p, %1, 0; @p mbarrier.arrive.shared::cluster.b64 _, [%0], 1;}"
                 ::"r"(bar), "r"((int)pred) : "memory");
}
__device__ __forceinline__ uint32_t mapa(uint32_t a, uint32_t cta) {
    uint32_t r;
    asm volatile("mapa.shared::cluster.u32 %0, %1, %2;" : "=r"(r) : "r"(a), "r"(cta));
    return r;
}
__device__ __forceinline__ bool mbar_try(uint32_t bar, uint32_t parity) {
    uint32_t ok;
    asm volatile("{.reg .pred p; mbarrier.try_wait.parity.shared::cta.b64 p, [%1], %2; selp.u32 %0,1,0,p;}"
                 : "=r"(ok) : "r"(bar), "r"(parity) : "memory");
    return ok;
}
__device__ __forceinline__ bool mbar_test(uint32_t bar, uint32_t parity) {
    uint32_t ok;
    asm volatile("{.reg .pred p; mbarrier.test_wait.parity.shared::cta.b64 p, [%1], %2; selp.u32 %0,1,0,p;}"
                 : "=r"(ok) : "r"(bar), "r"(parity) : "memory");
    return ok;
}
__device__ __forceinline__ void mbar_wait(uint32_t bar, uint32_t parity) {
    asm volatile("{.reg .pred p, q; .reg .u32 n; mov.u32 n, 0;\n"
                 "W%=: mbarrier.try_wait.parity.shared::cta.b64 p, [%0], %1;\n"
                 "add.u32 n, n, 1; setp.lt.and.u32 q, n, %2, !p; @q bra W%=; @!p trap;}" ::"r"(bar), "r"(parity), "n"(SPIN_LIMIT) : "memory");
}
__device__ __forceinline__ void mbar_spin(uint32_t bar, uint32_t parity) {
    asm volatile("{.reg .pred p;\nW%=: mbarrier.try_wait.parity.shared::cta.b64 p, [%0], %1; @!p bra W%=;}" ::"r"(bar), "r"(parity) : "memory");
}
__device__ __forceinline__ void mbar_wait_cluster(uint32_t bar, uint32_t parity) {
    uint32_t n = 0, ok;
    do {
        asm volatile("{.reg .pred p; mbarrier.try_wait.parity.acquire.cluster.shared::cta.b64 p, [%1], %2; selp.u32 %0,1,0,p;}"
                     : "=r"(ok) : "r"(bar), "r"(parity) : "memory");
        if (++n > SPIN_LIMIT) __trap();
    } while (!ok);
}
__device__ __forceinline__ void tma2d(uint32_t dst, const CUtensorMap* m, int c0, int c1, uint32_t bar) {
    asm volatile("cp.async.bulk.tensor.2d.shared::cluster.global.mbarrier::complete_tx::bytes [%0], [%1, {%3,%4}], [%2];"
                 ::"r"(dst), "l"(m), "r"(bar), "r"(c0), "r"(c1) : "memory");
}
__device__ __forceinline__ void tma2d_elect(uint32_t dst, const CUtensorMap* m, int c0, int c1, uint32_t bar) {
    asm volatile("{.reg .pred p; elect.sync _|p, 0xffffffff;"
                 " @p cp.async.bulk.tensor.2d.shared::cluster.global.mbarrier::complete_tx::bytes [%0], [%1, {%3,%4}], [%2];}"
                 ::"r"(dst), "l"(m), "r"(bar), "r"(c0), "r"(c1) : "memory");
}
__device__ __forceinline__ void tma2d_pair_elect(uint32_t dst, const CUtensorMap* m, int c0, int c1, uint32_t bar) {
    asm volatile("{.reg .pred p; elect.sync _|p, 0xffffffff;"
                 " @p cp.async.bulk.tensor.2d.shared::cluster.global.mbarrier::complete_tx::bytes.multicast::cluster"
                 " [%0], [%1, {%3,%4}], [%2], %5;}" ::"r"(dst), "l"(m), "r"(bar), "r"(c0), "r"(c1), "h"((uint16_t)3) : "memory");
}
__device__ __forceinline__ void mbar_expect_tx_elect(uint32_t bar, uint32_t bytes) {
    asm volatile("{.reg .pred p; elect.sync _|p, 0xffffffff; @p mbarrier.arrive.expect_tx.shared::cta.b64 _, [%0], %1;}"
                 ::"r"(bar), "r"(bytes) : "memory");
}
__device__ __forceinline__ void tma3d(uint32_t dst, const CUtensorMap* m, int row, int chunk, uint32_t bar) {
    asm volatile("cp.async.bulk.tensor.3d.shared::cluster.global.mbarrier::complete_tx::bytes [%0], [%1, {%3,%4,%5}], [%2];"
                 ::"r"(dst), "l"(m), "r"(bar), "r"(0), "r"(row), "r"(chunk) : "memory");
}
__device__ __forceinline__ void tma2d_prefetch(const CUtensorMap* m, int c0, int c1) {
    asm volatile("cp.async.bulk.prefetch.tensor.2d.L2.global [%0, {%1,%2}];" ::"l"(m), "r"(c0), "r"(c1) : "memory");
}
__device__ __forceinline__ void fence_proxy_async_smem() { asm volatile("fence.proxy.async.shared::cta;" ::: "memory"); }
__device__ __forceinline__ void fence_proxy_async_gmem() { asm volatile("fence.proxy.async.global;" ::: "memory"); }
__device__ __forceinline__ void prefetch_l2(const void* p) { asm volatile("prefetch.global.L2 [%0];" ::"l"(p)); }
__device__ __forceinline__ uint32_t ld_relaxed(const void* p) {
    uint32_t v;
    asm volatile("ld.relaxed.gpu.global.u32 %0, [%1];" : "=r"(v) : "l"(p) : "memory");
    return v;
}
__device__ __forceinline__ uint4 ld_relaxed4(const void* p) {
    uint4 v;
    asm volatile("ld.relaxed.gpu.global.v4.u32 {%0,%1,%2,%3}, [%4];" : "=r"(v.x), "=r"(v.y), "=r"(v.z), "=r"(v.w) : "l"(p) : "memory");
    return v;
}
__device__ __forceinline__ uint4 ld_relaxed_b128(const void* p) {
    uint4 v;
    asm volatile("{.reg .b128 t; ld.relaxed.gpu.global.b128 t, [%4]; mov.b128 {%0,%1,%2,%3}, t;}"
                 : "=r"(v.x), "=r"(v.y), "=r"(v.z), "=r"(v.w) : "l"(p) : "memory");
    return v;
}
__device__ __forceinline__ uint4 ld_relaxed_b128_if(const void* p, bool pred) {
    uint4 v = make_uint4(0, 0, 0, 0);
    asm volatile("{.reg .b128 t; .reg .pred p; setp.ne.b32 p, %5, 0; mov.b128 t, {%0,%1,%2,%3};"
                 " @p ld.relaxed.gpu.global.b128 t, [%4]; mov.b128 {%0,%1,%2,%3}, t;}"
                 : "+r"(v.x), "+r"(v.y), "+r"(v.z), "+r"(v.w) : "l"(p), "r"((int)pred) : "memory");
    return v;
}
__device__ __forceinline__ void st_relaxed_b128(void* p, uint32_t x, uint32_t y, uint32_t z, uint32_t w) {
    asm volatile("{.reg .b128 t; .reg .b64 a, b; mov.b64 a, {%1,%2}; mov.b64 b, {%3,%4}; mov.b128 t, {a, b};"
                 " st.relaxed.gpu.global.b128 [%0], t;}" ::"l"(p), "r"(x), "r"(y), "r"(z), "r"(w) : "memory");
}
__device__ __forceinline__ void st_relaxed(unsigned int* p, uint32_t v) {
    asm volatile("st.relaxed.gpu.global.u32 [%0], %1;" ::"l"(p), "r"(v) : "memory");
}
__device__ __forceinline__ void st_relaxed_if(unsigned int* p, uint32_t v, bool pred) {
    asm volatile("{.reg .pred p; setp.ne.b32 p, %2, 0; @p st.relaxed.gpu.global.u32 [%0], %1;}" ::"l"(p), "r"(v), "r"((int)pred) : "memory");
}
__device__ __forceinline__ void red_inc_if(unsigned int* p, bool pred) {
    asm volatile("{.reg .pred p; setp.ne.b32 p, %1, 0; @p red.relaxed.gpu.global.add.u32 [%0], 1;}" ::"l"(p), "r"((int)pred) : "memory");
}
__device__ __forceinline__ void st_key(unsigned int* p, uint32_t v) {
    asm volatile("{.reg .b32 old; atom.relaxed.gpu.global.exch.b32 old, [%0], %1;}" ::"l"(p), "r"(v) : "memory");
}
__device__ __forceinline__ uint32_t tagf(float v, uint32_t par) { return (__float_as_uint(v) & ~1u) | par; }
__device__ __forceinline__ uint4 wait_tags(const unsigned int* p, int bit, uint32_t par) {
    uint32_t n = 0;
    while (true) {
        const uint4 v = ld_relaxed4(p);
        const uint32_t m = par ? (v.x & v.y & v.z & v.w) : ~(v.x | v.y | v.z | v.w);
        if (__all_sync(0xffffffffu, (m >> bit) & 1u)) return v;
        __nanosleep(POLL_NS);
        if (++n > SPIN_LIMIT) __trap();
    }
}
template <int SLEEP>
__device__ __forceinline__ void wait_counters(const unsigned int* p, uint32_t want) {
    uint32_t n = 0;
    while (!__all_sync(0xffffffffu, (int)(ld_relaxed(p) - want) >= 0)) {
        if (SLEEP) __nanosleep(SLEEP);
        if (++n > SPIN_LIMIT) __trap();
    }
    asm volatile("fence.acquire.gpu;" ::: "memory");
}
__device__ __forceinline__ void red_release_add(unsigned int* p, uint32_t v) {
    asm volatile("red.release.gpu.global.add.u32 [%0], %1;" ::"l"(p), "r"(v) : "memory");
}
__device__ __forceinline__ void named_bar(int id, int n) { asm volatile("bar.sync %0, %1;" ::"r"(id), "r"(n) : "memory"); }
template <int OFF>
__device__ __forceinline__ uint4 ldg_nc_off(const void* p) {
    uint4 v;
    asm volatile("ld.global.nc.v4.u32 {%0,%1,%2,%3}, [%4+%5];" : "=r"(v.x), "=r"(v.y), "=r"(v.z), "=r"(v.w) : "l"(p), "n"(OFF));
    return v;
}
template <int OFF>
__device__ __forceinline__ void stg_off_if(void* p, const uint4& v, bool pred) {
    asm volatile("{.reg .pred p; setp.ne.b32 p, %6, 0; @p st.global.v4.u32 [%0+%5], {%1,%2,%3,%4};}"
                 ::"l"(p), "r"(v.x), "r"(v.y), "r"(v.z), "r"(v.w), "n"(OFF), "r"((int)pred) : "memory");
}
template <int OFF>
__device__ __forceinline__ void stg_off(void* p, const uint4& v) {
    asm volatile("st.global.v4.u32 [%0+%5], {%1,%2,%3,%4};" ::"l"(p), "r"(v.x), "r"(v.y), "r"(v.z), "r"(v.w), "n"(OFF) : "memory");
}
__device__ __forceinline__ void sts128(uint32_t a, const uint4& v) {
    asm volatile("st.shared.v4.u32 [%0], {%1,%2,%3,%4};" ::"r"(a), "r"(v.x), "r"(v.y), "r"(v.z), "r"(v.w) : "memory");
}
__device__ __forceinline__ uint4 lds128(uint32_t a) {
    uint4 v;
    asm volatile("ld.shared.v4.u32 {%0,%1,%2,%3}, [%4];" : "=r"(v.x), "=r"(v.y), "=r"(v.z), "=r"(v.w) : "r"(a) : "memory");
    return v;
}
__device__ __forceinline__ float selpf(float a, float b, bool p) {
    float r;
    asm("{.reg .pred q; setp.ne.b32 q, %3, 0; selp.f32 %0, %1, %2, q;}" : "=f"(r) : "f"(a), "f"(b), "r"((int)p));
    return r;
}
template <int N, int MASK, int SZ>
__device__ __forceinline__ void halve(float (&a)[SZ]) {
    const bool up = threadIdx.x & MASK;
#pragma unroll
    for (int j = 0; j < N; j++) a[j] = selpf(a[N + j], a[j], up) + __shfl_xor_sync(0xffffffffu, selpf(a[j], a[N + j], up), MASK);
}
__device__ __forceinline__ float bflo(uint32_t u) { return __uint_as_float(u << 16); }
__device__ __forceinline__ float bfhi(uint32_t u) { return __uint_as_float(u & 0xffff0000u); }
__device__ __forceinline__ uint32_t pack_bf16(float lo, float hi) {
    uint32_t r;
    asm("cvt.rn.bf16x2.f32 %0, %1, %2;" : "=r"(r) : "f"(hi), "f"(lo));
    return r;
}
__device__ __forceinline__ uint32_t hfma2_bf16(uint32_t a, uint32_t b, uint32_t c) {
    uint32_t r;
    asm("fma.rn.bf16x2 %0, %1, %2, %3;" : "=r"(r) : "r"(a), "r"(b), "r"(c));
    return r;
}
__device__ __forceinline__ uint32_t hmul2_bf16(uint32_t a, uint32_t b) {
    uint32_t r;
    asm("mul.rn.bf16x2 %0, %1, %2;" : "=r"(r) : "r"(a), "r"(b));
    return r;
}
__device__ __forceinline__ float sigmoidf_(float v) { return __frcp_rn(1.0f + __expf(-v)); }

__device__ __forceinline__ void wg_fence() { asm volatile("wgmma.fence.sync.aligned;" ::: "memory"); }
__device__ __forceinline__ void wg_commit() { asm volatile("wgmma.commit_group.sync.aligned;" ::: "memory"); }
template <int N> __device__ __forceinline__ void wg_wait() { asm volatile("wgmma.wait_group.sync.aligned %0;" ::"n"(N) : "memory"); }
__device__ __forceinline__ uint64_t desc64_lo(uint32_t lo) { return (uint64_t)lo | (0x80000020ull << 32); }
__device__ __forceinline__ uint64_t desc_lo(uint32_t lo) { return (uint64_t)lo | (0x40000040ull << 32); }
template <int LO, int HI, int N>
__device__ __forceinline__ void fence_regs(float (&d)[N]) {
#pragma unroll
    for (int i = LO; i < HI; i++) asm volatile("" : "+f"(d[i])::"memory");
}
template <int TB = 1>
__device__ __forceinline__ void wgmma128(float (&d)[64], uint64_t da, uint64_t db, int scaleD) {
    asm volatile(
        "{ .reg .pred p; setp.ne.b32 p, %66, 0;\n"
        "wgmma.mma_async.sync.aligned.m64n128k16.f32.bf16.bf16 "
        "{%0,%1,%2,%3,%4,%5,%6,%7,%8,%9,%10,%11,%12,%13,%14,%15,%16,%17,%18,%19,%20,%21,%22,%23,%24,%25,%26,%27,%28,%29,%30,%31,"
        "%32,%33,%34,%35,%36,%37,%38,%39,%40,%41,%42,%43,%44,%45,%46,%47,%48,%49,%50,%51,%52,%53,%54,%55,%56,%57,%58,%59,%60,%61,%62,%63}, "
        "%64, %65, p, 1, 1, 0, %67;\n}"
        : "+f"(d[0]), "+f"(d[1]), "+f"(d[2]), "+f"(d[3]), "+f"(d[4]), "+f"(d[5]), "+f"(d[6]), "+f"(d[7]),
          "+f"(d[8]), "+f"(d[9]), "+f"(d[10]), "+f"(d[11]), "+f"(d[12]), "+f"(d[13]), "+f"(d[14]), "+f"(d[15]),
          "+f"(d[16]), "+f"(d[17]), "+f"(d[18]), "+f"(d[19]), "+f"(d[20]), "+f"(d[21]), "+f"(d[22]), "+f"(d[23]),
          "+f"(d[24]), "+f"(d[25]), "+f"(d[26]), "+f"(d[27]), "+f"(d[28]), "+f"(d[29]), "+f"(d[30]), "+f"(d[31]),
          "+f"(d[32]), "+f"(d[33]), "+f"(d[34]), "+f"(d[35]), "+f"(d[36]), "+f"(d[37]), "+f"(d[38]), "+f"(d[39]),
          "+f"(d[40]), "+f"(d[41]), "+f"(d[42]), "+f"(d[43]), "+f"(d[44]), "+f"(d[45]), "+f"(d[46]), "+f"(d[47]),
          "+f"(d[48]), "+f"(d[49]), "+f"(d[50]), "+f"(d[51]), "+f"(d[52]), "+f"(d[53]), "+f"(d[54]), "+f"(d[55]),
          "+f"(d[56]), "+f"(d[57]), "+f"(d[58]), "+f"(d[59]), "+f"(d[60]), "+f"(d[61]), "+f"(d[62]), "+f"(d[63])
        : "l"(da), "l"(db), "r"(scaleD), "n"(TB));
}

__device__ __forceinline__ void mbar_init_elect(uint32_t bar, uint32_t cnt) {
    asm volatile("{.reg .pred p; elect.sync _|p, 0xffffffff; @p mbarrier.init.shared::cta.b64 [%0], %1;}" ::"r"(bar), "r"(cnt) : "memory");
}
__device__ __forceinline__ void mbar_arrive_elect(uint32_t bar) {
    asm volatile("{.reg .pred p; elect.sync _|p, 0xffffffff; @p mbarrier.arrive.shared::cta.b64 _, [%0];}" ::"r"(bar) : "memory");
}
__device__ __forceinline__ void tma3d_elect(uint32_t dst, const CUtensorMap* m, int row, int chunk, uint32_t bar) {
    asm volatile("{.reg .pred p; elect.sync _|p, 0xffffffff;"
                 " @p cp.async.bulk.tensor.3d.shared::cluster.global.mbarrier::complete_tx::bytes [%0], [%1, {%3,%4,%5}], [%2];}"
                 ::"r"(dst), "l"(m), "r"(bar), "r"(0), "r"(row), "r"(chunk) : "memory");
}
template <int N>
__device__ __forceinline__ void mbar_arrive_n_elect(uint32_t bar) {
    asm volatile("{.reg .pred p; elect.sync _|p, 0xffffffff; @p mbarrier.arrive.shared::cta.b64 _, [%0], %1;}" ::"r"(bar), "n"(N) : "memory");
}
template <int N>
__device__ __forceinline__ void bulk_store_elect(void* dst, uint32_t src) {
    asm volatile("{.reg .pred p; elect.sync _|p, 0xffffffff; @p cp.async.bulk.global.shared::cta.bulk_group [%0], [%1], %2;}"
                 ::"l"(dst), "r"(src), "n"(N) : "memory");
}
__device__ __forceinline__ void bulk_wait_read() {
    asm volatile("cp.async.bulk.commit_group; cp.async.bulk.wait_group.read 0;" ::: "memory");
    __syncwarp();
}
template <int N>
__device__ __forceinline__ void release_pair(uint32_t bar, uint32_t rbar, bool pred) {
    asm volatile("{.reg .pred p; setp.ne.b32 p, %2, 0; @p mbarrier.arrive.shared::cta.b64 _, [%0], %3;"
                 " @p mbarrier.arrive.shared::cluster.b64 _, [%1], %3;}" ::"r"(bar), "r"(rbar), "r"((int)pred), "n"(N) : "memory");
}
template <int OFF>
__device__ __forceinline__ void red_bf16x8(void* p, uint32_t x, uint32_t y, uint32_t z, uint32_t w) {
    asm volatile("red.relaxed.gpu.global.add.noftz.v4.bf16x2 [%0+%5], {%1,%2,%3,%4};"
                 ::"l"(p), "r"(x), "r"(y), "r"(z), "r"(w), "n"(OFF) : "memory");
}
template <int OFF>
__device__ __forceinline__ uint32_t lds32_off(uint32_t a) {
    uint32_t v;
    asm volatile("ld.shared.u32 %0, [%1+%2];" : "=r"(v) : "r"(a), "n"(OFF) : "memory");
    return v;
}
template <int OFF>
__device__ __forceinline__ void sts128_off(uint32_t a, const uint4& v) {
    asm volatile("st.shared.v4.u32 [%0+%5], {%1,%2,%3,%4};" ::"r"(a), "r"(v.x), "r"(v.y), "r"(v.z), "r"(v.w), "n"(OFF) : "memory");
}

__device__ __forceinline__ uint32_t gtime() {
    uint32_t t;
    asm volatile("mov.u32 %0, %%globaltimer_lo;" : "=r"(t));
    return t;
}
__device__ __forceinline__ uint2 ld_relaxed2(const void* p) {
    uint2 v;
    asm volatile("{.reg .b64 t; ld.relaxed.gpu.global.b64 t, [%2]; mov.b64 {%0,%1}, t;}" : "=r"(v.x), "=r"(v.y) : "l"(p) : "memory");
    return v;
}
__device__ __forceinline__ void st_stamp_if(unsigned int* p, uint32_t v, bool pred) {
    asm volatile("{.reg .pred p; .reg .b32 t; .reg .b64 w; setp.ne.b32 p, %2, 0; mov.u32 t, %%globaltimer_lo; mov.b64 w, {%1, t};"
                 " @p st.relaxed.gpu.global.b64 [%0], w;}" ::"l"(p), "r"(v), "r"((int)pred) : "memory");
}
__device__ __forceinline__ uint32_t pin(uint32_t v) { return __shfl_xor_sync(0xffffffffu, v, 0); }
template <class T>
__device__ __forceinline__ T* pin(T* p) { return (T*)__shfl_xor_sync(0xffffffffu, (unsigned long long)p, 0); }
template <class T>
__device__ __forceinline__ T* pin_uniform(T* p) { return (T*)__shfl_sync(0xffffffffu, (unsigned long long)p, 0); }
__device__ __forceinline__ uint32_t stale_tags(uint32_t a, uint32_t par) {
    uint32_t r;
    asm volatile("{.reg .b32 v<16>;\n"
                 "ld.shared.u32 v0, [%1]; ld.shared.u32 v1, [%1+256]; ld.shared.u32 v2, [%1+512]; ld.shared.u32 v3, [%1+768];\n"
                 "ld.shared.u32 v4, [%1+4096]; ld.shared.u32 v5, [%1+4352]; ld.shared.u32 v6, [%1+4608]; ld.shared.u32 v7, [%1+4864];\n"
                 "ld.shared.u32 v8, [%1+8192]; ld.shared.u32 v9, [%1+8448]; ld.shared.u32 v10, [%1+8704]; ld.shared.u32 v11, [%1+8960];\n"
                 "ld.shared.u32 v12, [%1+12288]; ld.shared.u32 v13, [%1+12544]; ld.shared.u32 v14, [%1+12800]; ld.shared.u32 v15, [%1+13056];\n"
                 "lop3.b32 v0, v0, v1, %2, 0x7e; lop3.b32 v2, v2, v3, %2, 0x7e; lop3.b32 v4, v4, v5, %2, 0x7e; lop3.b32 v6, v6, v7, %2, 0x7e;\n"
                 "lop3.b32 v8, v8, v9, %2, 0x7e; lop3.b32 v10, v10, v11, %2, 0x7e; lop3.b32 v12, v12, v13, %2, 0x7e; lop3.b32 v14, v14, v15, %2, 0x7e;\n"
                 "lop3.b32 v0, v0, v2, v4, 0xfe; lop3.b32 v6, v6, v8, v10, 0xfe; lop3.b32 v0, v0, v6, v12, 0xfe; or.b32 %0, v0, v14;}"
                 : "=r"(r) : "r"(a), "r"(par) : "memory");
    return r;
}

__device__ __forceinline__ void wgmma128_rs(float (&d)[64], const uint32_t* a, uint64_t db, int scaleD) {
    asm volatile(
        "{ .reg .pred p; setp.ne.b32 p, %69, 0;\n"
        "wgmma.mma_async.sync.aligned.m64n128k16.f32.bf16.bf16 "
        "{%0,%1,%2,%3,%4,%5,%6,%7,%8,%9,%10,%11,%12,%13,%14,%15,%16,%17,%18,%19,%20,%21,%22,%23,%24,%25,%26,%27,%28,%29,%30,%31,"
        "%32,%33,%34,%35,%36,%37,%38,%39,%40,%41,%42,%43,%44,%45,%46,%47,%48,%49,%50,%51,%52,%53,%54,%55,%56,%57,%58,%59,%60,%61,%62,%63}, "
        "{%64,%65,%66,%67}, %68, p, 1, 1, 0;\n}"
        : "+f"(d[0]), "+f"(d[1]), "+f"(d[2]), "+f"(d[3]), "+f"(d[4]), "+f"(d[5]), "+f"(d[6]), "+f"(d[7]),
          "+f"(d[8]), "+f"(d[9]), "+f"(d[10]), "+f"(d[11]), "+f"(d[12]), "+f"(d[13]), "+f"(d[14]), "+f"(d[15]),
          "+f"(d[16]), "+f"(d[17]), "+f"(d[18]), "+f"(d[19]), "+f"(d[20]), "+f"(d[21]), "+f"(d[22]), "+f"(d[23]),
          "+f"(d[24]), "+f"(d[25]), "+f"(d[26]), "+f"(d[27]), "+f"(d[28]), "+f"(d[29]), "+f"(d[30]), "+f"(d[31]),
          "+f"(d[32]), "+f"(d[33]), "+f"(d[34]), "+f"(d[35]), "+f"(d[36]), "+f"(d[37]), "+f"(d[38]), "+f"(d[39]),
          "+f"(d[40]), "+f"(d[41]), "+f"(d[42]), "+f"(d[43]), "+f"(d[44]), "+f"(d[45]), "+f"(d[46]), "+f"(d[47]),
          "+f"(d[48]), "+f"(d[49]), "+f"(d[50]), "+f"(d[51]), "+f"(d[52]), "+f"(d[53]), "+f"(d[54]), "+f"(d[55]),
          "+f"(d[56]), "+f"(d[57]), "+f"(d[58]), "+f"(d[59]), "+f"(d[60]), "+f"(d[61]), "+f"(d[62]), "+f"(d[63])
        : "r"(a[0]), "r"(a[1]), "r"(a[2]), "r"(a[3]), "l"(db), "r"(scaleD));
}
__device__ __forceinline__ void ldsm4(uint32_t* r, uint32_t a) {
    asm volatile("ldmatrix.sync.aligned.m8n8.x4.shared.b16 {%0,%1,%2,%3}, [%4];" : "=r"(r[0]), "=r"(r[1]), "=r"(r[2]), "=r"(r[3]) : "r"(a) : "memory");
}

__device__ __forceinline__ int tile_of_step(int step, int own, int kh) {
    const int u = step >= 17 ? step - 17 : step - 1 - (step > OLS);
    int e = (u + (u >= ((own - 8 * kh) & 14) ? 2 : 0) + 8 * kh) & 15;
    if (u == 14) e = own ^ 1;
    if (step == 0 || step == OLS) e = own;
    return e + (step >= 17 || step == OLS ? 16 : 0);
}
__device__ __forceinline__ uint32_t router_key(float score, int row) {
    const float r = score + 0.0f;
    uint32_t u = pack_bf16(r, 0.f) & 0xffffu;
    u = (u & 0x8000u) ? (~u & 0xffffu) : (u | 0x8000u);
    if (r != r) u = 0;
    return (u << 16) | (uint32_t)(0x7fff - row);
}

#define g_fb_h ((float*)g_s.part)
#define g_fb_upd (g_fb_h + 2048)
#define g_fb_gate (g_fb_h + 4096)
#define g_fb_keys (g_s.part + 8192)
__global__ void fb_hidden(const bf16* x, const bf16* dre, const bf16* dim, const bf16* gw, const bf16* wr) {
    __shared__ float xs[D_];
    const int s = blockIdx.x, t = threadIdx.x;
    xs[t] = __bfloat162float(x[s * D_ + t]);
    __syncthreads();
    float a = 0.f, b = 0.f;
    for (int d = 0; d < D_; d++) { a = fmaf(xs[d], __bfloat162float(dre[t * D_ + d]), a); b = fmaf(xs[d], __bfloat162float(dim[t * D_ + d]), b); }
    ((bf16*)g_s.ab)[s * 1024 + t] = __float2bfloat16(a);
    ((bf16*)g_s.ab)[s * 1024 + 512 + t] = __float2bfloat16(b);
    if (t == 0) {
        float u = 0.f, v = 0.f;
        for (int d = 0; d < D_; d++) { u = fmaf(xs[d], __bfloat162float(gw[d]), u); v = fmaf(xs[d], __bfloat162float(wr[d]), v); }
        g_fb_gate[s] = sigmoidf_(u);
        g_fb_keys[s] = router_key(v, s);
    }
}
__device__ uint32_t fb_best() {
    uint32_t k = 0;
    for (int i = 0; i < S_; i++) k = max(k, g_fb_keys[i]);
    return k;
}
__global__ void fb_ffn1(const bf16* x, const bf16* wg, const bf16* wu) {
    const int f = blockIdx.x * blockDim.x + threadIdx.x, idx = 0x7fff - (int)(fb_best() & 0x7fffu);
    float a = 0.f, b = 0.f;
    for (int d = 0; d < D_; d++) {
        const float xv = __bfloat162float(x[idx * D_ + d]);
        a = fmaf(xv, __bfloat162float(wg[d * F_ + f]), a); b = fmaf(xv, __bfloat162float(wu[d * F_ + f]), b);
    }
    g_fb_h[f] = a * sigmoidf_(a) * b;
}
__global__ void fb_ffn2(const bf16* wd) {
    const int e = blockIdx.x * blockDim.x + threadIdx.x;
    const uint32_t u = fb_best() >> 16, rb = (u & 0x8000u) ? (u & 0x7fffu) : (~u & 0xffffu);
    float a = 0.f;
    for (int f = 0; f < F_; f++) a = fmaf(g_fb_h[f], __bfloat162float(wd[f * D_ + e]), a);
    g_fb_upd[e] = a * sigmoidf_(__uint_as_float(rb << 16));
}
__global__ void fb_seq(const bf16* x, const bf16* cre, const bf16* cim, bf16* out) {
    __shared__ float c[2][S_];
    __shared__ int idx;
    const int t = blockIdx.x, e = threadIdx.x;
    for (int i = e; i < S_; i += D_) { c[0][i] = __bfloat162float(cre[t * S_ + i]); c[1][i] = __bfloat162float(cim[t * S_ + i]); }
    if (e == 0) idx = 0x7fff - (int)(fb_best() & 0x7fffu);
    __syncthreads();
    float y = 0.f;
    for (int s = 0; s < S_; s++)
        y += c[0][s] * __bfloat162float(((const bf16*)g_s.ab)[s * 1024 + e]) - c[1][s] * __bfloat162float(((const bf16*)g_s.ab)[s * 1024 + 512 + e]);
    const float g = g_fb_gate[t];
    out[t * D_ + e] = __float2bfloat16(g * y + (1.f - g) * (__bfloat162float(x[t * D_ + e]) + (t == idx ? g_fb_upd[e] : 0.f)));
}

__device__ __forceinline__ void spare_job(const Params& p, unsigned char* smem, int sp, uint32_t tstart) {
    const int tid = threadIdx.x, warp = tid >> 5, lane = tid & 31;
    const uint32_t e1 = *(volatile unsigned int*)&p.s->epoch[NCTA + sp] + 1u;
    const uint32_t par = e1 & 1u;
    uint32_t* red = (uint32_t*)smem;
    __syncthreads();
    if (tid == 0) *(volatile unsigned int*)&p.s->epoch[NCTA + sp] = e1;
#pragma unroll 1
    for (int k = 0; k < 6; k++) {
        const char* src = k < 2 ? (const char*)p.wd + (sp * 2 + k) * 229376
                                : (const char*)((sp & 1) ? p.wu : p.wg) + ((sp >> 1) * 4 + k - 2) * 229376;
        while ((uint32_t)clock64() - tstart < PF_T0 + k * PF_DT) __nanosleep(LOWP ? 200 : 20);
        if (tid >= 448) {
            if (tid < 455) asm volatile("cp.async.bulk.prefetch.L2.global [%0], 16384;" ::"l"(src + (tid - 448) * 16384) : "memory");
        } else {
            prefetch_l2(src + 114688 + tid * 128);
            prefetch_l2(src + 172032 + tid * 128);
        }
        __syncwarp();
    }
    if (tid == 0) PROF(1);
    if (warp == 0) {
        const uint4 k4 = wait_tags(p.s->keys + lane * 4, 15, par);
        const uint32_t k = __reduce_max_sync(0xffffffffu, max(max(k4.x, k4.y), max(k4.z, k4.w)));
        const int idx = 0x7fff - (int)(k & 0x7fffu);
        const uint4 g4 = wait_tags(p.s->gate + (idx & ~3), 0, par);
        const uint32_t gw = (idx & 2) ? ((idx & 1) ? g4.w : g4.z) : ((idx & 1) ? g4.y : g4.x);
        const uint32_t u = k >> 16;
        const uint32_t rb = (u & 0x8000u) ? (u & 0x7fffu) : (~u & 0xffffu);
        if (lane == 0) {
            red[16] = idx;
            red[17] = __float_as_uint((1.f - __uint_as_float(gw & ~1u)) * sigmoidf_(__uint_as_float(rb << 16)));
        }
    }
    while ((uint32_t)clock64() - tstart < SUM_T0) __nanosleep(200);
    float4 s = make_float4(0.f, 0.f, 0.f, 0.f);
    if (warp < 14) {
        uint32_t n = 0;
        while ((int)(ld_relaxed(p.s->phint + (sp * 16 + warp) * 8) - e1 * 8u) < 0) {
            __nanosleep(40);
            if (++n > SPIN_LIMIT) __trap();
        }
        if (tid == 0) PROF(2);
        const unsigned int* src = p.s->part + warp * 4 * D_ + sp * 128 + lane * 4;
        uint4 v[4];
        while (true) {
            uint32_t bad = 0;
#pragma unroll
            for (int i = 0; i < 4; i++) v[i] = ld_relaxed4(src + i * D_);
#pragma unroll
            for (int i = 0; i < 4; i++) bad |= (v[i].x ^ par) | (v[i].y ^ par) | (v[i].z ^ par) | (v[i].w ^ par);
            if (!__any_sync(0xffffffffu, bad & 1u)) break;
            if (++n > SPIN_LIMIT) __trap();
        }
#pragma unroll
        for (int i = 0; i < 4; i++) {
            s.x += __uint_as_float(v[i].x); s.y += __uint_as_float(v[i].y);
            s.z += __uint_as_float(v[i].z); s.w += __uint_as_float(v[i].w);
        }
    } else if (warp == 14) {
        wait_counters<100>(p.s->ready + (lane & 7) * 32, e1 * 16u);
    }
    float* acc = (float*)(smem + 1024);
    *(float4*)&acc[warp * 128 + lane * 4] = s;
    __syncthreads();
    if (tid < 64) {
        float t0 = 0.f, t1 = 0.f;
#pragma unroll
        for (int i = 0; i < 14; i++) {
            const float2 z = *(const float2*)&acc[i * 128 + tid * 2];
            t0 += z.x; t1 += z.y;
        }
        const float f = __uint_as_float(red[17]);
        asm volatile("red.relaxed.gpu.global.add.noftz.bf16x2 [%0], %1;"
                     ::"l"(p.out + red[16] * D_ + sp * 128 + tid * 2), "r"(pack_bf16(t0 * f, t1 * f)) : "memory");
    }
}

__host__ __device__ constexpr int off_d(int c) { return (c < 2 ? 1 : c / 2 + 2) * REGION + (c & 1) * 16384; }
__host__ __device__ constexpr int off_xe(int c) { return (c < 2 ? 6 * REGION : c < 4 ? 16384 : c < 6 ? 0 : 6 * REGION + 16384) + (c & 1) * 8192; }
__host__ __device__ constexpr int off_xl(int c) { return c < 4 ? 2 * REGION + c * 8192 : off_xe(c - 4); }

__global__ void __cluster_dims__(2, 1, 1) __launch_bounds__(NTHREADS, 1)
fused_kernel(const __grid_constant__ Params p) {
    extern __shared__ __align__(1024) unsigned char smem[];
    const uint32_t tstart = (uint32_t)clock64();
    const uint32_t sb = smem_u32(smem);
    const int tid = threadIdx.x, lane = tid & 31;
    const int warp = __shfl_sync(0xffffffffu, tid >> 5, 0);
    const int rank = blockIdx.x & 1;
    uint32_t smid, role;
    asm volatile("mov.u32 %0, %%smid;" : "=r"(smid));
    asm("{.reg .pred p, q; .reg .u32 t, a, b; shr.u32 t, %1, 1; mad.lo.u32 a, t, 293, -928; shr.u32 a, a, 8; mad.lo.u32 b, t, 8, -464;"
        " setp.lt.u32 p, t, 32; setp.lt.u32 q, t, 62; selp.u32 a, a, b, q; selp.u32 %0, t, a, p;}" : "=r"(role) : "r"(smid));
    const int gpc = role & 7;
    const int tn = (role >> 3) & 3;
    const int kh = (role >> 5) & 1;
    const int comp = gpc & 1;
    const int xrow = kh * 1024 + (gpc >> 1) * 128 + rank * 64;
    constexpr int XLATE = 512;
    const CUtensorMap* mD = &p.mDre + comp;
    const int rot = ROT == 1 ? gpc & 6 : ROT == 2 ? (gpc & 2) * 2 : ROT == 3 ? gpc & 2 : ROT == 4 ? kh * 4 : 0;
    const int blk = role >> 3;
    const int own = gpc * 2 + rank;
    const int cta = gpc * 16 + blk * 2 + rank;
    const bool ffn = cta < FFN_CTAS;
    uint32_t epoch = 0;
    if (warp == 0 && role < 64) {
        mbar_init_elect(sb + B_F, 1);
        tma3d_elect(sb + off_d(0), mD, tn * 128, rot, sb + B_F);
        tma3d_elect(sb + off_xe(0), &p.mX1, xrow, rot, sb + B_F);
        mbar_expect_tx_elect(sb + B_F, 24576);
        const uint32_t t1 = (uint32_t)clock64();
#pragma unroll
        for (int c = 1; c < 9; c++) mbar_init_elect(sb + B_F + 8 * c, 1);
        asm volatile("bar.arrive 0, 512;" ::: "memory");
        asm volatile("barrier.cluster.arrive.relaxed.aligned;" ::: "memory");
#pragma unroll
        for (int c = 1; c < 8; c++) {
            if (PACE) while ((uint32_t)clock64() - t1 < c * PACE) {}
            tma3d_elect(sb + off_d(c), mD, tn * 128, c ^ rot, sb + B_F + 8 * c);
            tma3d_elect(sb + off_xe(c), &p.mX1, xrow, c ^ rot, sb + B_F + 8 * c);
            mbar_expect_tx_elect(sb + B_F + 8 * c, 24576);
            if (c == XL_AT) {
                tma3d_elect(sb + off_xl(0), &p.mX2, xrow + XLATE, 0 ^ rot, sb + B_G0);
                tma3d_elect(sb + off_xl(2), &p.mX2, xrow + XLATE, 2 ^ rot, sb + B_G0);
                mbar_expect_tx_elect(sb + B_G0, 32768);
            }
        }
        if (PFX && (blk & 3) < 2 && (KC ? blk < 4 : true)) {
            asm volatile("{.reg .pred p; elect.sync _|p, 0xffffffff; @p cp.async.bulk.prefetch.tensor.3d.L2.global [%0, {%1,%2,%3}];}"
                         ::"l"(&p.mX2), "r"(0), "r"(xrow + XLATE), "r"((4 + 2 * (blk & 1)) ^ rot) : "memory");
        }
    } else {
        if (role >= 64) {
            spare_job(p, smem, smid & 3, tstart);
            return;
        }
        const uint32_t b1 = sb + B_F + 8 * warp;
        if (warp < 4 || warp > 8) mbar_init_elect(warp < 4 ? b1 + 360 : b1, 1);
        mbar_init_elect(b1 + 120, warp < 7 ? 5 : warp < 14 ? 4 : 6);
        mbar_init_elect(b1 + 240, 1);
        if (warp == 9 || warp == 15) mbar_expect_tx_elect(b1 + 240, warp == 9 ? 2048 : 4);
        asm volatile("fence.mbarrier_init.release.cluster;" ::: "memory");
        if (tid == 128) epoch = *(volatile unsigned int*)&p.s->epoch[cta];
        asm volatile("bar.sync 0, 512;" ::: "memory");
        asm volatile("barrier.cluster.arrive.relaxed.aligned;" ::: "memory");
    }

    if (warp < 4) {
        if (warp == 0) {
            asm volatile("barrier.cluster.wait.acquire.aligned;" ::: "memory");
            PROF(2);
            mbar_spin(sb + B_XE, 0);
            tma3d_elect(sb + off_xl(4), &p.mX2, xrow + XLATE, 4 ^ rot, sb + B_G1);
            tma3d_elect(sb + off_xl(6), &p.mX2, xrow + XLATE, 6 ^ rot, sb + B_G1);
            mbar_expect_tx_elect(sb + B_G1, 32768);
            PROF(3);
            const int el = tile_of_step(lane, own, kh);
            const int taba = kh * 1024 + (el >> 2) * 128 + (el & 1) * 64 + ((el >> 1) & 1);
#define AMAP(c) &p.mCre + (c & 1), c & ~1
            const int tabb = (blk * 32 + el) * 128 + rank * 64;
            const uint32_t dst = sb + 16384 + rank * 8192;
#define LOAD_A() const int c = __shfl_sync(0xffffffffu, taba, step);                                            \
                 const uint32_t bar = sb + 8 * slot;                                                            \
                 mbar_spin(bar + B_EMPTY, ph);                                                                  \
                 tma2d_elect(sb + slot * REGION, AMAP(c), own * 128, bar + B_FULL); \
                 mbar_expect_tx_elect(bar + B_FULL, 16384)
            uint32_t slot = 0, ph = 0;
            int step = 0;
#pragma unroll 1
            for (; step < NSTAGE; step++, slot++) { LOAD_A(); PROFIF(step == 0 ? 4 : 5, step == 0 || step == 5); }
            slot = 0; ph = 1;
#pragma unroll 1
            for (int h = PE; h < 2; h++) {
#pragma unroll 1
                for (; step < 16 + 15 * h; step++) {
                    const int row = __shfl_sync(0xffffffffu, tabb, step);
                    LOAD_A();
                    if (step == 6 || step == 17) mbar_spin(sb + B_SEEN + (step >> 4) * 8, 0);
                    tma2d_pair_elect(dst + slot * REGION, &p.mAB, 0, row, bar + B_BL);
                    mbar_expect_tx_elect(bar + B_BL, 16384);
                    PROF(160 + step);
                    if (++slot == NSTAGE) { slot = 0; ph ^= 1; }
                }
                const int row = __shfl_sync(0xffffffffu, tabb, step);
                LOAD_A();
                tma2d_elect(dst + slot * REGION, &p.mAB, 0, row, bar + B_BL);
                tma2d_elect((dst ^ 8192) + slot * REGION, &p.mAB, 0, row ^ 64, bar + B_BL);
                mbar_expect_tx_elect(bar + B_BL, 16384);
                PROF(160 + step);
                step++; slot++;
            }
        } else if (warp == 1) {
            if (lane < 4) asm volatile("prefetch.tensormap [%0];" ::"l"(&p.mCre + lane) : "memory");
            __syncwarp();
            asm volatile("barrier.cluster.wait.acquire.aligned;" ::: "memory");
            if (lane == 0)
                asm volatile("st.async.weak.shared::cluster.mbarrier::complete_tx::bytes.u32 [%0], %1, [%2];"
                             ::"r"(mapa(sb + M_ROLE, rank ^ 1)), "r"(role), "r"(mapa(sb + B_ROLE, rank ^ 1)) : "memory");
            mbar_wait_cluster(sb + B_ROLE, 0);
            if (*(volatile uint32_t*)(smem + M_ROLE) != role) __trap();
            mbar_wait(sb + B_EPOCH, 0);
            const uint32_t want = *(volatile uint32_t*)(smem + M_EPOCH) + 1u;
            const int el = tile_of_step(lane, own, kh) & 15;
            const int tab = (blk * 32 + el) * 128 + rank * 64;
            const unsigned int* hp = p.s->hint + (blk * 8 + (el >> 1)) * 32 + (el & 1) * 2;
            uint2 st = ld_relaxed2(hp);
            const uint32_t wante = HINTM ? want * 4u : want;
            uint32_t seen = __ballot_sync(0xffffffffu, st.x == wante);
            mbar_wait(sb + B_EMPTY, 0);
#define POLL() { st = ld_relaxed2(hp); seen = __ballot_sync(0xffffffffu, st.x == wante); }
#pragma unroll 1
            for (int step = PE ? 3 : OLS == 1 ? 2 : 1; step < NSTAGE; step++) {
                const int row = __shfl_sync(0xffffffffu, tab, step);
                const uint32_t bar = sb + 8 * step;
                mbar_expect_tx_elect(bar + B_BL, 16384);
                while (!((seen >> step) & 1u)) POLL();
                const uint32_t due = __shfl_sync(0xffffffffu, st.y, step) + TSD;
                PROFIF(40, step == (PE ? 3 : 3 - OLS));
                mbar_spin(bar + B_EMPTY, 0);
                PROFIF(41, step == (PE ? 3 : 3 - OLS));
                if (!HINTM) while ((int)(gtime() - due) < 0) {}
                tma2d_pair_elect(sb + 16384 + rank * 8192 + step * REGION, &p.mAB, 0, row, bar + B_BL);
                PROF(160 + step);
                if (OLS == 2 && step == 1) step++;
            }
            mbar_wait(sb + B_FULL + 8 * OLS, 0);
            while (~seen) POLL();
            if (!HINTM) while (__any_sync(0xffffffffu, (int)(gtime() - st.y - TSD) < 0)) {}
            mbar_arrive_elect(sb + B_SEEN);
            PROF(7);
            unsigned char* gdst = p.s->ab + (blk * 32 + own + 16) * 16384;
            uint32_t t3 = (uint32_t)clock64() + OL_T0;
#pragma unroll 1
            for (int i = 0; i < 8; i++) {
                while ((int)((uint32_t)clock64() - t3) < 0) { if (LOWP) __nanosleep(64); }
                t3 += OL_DT;
                bulk_store_elect<2048>(gdst + i * 2048, sb + 6 * REGION + i * 2048);
            }
            bulk_wait_read();
            st_relaxed_if(p.s->hint + (blk * 8 + gpc) * 32 + 4 + rank, want, lane == 0);
            mbar_arrive_n_elect<4>(sb + B_FREE + 8);
            PROF(8);
            wait_counters<100>(hp + 4 - (el & 1), want);
            mbar_arrive_elect(sb + B_SEEN + 8);
            PROF(9);
            mbar_wait(sb + B_PUBI, 0);
            PROF(29);
            if (lane == 0) {
                if (TRED) fence_proxy_async_gmem();
                red_release_add(p.s->ready + blk * 32, 1);
            }
            __syncwarp();
            PROF(30);
            wait_counters<100>(p.s->ready + (lane & 7) * 32, want * 16u);
            mbar_arrive_elect(sb + B_INIT);
            PROF(10);
        } else {
            mbar_arrive_elect(sb + B_BL + 8 * OLS * (warp & 1));
            if (PE && warp == 2) {
                mbar_arrive_elect(sb + B_BL + 8);
                mbar_expect_tx_elect(sb + B_FULL + 8, 16384);
                mbar_arrive_n_elect<3>(sb + B_FULL + 8);
            }
            if (PFA_T && warp == 3) {
                const int e = tile_of_step(PFA_S + tn, own, kh);
                while ((uint32_t)clock64() - tstart < PFA_T) __nanosleep(20);
                if (lane == 0) tma2d_prefetch(&p.mCre + ((e >> 1) & 1), kh * 1024 + (e >> 2) * 128 + (e & 1) * 64, own * 128);
                __syncwarp();
            }
            mbar_wait(sb + B_EPOCH, 0);
            const uint32_t par = (*(volatile uint32_t*)(smem + M_EPOCH) + 1u) & 1u;
            const uint32_t a0 = sb + 16384 + (lane >> 3) * 1028 + ((lane >> 2) & 1) * 144 + (lane & 3) * 32;
            const int tab = (blk * 32 + tile_of_step(lane, own, kh)) * 128;
            const uint32_t retry = sb + B_RETRY + (warp & 1) * 240;
            uint32_t slot = PE ? 6 - warp : OLS == 1 ? warp : 10 - 3 * warp, ph = 0, rph = 0;
#pragma unroll 1
            for (int step = slot; step < 32; step += 2) {
                const uint32_t a = a0 + slot * REGION, bar = sb + 8 * slot;
                mbar_wait(bar + B_BL, ph);
                PROF(192 + step);
#pragma unroll 1
                while (__any_sync(0xffffffffu, stale_tags(a, par) & 1u)) {
                    const int row = __shfl_sync(0xffffffffu, tab, step);
                    mbar_expect_tx_elect(retry, 16384);
                    tma2d_elect(sb + slot * REGION + 16384, &p.mAB, 0, row, retry);
                    tma2d_elect(sb + slot * REGION + 24576, &p.mAB, 0, row + 64, retry);
                    mbar_spin(retry, rph);
                    rph ^= 1u;
                }
                mbar_arrive_n_elect<4>(bar + B_FULL);
                PROF(128 + step);
                const uint32_t j = step < FFN_S0 + 4 ? step - FFN_S0 : step < FFN_S1 ? 99 : step - FFN_S1 + 4;
                if (ffn && j < 12) {
                    if (!(j & 2)) mbar_wait(sb + B_FREE + 2 * (j & 12), 0);
                    const uint32_t fb = sb + B_FFN + (j < 4 ? 24 : 4 * (j & 14) - 16);
                    if (j == 0 || (j >= 4 && !(j & 1))) mbar_expect_tx_elect(fb, j ? 8192 : 16384);
                    tma2d_elect(sb + 6 * REGION + ((j + 4) & 7) * 4096, j < 4 ? &p.mWd : &p.mWg + (j & 1), j < 4 ? rank * 256 : (cta >> 1) * 32,
                                j < 4 ? (cta >> 1) * 32 + j * 8 : rank * 256 + (j >> 1) * 64 - 128, fb);
                }
                if (PFL && step == PFL) {
                    const int e = tile_of_step(28 + tn, own, kh);
                    if (lane == 0) tma2d_prefetch(&p.mCre + ((e >> 1) & 1), kh * 1024 + (e >> 2) * 128 + (e & 1) * 64, own * 128);
                    __syncwarp();
                }
                slot += 2;
                if (slot >= NSTAGE) { slot -= NSTAGE; ph ^= 1; }
            }
        }
    } else if (warp < 8) {
        const int t = tid - 128, w = warp - 4;
        if (t == 0) {
            *(volatile uint32_t*)(smem + M_EPOCH) = epoch;
            *(volatile unsigned int*)&p.s->epoch[cta] = epoch + 1;
            mbar_arrive(sb + B_EPOCH);
        }
        const uint4 gw0 = ldg_nc_off<0>(p.gate_w + lane * 8), gw1 = ldg_nc_off<512>(p.gate_w + lane * 8);
        const uint4 rw0 = ldg_nc_off<0>(p.w_r + lane * 8), rw1 = ldg_nc_off<512>(p.w_r + lane * 8);
        mbar_wait(sb + B_EPOCH, 0);
        const uint32_t par = (*(volatile uint32_t*)(smem + M_EPOCH) + 1u) & 1u;
        mbar_wait(sb + B_F + 8 * ROUTER_C, 0);
        const int row0 = cta * 16 + w * 4;
        uint4 xr[8];
        {
            const char* xp = (const char*)p.x + (uint32_t)row0 * (D_ * 2) + lane * 16;
            xr[0] = ldg_nc_off<0>(xp);    xr[1] = ldg_nc_off<512>(xp);  xr[2] = ldg_nc_off<1024>(xp); xr[3] = ldg_nc_off<1536>(xp);
            xr[4] = ldg_nc_off<2048>(xp); xr[5] = ldg_nc_off<2560>(xp); xr[6] = ldg_nc_off<3072>(xp); xr[7] = ldg_nc_off<3584>(xp);
            float a[8];
#pragma unroll
            for (int i = 0; i < 4; i++) {
                const uint32_t xv[8] = {xr[2 * i].x, xr[2 * i].y, xr[2 * i].z, xr[2 * i].w, xr[2 * i + 1].x, xr[2 * i + 1].y, xr[2 * i + 1].z, xr[2 * i + 1].w};
                const uint32_t gv[8] = {gw0.x, gw0.y, gw0.z, gw0.w, gw1.x, gw1.y, gw1.z, gw1.w};
                const uint32_t rv[8] = {rw0.x, rw0.y, rw0.z, rw0.w, rw1.x, rw1.y, rw1.z, rw1.w};
                float u = 0.f, v = 0.f;
#pragma unroll
                for (int j = 0; j < 8; j++) {
                    u = fmaf(bflo(xv[j]), bflo(gv[j]), u); u = fmaf(bfhi(xv[j]), bfhi(gv[j]), u);
                    v = fmaf(bflo(xv[j]), bflo(rv[j]), v); v = fmaf(bfhi(xv[j]), bfhi(rv[j]), v);
                }
                a[i] = u; a[4 + i] = v;
            }
            if (RSPLIT) mbar_wait(sb + B_FULL + 8 * (RSPLIT - 1), 0);
            halve<4, 16>(a); halve<2, 8>(a); halve<1, 4>(a);
            a[0] += __shfl_xor_sync(0xffffffffu, a[0], 1);
            a[0] += __shfl_xor_sync(0xffffffffu, a[0], 2);
            const int row = row0 + ((lane >> 2) & 3);
            const float gate = sigmoidf_(a[0]);
            if (lane < 16 && (lane & 3) == 0) st_relaxed(&p.s->gate[row], tagf(gate, par));
            const uint32_t best = __reduce_max_sync(0xffffffffu, lane >= 16 ? router_key(a[0], row) : 0u);
            if (lane == 0) *(volatile uint32_t*)(smem + M_RED + w * 4) = best;
            named_bar(1, 128);
            if (t < 8) {
                const uint4 k = *(const uint4*)(smem + M_RED);
                st_key(&p.s->keys[t * NCTA + cta], max(max(k.x, k.y), max(k.z, k.w)) | (par << 15));
            }
            PROFIF(11, t == 0);
            const uint32_t og = pack_bf16(1.f - gate, 1.f - gate);
#pragma unroll
            for (int i = 0; i < 8; i++) {
                const uint32_t o = __shfl_sync(0xffffffffu, og, 4 * (i >> 1));
                xr[i] = make_uint4(hmul2_bf16(o, xr[i].x), hmul2_bf16(o, xr[i].y), hmul2_bf16(o, xr[i].z), hmul2_bf16(o, xr[i].w));
            }
        }
        mbar_wait(sb + B_FULL + 8 * OLS, 0);
        if (w == 0) {
            const uint4 k4 = wait_tags(p.s->keys + gpc * NCTA + lane * 4, 15, par);
            const uint32_t k = __reduce_max_sync(0xffffffffu, max(max(k4.x, k4.y), max(k4.z, k4.w)));
            sts128(sb + M_UPD + lane * 16, ldg_nc_off<0>(p.x + (0x7fff - (k & 0x7fffu)) * D_ + rank * 256 + lane * 8));
        } else if (w == 1) {
            const uint4 g4 = wait_tags(p.s->gate + own * 128 + lane * 4, 0, par);
            *(uint4*)(smem + M_G + lane * 16) = make_uint4(g4.x & ~1u, g4.y & ~1u, g4.z & ~1u, g4.w & ~1u);
            mbar_arrive_warp(sb + B_GATE);
        }
        char* op = (char*)p.out + (uint32_t)row0 * (D_ * 2) + lane * 16;
        float a[16];
        uint32_t vd[32];
#pragma unroll
        for (int i = 0; i < 16; i++) a[i] = 0.f;
        if (ffn) mbar_wait(sb + B_FFN + 24, 0);
#pragma unroll
        for (int i = 0; i < 32; i++) vd[i] = *(const volatile uint32_t*)(smem + 6 * REGION + 16384 + i * 512 + t * 4);
        named_bar(1, 128);
        mbar_arrive_if(sb + B_VD, t == 0);
        PROFIF(13, t == 0);
        mbar_wait(sb + B_FREE + 8, 0);
        const uint32_t t2 = (uint32_t)clock64();
#pragma unroll
        for (int j = 0; j < 4; j++) {
            while ((uint32_t)clock64() - t2 < INIT_T0 + j * INIT_DT) __nanosleep(LOWP ? 100 : 20);
            *(uint4*)(op + j * 512) = xr[j];
        }
#pragma unroll 1
        for (int i = 0; i < 4; i++) {
            if (ffn) {
                const float xs0 = __bfloat162float(((const bf16*)(smem + M_UPD))[64 * i + (t >> 2)]);
                const float xs1 = __bfloat162float(((const bf16*)(smem + M_UPD))[64 * i + 32 + (t >> 2)]);
                const uint32_t wa = sb + 6 * REGION + i * 8192 + t * 16;
                mbar_wait(sb + B_FFN + 8 * i, i == 3);
                const uint4 v0 = lds128(wa), v1 = lds128(wa + 4096), v2 = lds128(wa + 2048), v3 = lds128(wa + 6144);
                const uint32_t w0[8] = {v0.x, v0.y, v0.z, v0.w, v1.x, v1.y, v1.z, v1.w};
                const uint32_t w1[8] = {v2.x, v2.y, v2.z, v2.w, v3.x, v3.y, v3.z, v3.w};
#pragma unroll
                for (int k = 0; k < 8; k++) {
                    a[2 * k] = fmaf(xs1, bflo(w1[k]), fmaf(xs0, bflo(w0[k]), a[2 * k]));
                    a[2 * k + 1] = fmaf(xs1, bfhi(w1[k]), fmaf(xs0, bfhi(w0[k]), a[2 * k + 1]));
                }
            } else {
                __nanosleep(300);
            }
            if (i < 2) {
                *(uint4*)(op + 2048 + i * 1024) = xr[4];
                *(uint4*)(op + 2560 + i * 1024) = xr[5];
                xr[4] = xr[6]; xr[5] = xr[7];
                if (i == 1) mbar_arrive_warp(sb + B_PUBI);
            }
        }
        PROFIF(14, t == 0);
        if (ffn) {
            halve<8, 16>(a); halve<4, 8>(a); halve<2, 4>(a);
            const uint32_t ho = (lane >> 4) * 128 + (lane & 3) * 32 + ((lane >> 2) & 3) * 8;
            asm volatile("barrier.cluster.wait.acquire.aligned;" ::: "memory");
#pragma unroll
            for (int k = 0; k < 2; k++)
                asm volatile("st.async.weak.shared::cluster.mbarrier::complete_tx::bytes.v2.f32 [%0], {%1,%2}, [%3];"
                             ::"r"(mapa(sb + (k ? 6 * REGION + w * 512 : M_HX + w * 256) + ho, rank ^ k ^ 1)), "f"(a[0]), "f"(a[1]),
                               "r"(mapa(sb + B_HX, rank ^ k ^ 1)) : "memory");
            mbar_wait_cluster(sb + B_HX, 0);
            const float *hx = (const float*)(smem + M_HX) + lane, *hy = (const float*)(smem + 6 * REGION) + lane;
            const float gs = ((hx[0] + hy[0]) + (hx[64] + hy[128])) + ((hx[128] + hy[256]) + (hx[192] + hy[384]));
            const float us = ((hx[32] + hy[32]) + (hx[96] + hy[160])) + ((hx[160] + hy[288]) + (hx[224] + hy[416]));
            float* hrow = (float*)(smem + 6 * REGION + 256) + w * 128;
            hrow[lane] = gs * sigmoidf_(gs) * us;
            __syncwarp();
            float o0 = 0.f, o1 = 0.f;
#pragma unroll
            for (int j4 = 0; j4 < 8; j4++) {
                const float4 hv = *(const float4*)&hrow[j4 * 4];
                o0 = fmaf(hv.x, bflo(vd[4 * j4]), o0);     o1 = fmaf(hv.x, bfhi(vd[4 * j4]), o1);
                o0 = fmaf(hv.y, bflo(vd[4 * j4 + 1]), o0); o1 = fmaf(hv.y, bfhi(vd[4 * j4 + 1]), o1);
                o0 = fmaf(hv.z, bflo(vd[4 * j4 + 2]), o0); o1 = fmaf(hv.z, bfhi(vd[4 * j4 + 2]), o1);
                o0 = fmaf(hv.w, bflo(vd[4 * j4 + 3]), o0); o1 = fmaf(hv.w, bfhi(vd[4 * j4 + 3]), o1);
            }
            asm volatile("st.relaxed.gpu.global.v2.u32 [%0], {%1,%2};" ::"l"(&p.s->part[(cta >> 1) * D_ + rank * 256 + t * 2]),
                         "r"(tagf(o0, par)), "r"(tagf(o1, par)) : "memory");
            if (lane == 0) asm volatile("red.relaxed.gpu.global.add.u32 [%0], 1;" ::"l"(p.s->phint + ((rank * 2 + (w >> 1)) * 16 + (cta >> 3)) * 8) : "memory");
            PROFIF(15, t == 0);
        }
    } else {
        const int wg = (warp >> 2) - 2, wq = warp & 3;
        const uint32_t sbd = (sb & 0x3FFFF) >> 4;
        const bool lead = (tid & 127) == 0;
        const bool lead0 = lead && !wg, lead1 = lead && wg;
        const int q = lane & 3;
        float acc[64];
        const uint32_t rE = mapa(sb + B_EMPTY, rank ^ 1);
#define RELEASE(n, slot, pred) release_pair<n>(sb + B_EMPTY + 8 * (slot), rE + 8 * (slot), pred)
        const uint32_t img = sb + 6 * REGION + (wg ? 0 : 16384) + wq * 4096;
        const uint32_t sdst = pin(img + (lane >> 2) * 64 + ((q ^ (lane >> 3)) << 4));
        unsigned char* gdst = pin_uniform(p.s->ab + ((blk * 32 + own) * 4 + wq) * 4096);
        unsigned char* gd2 = pin(gdst + (sdst - img));
        unsigned int* hint = pin(p.s->hint + (blk * 8 + gpc) * 32 + rank * 2);
        uint32_t e1 = 0;
        asm volatile("barrier.cluster.wait.acquire.aligned;" ::: "memory");
        if (wg) {
            mbar_spin(sb + B_G0, 0);
            PROFIF(20, lead);
            mbar_spin(sb + B_GO1, 0);
        }
#pragma unroll
        for (int c = RS1 ? 2 : 0; c < 8; c++) {
            mbar_spin(sb + (c == 4 && wg ? B_G1 : PAUSE && c == 1 && wg ? B_XE : B_F + 8 * c), PAUSE && c == 1 && wg);
            if (c == 0) { PROFIF(16 + 5 * wg, lead); PROFL(0); }
            wg_fence();
#pragma unroll
            for (int kk = 0; kk < 4; kk++) {
                wgmma128<0>(acc, desc_lo(sbd + 0x10000 + (wg ? off_xl(c) : off_xe(c)) / 16 + 2 * kk), desc_lo(sbd + 0x10000 + off_d(c) / 16 + 2 * kk), (c | kk) != 0);
                if (c == 7 && kk == GOK - 1) wg_commit();
            }
            wg_commit();
            if (c == 3) {
                mbar_spin(sb + B_EPOCH, 0);
                e1 = *(volatile uint32_t*)(smem + M_EPOCH) + 1u;
            }
            if (c == 7 && wg) mbar_spin(sb + B_FULL, 0);
            if (c >= 2 && c != 3 && c != 5) wg_wait<1>();
            if (c == 2) RELEASE(2, 1, lead1);
            if (c == 4) { mbar_arrive_if(sb + B_XE, lead0); RELEASE(2, 2, lead1); RELEASE(2, 3, lead1); }
            if (c == 6 && !HINTM) st_stamp_if(hint, e1, lead0);
            if (c == 6) RELEASE(2, 4 * wg, lead);
            if (c == 7) mbar_arrive_if(sb + B_GO1 + 8 * wg, lead);
        }
        const uint32_t neg = comp && !KC ? 0x80008000u : 0u, negp = neg | (e1 & 1u);
        const int rh = RSW ? wg ^ kh : wg;
        const uint32_t da0 = sbd + 0x10000 + rh * 512, db0 = sbd + 0x400000 + 1024;
#define STEP(da, db, first) wg_fence();                                                                     \
        _Pragma("unroll") for (int kk = 0; kk < 4; kk++)                                                    \
            wgmma128(acc, desc_lo((da) + kk * 2), desc64_lo((db) + kk * 256), !((first) && kk == 0));       \
        wg_commit()
#define PROFSTEP(s) PROFIF(64 + wg * 32 + (s), lead)
        const uint32_t dbe = db0 + 6 * (REGION / 16), dbl = dbe - 1024;
#define PW(i, j) pack_bf16(acc[16 * ((i) >> 1) + 2 * ((i) & 1) + 4 * (j)], acc[16 * ((i) >> 1) + 2 * ((i) & 1) + 4 * (j) + 1])
#define PT(i, j) ((j) == ((i) >> 1) ? (PW(i, j) & ~1u) ^ negp : PW(i, j) ^ neg)
#define PIECE(i) make_uint4(PT(i, 0), PT(i, 1), PT(i, 2), PT(i, 3))
        if (wg) {
            wg_wait<0>();
            fence_regs<0, 64>(acc);
            PROFIF(22, lead); PROFL(1);
#define STS1(i) sts128_off<(i) * 512>(sdst, PIECE(i))
            STS1(0); STS1(1); STS1(2); STS1(3); STS1(4); STS1(5); STS1(6); STS1(7);
            if (W1FIRST == 1) { PROFL(3); STEP(da0, dbe, true); }
            fence_proxy_async_smem();
            __syncwarp();
            mbar_arrive_if(sb + B_FULL + 8 * OLS, lane == 0);
            PROFL(2);
            if (!W1FIRST) { PROFL(3); STEP(da0, dbe, true); }
            PROFIF(23, lead);
            RELEASE(1, 5, lead);
        } else {
            wg_wait<0>();
            fence_regs<0, 64>(acc);
            PROFIF(17, lead); PROFL(1);
            uint4 v[8];
#define STG0(i) v[i] = PIECE(i); stg_off<(i) * 512>(gd2, v[i]); red_inc_if(hint, HINTM == (i) + 1 && lane == 0); if (PAUSE == (i) + 1) mbar_arrive_if(sb + B_XE, lead)
            STG0(0); STG0(1); STG0(2); STG0(3); STG0(4); STG0(5); STG0(6); STG0(7);
            PROFIF(48 + wq, lane == 0);
#define STS0(i) if (THR && (i) % THR == 0) mbar_spin(sb + B_EPOCH, 0); sts128_off<(i) * 512>(sdst, v[i])
            STS0(0); STS0(1); STS0(2); STS0(3); STS0(4); STS0(5); STS0(6); STS0(7);
            if (PE) mbar_spin(sb + B_EMPTY + 8, 0);
            fence_proxy_async_smem();
            __syncwarp();
            if (PE)
                asm volatile("{.reg .pred p; elect.sync _|p, 0xffffffff;"
                             " @p cp.async.bulk.shared::cluster.shared::cta.mbarrier::complete_tx::bytes [%0], [%1], 4096, [%2];}"
                             ::"r"(rE - B_EMPTY + REGION + 16384 + wq * 4096), "r"(img), "r"(rE - B_EMPTY + B_FULL + 8) : "memory");
            mbar_arrive_if(sb + B_FULL, lane == 0);
            PROFIF(19, lead); PROFL(2);
            RELEASE(1, 5, lead);
            mbar_arrive_if(sb + B_FREE, lane == 0);
            mbar_spin(sb + B_FULL, 0);
            mbar_spin(sb + B_SKEW0, 0);
            PROFSTEP(0); PROFL(3);
            STEP(da0, dbe, true);
        }
#pragma unroll
        for (int step = 1; step < 4; step++) {
            mbar_spin(sb + B_FULL + 8 * step, 0);
            PROFSTEP(step); PROFL(3 + step);
            STEP(da0 + step * (REGION / 16), step == OLS ? dbl : db0 + step * (REGION / 16), false);
            wg_wait<1>();
            RELEASE(1, step - 1, lead);
            if (step == 1) mbar_arrive_if(sb + B_FREE, lead);
            if (step == OLS + 1) mbar_arrive_if(sb + B_FREE + 8, lead);
        }
        PROFL(7);
        int slot = 4, ph = 0, pslot = 3;
#pragma unroll 1
        for (int step = 4; step < 26; step++) {
            mbar_wait(sb + B_FULL + 8 * slot, ph);
            PROFSTEP(step);
            STEP(da0 + slot * (REGION / 16), db0 + slot * (REGION / 16), false);
            wg_wait<1>();
            RELEASE(1, pslot, lead);
            pslot = slot;
            if (++slot == NSTAGE) { slot = 0; ph ^= 1; }
        }
        PROFL(8);
        float g0 = 0.f, g1 = 0.f;
        char* op = nullptr;
        const int r0 = rh * 64 + wq * 16 + (lane >> 2);
        const bool odd = lane & 4;
#define OUT_SETUP() mbar_wait(sb + B_GATE, 0);                                                              \
        g0 = ((const volatile float*)(smem + M_G))[r0];                                                     \
        g1 = ((const volatile float*)(smem + M_G))[r0 + 8];                                                 \
        if (KC && comp) { g0 = -g0; g1 = -g1; }                                                             \
        op = pin((char*)p.out + (uint32_t)((own * 128 + (SHUF ? r0 & ~1 : r0)) * D_ + tn * 128 + (lane & (SHUF ? 7 : 3)) * 8) * 2u)
        if (SK == 6 && wg) {
            wg_wait<0>();
        } else {
            mbar_wait(sb + B_FULL + 8 * 2, 0);
            STEP(da0 + 2 * (REGION / 16), db0 + 2 * (REGION / 16), false);
            wg_wait<1>();
            slot = 3;
        }
        RELEASE(1, 1, lead);
#pragma unroll 1
        for (int step = 24 + slot; step < 32; step++) {
            if (step == (wg ? 32 - SK : 30)) {
                OUT_SETUP();
                mbar_wait(sb + (wg ? B_TAIL : B_INIT), 0);
            }
            if (!wg || step < 32 - SK) mbar_wait(sb + B_FULL + 8 * slot, ph);
            STEP(da0 + slot * (REGION / 16), db0 + slot * (REGION / 16), false);
            if (++slot == NSTAGE) { slot = 0; ph ^= 1; }
        }
        if (!wg) {
            wg_wait<1>();
            mbar_arrive_if(sb + B_TAIL, lead);
        }
        if (!wg || TRED == 2) {
            const int sr = ((lane >> 2) & 1) * 4 + (lane >> 3);
            const uint32_t st0 = sb + rh * 8192 + wq * 2048, sa = st0 + sr * 128 + ((q ^ sr) << 4);
            wg_wait<0>();
            fence_regs<0, 64>(acc);
            PROFIF(24 + 2 * wg, lead); PROFL(9);
#define OW(i, j) pack_bf16((((i) & 1) ? g1 : g0) * acc[16 * ((i) >> 1) + 2 * ((i) & 1) + 4 * (j)], (((i) & 1) ? g1 : g0) * acc[16 * ((i) >> 1) + 2 * ((i) & 1) + 4 * (j) + 1])
#define OSTS(i) sts128_off<((i) >> 2) * REGION + ((i) & 1) * 1024>(((i) & 2) ? sa ^ 64 : sa, make_uint4(OW(i, 0), OW(i, 1), OW(i, 2), OW(i, 3)))
#define ORED(h) fence_proxy_async_smem(); __syncwarp();                                                     \
            asm volatile("{.reg .pred p; elect.sync _|p, 0xffffffff;"                                       \
                         " @p cp.reduce.async.bulk.tensor.4d.global.shared::cta.add.tile.bulk_group [%0, {%2,%3,%3,%4}], [%1];}" \
                         ::"l"(&p.mOut), "r"(st0 + (h) * REGION), "r"(tn * 128 + (h) * 64), "r"(0), "r"(own * 16 + rh * 8 + wq * 2) : "memory")
            OSTS(0); OSTS(1); OSTS(2); OSTS(3);
            ORED(0);
            OSTS(4); OSTS(5); OSTS(6); OSTS(7);
            ORED(1);
            bulk_wait_read();
        } else {
        char* opb = op + (odd ? 1024 - 64 : 1024 + 64);
        wg_wait<0>();
        fence_regs<0, 64>(acc);
        PROFIF(24 + 2 * wg, lead); PROFL(9);
        uint32_t k[4][4], r[4][4];
#define PACKLINE(i) _Pragma("unroll") for (int j = 0; j < 4; j++) {                                         \
            const int o = 32 * ((i) >> 1) + 2 * ((i) & 1) + 4 * j;                                          \
            const float g = ((i) & 1) ? g1 : g0;                                                            \
            r[i][j] = __shfl_xor_sync(0xffffffffu, pack_bf16(g * acc[o + 16], g * acc[o + 17]), 4);         \
            k[i][j] = pack_bf16(g * acc[o], g * acc[o + 1]); }
#define REDLINE(i)                                                                                          \
        red_bf16x8<((i) & 1) * 8192 + ((i) >> 1) * 128>(op, odd ? r[i][0] : k[i][0], odd ? r[i][1] : k[i][1], odd ? r[i][2] : k[i][2], odd ? r[i][3] : k[i][3]); \
        red_bf16x8<((i) & 1) * 8192 + ((i) >> 1) * 128>(opb, odd ? k[i][0] : r[i][0], odd ? k[i][1] : r[i][1], odd ? k[i][2] : r[i][2], odd ? k[i][3] : r[i][3])
        PACKLINE(0) __syncwarp(); PACKLINE(1) __syncwarp();
        REDLINE(0); __syncwarp(); PACKLINE(2) __syncwarp();
        REDLINE(1); __syncwarp(); PACKLINE(3) __syncwarp();
        REDLINE(2); REDLINE(3);
        }
    }
}

typedef CUresult (*EncodeTiledFn)(CUtensorMap*, CUtensorMapDataType, cuuint32_t, void*, const cuuint64_t*, const cuuint64_t*,
                                  const cuuint32_t*, const cuuint32_t*, CUtensorMapInterleave, CUtensorMapSwizzle,
                                  CUtensorMapL2promotion, CUtensorMapFloatOOBfill);

static void make_map(EncodeTiledFn enc, CUtensorMap* m, const void* base, uint64_t cols, uint64_t rows, uint32_t box_rows,
                     CUtensorMapSwizzle sw = CU_TENSOR_MAP_SWIZZLE_128B, uint32_t box_cols = 64,
                     CUtensorMapL2promotion promo = CU_TENSOR_MAP_L2_PROMOTION_L2_128B) {
    cuuint64_t dims[2] = {cols, rows};
    cuuint64_t str[1] = {cols * 2};
    cuuint32_t box[2] = {box_cols, box_rows};
    cuuint32_t es[2] = {1, 1};
    enc(m, CU_TENSOR_MAP_DATA_TYPE_BFLOAT16, 2, (void*)base, dims, str, box, es, CU_TENSOR_MAP_INTERLEAVE_NONE,
        sw, promo, CU_TENSOR_MAP_FLOAT_OOB_FILL_NONE);
}

static void make_map_chunks(EncodeTiledFn enc, CUtensorMap* m, const void* base, uint64_t rows, uint32_t box_rows, uint32_t n = 1) {
    cuuint64_t dims[3] = {64, rows, 8};
    cuuint64_t str[2] = {D_ * 2, 128};
    cuuint32_t box[3] = {64, box_rows, n};
    cuuint32_t es[3] = {1, 1, 1};
    enc(m, CU_TENSOR_MAP_DATA_TYPE_BFLOAT16, 3, (void*)base, dims, str, box, es, CU_TENSOR_MAP_INTERLEAVE_NONE,
        CU_TENSOR_MAP_SWIZZLE_128B, CU_TENSOR_MAP_L2_PROMOTION_L2_128B, CU_TENSOR_MAP_FLOAT_OOB_FILL_NONE);
}

static void make_map_out(EncodeTiledFn enc, CUtensorMap* m, const void* base) {
    cuuint64_t dims[4] = {D_, 4, 2, S_ / 8};
    cuuint64_t str[3] = {2 * D_ * 2, D_ * 2, 8 * D_ * 2};
    cuuint32_t box[4] = {64, 4, 2, 2};
    cuuint32_t es[4] = {1, 1, 1, 1};
    enc(m, CU_TENSOR_MAP_DATA_TYPE_BFLOAT16, 4, (void*)base, dims, str, box, es, CU_TENSOR_MAP_INTERLEAVE_NONE,
        CU_TENSOR_MAP_SWIZZLE_128B, CU_TENSOR_MAP_L2_PROMOTION_NONE, CU_TENSOR_MAP_FLOAT_OOB_FILL_NONE);
}

extern "C" void kernel_launch(void* const* d_in, const int* in_sizes, int n_in, void* d_out, int out_size) {
    (void)in_sizes; (void)n_in; (void)out_size;
    static EncodeTiledFn enc = nullptr;
    static bool fused_ok = false;
    static void* ab_ptr = nullptr;
    if (!enc) {
        void* fn = nullptr;
        cudaDriverEntryPointQueryResult q;
        cudaGetDriverEntryPoint("cuTensorMapEncodeTiled", &fn, cudaEnableDefault, &q);
        enc = (EncodeTiledFn)fn;
        cudaGetSymbolAddress(&ab_ptr, g_s);
        cudaFuncSetAttribute(fused_kernel, cudaFuncAttributeMaxDynamicSharedMemorySize, SMEM_BYTES);
        int dev = 0, nsm = 0, ncl = 0;
        cudaGetDevice(&dev);
        cudaDeviceGetAttribute(&nsm, cudaDevAttrMultiProcessorCount, dev);
        cudaLaunchConfig_t cfg = {};
        cfg.gridDim = dim3(132); cfg.blockDim = dim3(NTHREADS); cfg.dynamicSmemBytes = SMEM_BYTES;
        cudaLaunchAttribute at;
        at.id = cudaLaunchAttributeClusterDimension;
        at.val.clusterDim.x = 2; at.val.clusterDim.y = 1; at.val.clusterDim.z = 1;
        cfg.attrs = &at; cfg.numAttrs = 1;
        fused_ok = cudaOccupancyMaxActiveClusters(&ncl, fused_kernel, &cfg) == cudaSuccess && nsm == 132 && ncl == 66;
        (void)cudaGetLastError();
    }
    if (!fused_ok) {
        const bf16* const* in = (const bf16* const*)d_in;
        fb_hidden<<<S_, D_, 0, cudaStreamPerThread>>>(in[0], in[3], in[4], in[10], in[6]);
        fb_ffn1<<<F_ / 128, 128, 0, cudaStreamPerThread>>>(in[0], in[7], in[8]);
        fb_ffn2<<<D_ / 64, 64, 0, cudaStreamPerThread>>>(in[9]);
        fb_seq<<<S_, D_, 0, cudaStreamPerThread>>>(in[0], in[1], in[2], (bf16*)d_out);
        return;
    }
    Params p;
    p.s = (Scratch*)ab_ptr;
    p.x = (const bf16*)d_in[0];
    p.w_r = (const bf16*)d_in[6];
    p.wg = (const bf16*)d_in[7];
    p.wu = (const bf16*)d_in[8];
    p.wd = (const bf16*)d_in[9];
    p.gate_w = (const bf16*)d_in[10];
    p.out = (bf16*)d_out;
    make_map_chunks(enc, &p.mX1, d_in[0], S_, 64);
    make_map_chunks(enc, &p.mX2, d_in[0], S_, 64, 2);
    make_map(enc, &p.mCre, d_in[1], S_, S_, 128);
    make_map(enc, &p.mCim, d_in[2], S_, S_, 128);
    make_map_chunks(enc, &p.mDre, d_in[3], D_, 128);
    make_map_chunks(enc, &p.mDim, d_in[4], D_, 128);
    make_map(enc, &p.mAB, ab_ptr, 64, 8 * 32 * 128, 64, CU_TENSOR_MAP_SWIZZLE_NONE);
    make_map_out(enc, &p.mOut, d_out);
    make_map(enc, &p.mWg, d_in[7], F_, D_, 64, CU_TENSOR_MAP_SWIZZLE_NONE, 32, CU_TENSOR_MAP_L2_PROMOTION_NONE);
    make_map(enc, &p.mWu, d_in[8], F_, D_, 64, CU_TENSOR_MAP_SWIZZLE_NONE, 32, CU_TENSOR_MAP_L2_PROMOTION_NONE);
    make_map(enc, &p.mWd, d_in[9], D_, F_, 8, CU_TENSOR_MAP_SWIZZLE_NONE, 256);
    fused_kernel<<<132, NTHREADS, SMEM_BYTES, cudaStreamPerThread>>>(p);
}
```

```cpp
#include <cuda_runtime.h>
#include <cuda.h>
#include <cuda_bf16.h>
#include <stdint.h>

typedef __nv_bfloat16 bf16;

#define PACE 250
#define PE 0
#define OLS 1
#define HINT_AT 400
#define PRIO 0
#define SK 5
#define PF_T0 3000
#define PF_DT 1700
#define FFN_S0 4
#define FFN_S1 11
#define NI0 0
#define INIT_T0 0
#define INIT_DT 400
#define W1FIRST 0
#define THR 1
#define TSD 1500
#define KC 1
#define PAUSE 0
#define PFA_T 0
#define PFA_S 0
#define HINTM 5
#define GOK 1
#define PFX 1
#define ROT 0
#define LOWP 1
#define PFL 0
#define TRED 1
#define RSW 1
#define MAP4 1
#define PFD 1
#define PF_N0 3
#define FW0 7
#define FW1 3
#define VDT 0
#define WPROMO CU_TENSOR_MAP_L2_PROMOTION_L2_128B
#define GO0 1
#define NC0 2
#define FAST0 1
#define PK 8
#define PACE2 200
#define PTIME(c) ((c) <= PK ? (c) * PACE : PK * PACE + ((c) - PK) * PACE2)
#define ESTG 5
#define XL_AT 7
#define PD0 500
#define PD1 200
#define OL_T0 0
#define OL_DT 400
#define RS1 0
#define RSPLIT 1
#define GO_LATE 0
#define SUM_T0 15000
#define ROUTER_C 3
#define SHUF 1
#define POLL_NS 100

constexpr int S_ = 2048, D_ = 512, F_ = 1792;
constexpr int NCTA = 128;
constexpr int NTHREADS = 512;
constexpr int NSTAGE = 6;
constexpr int REGION = 32768;
constexpr int FFN_CTAS = F_ / 16;
constexpr uint32_t SPIN_LIMIT = 1u << 22;

constexpr int OFF_MISC = 7 * REGION;
constexpr int B_F = OFF_MISC;
constexpr int B_G0 = B_F + 64;
constexpr int B_G1 = B_G0 + 8;
constexpr int B_XE = B_G1 + 8;
constexpr int B_GO1 = B_XE + 8;
constexpr int B_SKEW0 = B_GO1 + 8;
constexpr int B_EPOCH = B_SKEW0 + 8;
constexpr int B_RETRY = B_EPOCH + 8;
constexpr int B_INIT = B_RETRY + 8;
constexpr int B_FULL = B_INIT + 8;
constexpr int B_EMPTY = B_FULL + 48;
constexpr int B_PUBI = B_EMPTY + 48;
constexpr int B_FREE = B_PUBI + 8;
constexpr int B_VD = B_FREE + 16;
constexpr int B_BL = B_VD + 8;
constexpr int B_TAIL = B_BL + 48;
constexpr int B_HX = B_TAIL + 8;
constexpr int B_FFN = B_HX + 8;
constexpr int B_ROLE = B_FFN + 40;
constexpr int B_SEEN = B_ROLE + 8;
constexpr int B_GATE = B_SEEN + 16;
constexpr int B_G2 = B_GATE + 8;
constexpr int M_EPOCH = B_G2 + 8;
constexpr int M_ROLE = M_EPOCH + 4;
constexpr int M_RED = OFF_MISC + 416;
constexpr int M_HX = OFF_MISC + 512;
constexpr int M_G = M_HX + 1024;
constexpr int M_UPD = M_G + 512;
constexpr int M_PROF = M_UPD + 512;
constexpr int SMEM_BYTES = 232448;
static_assert(M_ROLE + 4 <= M_RED && M_UPD + 512 <= SMEM_BYTES, "smem");

struct Scratch {
    unsigned char ab[8 * 32 * 16384];
    unsigned int hint[8 * 8 * 32];
    unsigned int ready[8 * 32];
    unsigned int gate[S_];
    unsigned int part[FFN_CTAS / 2 * D_];
    unsigned int phint[4 * 16 * 8];
    unsigned int keys[8 * NCTA];
    unsigned int epoch[NCTA + 4];
};
__device__ __align__(1024) Scratch g_s;

struct Params {
    Scratch* s;
    bf16* out;
    const bf16 *x, *gate_w, *w_r, *wg, *wu, *wd;
    CUtensorMap mDre, mDim, mX1, mX2, mCre, mCim, mAB, mOut, mWg, mWu, mWd;
};

__device__ __forceinline__ uint32_t smem_u32(const void* p) { return (uint32_t)__cvta_generic_to_shared(p); }
#define PROFL(i) do {} while (0)
#define PROFIF(slot, pred) do {} while (0)
#define PROF(slot) do {} while (0)
#define PROFG(slot) do {} while (0)

__device__ __forceinline__ void mbar_init(uint32_t bar, uint32_t cnt) {
    asm volatile("mbarrier.init.shared::cta.b64 [%0], %1;" ::"r"(bar), "r"(cnt) : "memory");
}
__device__ __forceinline__ void mbar_expect_tx(uint32_t bar, uint32_t bytes) {
    asm volatile("mbarrier.arrive.expect_tx.shared::cta.b64 _, [%0], %1;" ::"r"(bar), "r"(bytes) : "memory");
}
__device__ __forceinline__ void mbar_arrive(uint32_t bar) {
    asm volatile("mbarrier.arrive.shared::cta.b64 _, [%0];" ::"r"(bar) : "memory");
}
__device__ __forceinline__ void mbar_arrive_if(uint32_t bar, bool pred) {
    asm volatile("{.reg .pred p; setp.ne.b32 p, %1, 0; @p mbarrier.arrive.shared::cta.b64 _, [%0];}" ::"r"(bar), "r"((int)pred) : "memory");
}
__device__ __forceinline__ void mbar_arrive_warp(uint32_t bar) {
    __syncwarp();
    mbar_arrive_if(bar, (threadIdx.x & 31) == 0);
}
__device__ __forceinline__ void mbar_arrive_cluster_if(uint32_t bar, bool pred) {
    asm volatile("{.reg .pred p; setp.ne.b32 p, %1, 0; @p mbarrier.arrive.shared::cluster.b64 _, [%0], 1;}"
                 ::"r"(bar), "r"((int)pred) : "memory");
}
__device__ __forceinline__ uint32_t mapa(uint32_t a, uint32_t cta) {
    uint32_t r;
    asm volatile("mapa.shared::cluster.u32 %0, %1, %2;" : "=r"(r) : "r"(a), "r"(cta));
    return r;
}
__device__ __forceinline__ bool mbar_try(uint32_t bar, uint32_t parity) {
    uint32_t ok;
    asm volatile("{.reg .pred p; mbarrier.try_wait.parity.shared::cta.b64 p, [%1], %2; selp.u32 %0,1,0,p;}"
                 : "=r"(ok) : "r"(bar), "r"(parity) : "memory");
    return ok;
}
__device__ __forceinline__ bool mbar_test(uint32_t bar, uint32_t parity) {
    uint32_t ok;
    asm volatile("{.reg .pred p; mbarrier.test_wait.parity.shared::cta.b64 p, [%1], %2; selp.u32 %0,1,0,p;}"
                 : "=r"(ok) : "r"(bar), "r"(parity) : "memory");
    return ok;
}
__device__ __forceinline__ void mbar_wait(uint32_t bar, uint32_t parity) {
    asm volatile("{.reg .pred p, q; .reg .u32 n; mov.u32 n, 0;\n"
                 "W%=: mbarrier.try_wait.parity.shared::cta.b64 p, [%0], %1;\n"
                 "add.u32 n, n, 1; setp.lt.and.u32 q, n, %2, !p; @q bra W%=; @!p trap;}" ::"r"(bar), "r"(parity), "n"(SPIN_LIMIT) : "memory");
}
__device__ __forceinline__ void mbar_spin(uint32_t bar, uint32_t parity) {
    asm volatile("{.reg .pred p;\nW%=: mbarrier.try_wait.parity.shared::cta.b64 p, [%0], %1; @!p bra W%=;}" ::"r"(bar), "r"(parity) : "memory");
}
__device__ __forceinline__ void mbar_wait_cluster(uint32_t bar, uint32_t parity) {
    uint32_t n = 0, ok;
    do {
        asm volatile("{.reg .pred p; mbarrier.try_wait.parity.acquire.cluster.shared::cta.b64 p, [%1], %2; selp.u32 %0,1,0,p;}"
                     : "=r"(ok) : "r"(bar), "r"(parity) : "memory");
        if (++n > SPIN_LIMIT) __trap();
    } while (!ok);
}
__device__ __forceinline__ void tma2d(uint32_t dst, const CUtensorMap* m, int c0, int c1, uint32_t bar) {
    asm volatile("cp.async.bulk.tensor.2d.shared::cluster.global.mbarrier::complete_tx::bytes [%0], [%1, {%3,%4}], [%2];"
                 ::"r"(dst), "l"(m), "r"(bar), "r"(c0), "r"(c1) : "memory");
}
__device__ __forceinline__ void tma2d_elect(uint32_t dst, const CUtensorMap* m, int c0, int c1, uint32_t bar) {
    asm volatile("{.reg .pred p; elect.sync _|p, 0xffffffff;"
                 " @p cp.async.bulk.tensor.2d.shared::cluster.global.mbarrier::complete_tx::bytes [%0], [%1, {%3,%4}], [%2];}"
                 ::"r"(dst), "l"(m), "r"(bar), "r"(c0), "r"(c1) : "memory");
}
__device__ __forceinline__ void tma2d_pair_elect(uint32_t dst, const CUtensorMap* m, int c0, int c1, uint32_t bar) {
    asm volatile("{.reg .pred p; elect.sync _|p, 0xffffffff;"
                 " @p cp.async.bulk.tensor.2d.shared::cluster.global.mbarrier::complete_tx::bytes.multicast::cluster"
                 " [%0], [%1, {%3,%4}], [%2], %5;}" ::"r"(dst), "l"(m), "r"(bar), "r"(c0), "r"(c1), "h"((uint16_t)3) : "memory");
}
__device__ __forceinline__ void mbar_expect_tx_elect(uint32_t bar, uint32_t bytes) {
    asm volatile("{.reg .pred p; elect.sync _|p, 0xffffffff; @p mbarrier.arrive.expect_tx.shared::cta.b64 _, [%0], %1;}"
                 ::"r"(bar), "r"(bytes) : "memory");
}
__device__ __forceinline__ void tma3d(uint32_t dst, const CUtensorMap* m, int row, int chunk, uint32_t bar) {
    asm volatile("cp.async.bulk.tensor.3d.shared::cluster.global.mbarrier::complete_tx::bytes [%0], [%1, {%3,%4,%5}], [%2];"
                 ::"r"(dst), "l"(m), "r"(bar), "r"(0), "r"(row), "r"(chunk) : "memory");
}
__device__ __forceinline__ void tma2d_prefetch(const CUtensorMap* m, int c0, int c1) {
    asm volatile("cp.async.bulk.prefetch.tensor.2d.L2.global [%0, {%1,%2}];" ::"l"(m), "r"(c0), "r"(c1) : "memory");
}
__device__ __forceinline__ void fence_proxy_async_smem() { asm volatile("fence.proxy.async.shared::cta;" ::: "memory"); }
__device__ __forceinline__ void fence_proxy_async_gmem() { asm volatile("fence.proxy.async.global;" ::: "memory"); }
__device__ __forceinline__ void prefetch_l2(const void* p) { asm volatile("prefetch.global.L2 [%0];" ::"l"(p)); }
__device__ __forceinline__ uint32_t ld_relaxed(const void* p) {
    uint32_t v;
    asm volatile("ld.relaxed.gpu.global.u32 %0, [%1];" : "=r"(v) : "l"(p) : "memory");
    return v;
}
__device__ __forceinline__ uint4 ld_relaxed4(const void* p) {
    uint4 v;
    asm volatile("ld.relaxed.gpu.global.v4.u32 {%0,%1,%2,%3}, [%4];" : "=r"(v.x), "=r"(v.y), "=r"(v.z), "=r"(v.w) : "l"(p) : "memory");
    return v;
}
__device__ __forceinline__ uint4 ld_relaxed_b128(const void* p) {
    uint4 v;
    asm volatile("{.reg .b128 t; ld.relaxed.gpu.global.b128 t, [%4]; mov.b128 {%0,%1,%2,%3}, t;}"
                 : "=r"(v.x), "=r"(v.y), "=r"(v.z), "=r"(v.w) : "l"(p) : "memory");
    return v;
}
__device__ __forceinline__ uint4 ld_relaxed_b128_if(const void* p, bool pred) {
    uint4 v = make_uint4(0, 0, 0, 0);
    asm volatile("{.reg .b128 t; .reg .pred p; setp.ne.b32 p, %5, 0; mov.b128 t, {%0,%1,%2,%3};"
                 " @p ld.relaxed.gpu.global.b128 t, [%4]; mov.b128 {%0,%1,%2,%3}, t;}"
                 : "+r"(v.x), "+r"(v.y), "+r"(v.z), "+r"(v.w) : "l"(p), "r"((int)pred) : "memory");
    return v;
}
__device__ __forceinline__ void st_relaxed_b128(void* p, uint32_t x, uint32_t y, uint32_t z, uint32_t w) {
    asm volatile("{.reg .b128 t; .reg .b64 a, b; mov.b64 a, {%1,%2}; mov.b64 b, {%3,%4}; mov.b128 t, {a, b};"
                 " st.relaxed.gpu.global.b128 [%0], t;}" ::"l"(p), "r"(x), "r"(y), "r"(z), "r"(w) : "memory");
}
__device__ __forceinline__ void st_relaxed(unsigned int* p, uint32_t v) {
    asm volatile("st.relaxed.gpu.global.u32 [%0], %1;" ::"l"(p), "r"(v) : "memory");
}
__device__ __forceinline__ void st_relaxed_if(unsigned int* p, uint32_t v, bool pred) {
    asm volatile("{.reg .pred p; setp.ne.b32 p, %2, 0; @p st.relaxed.gpu.global.u32 [%0], %1;}" ::"l"(p), "r"(v), "r"((int)pred) : "memory");
}
__device__ __forceinline__ void red_inc_if(unsigned int* p, bool pred) {
    asm volatile("{.reg .pred p; setp.ne.b32 p, %1, 0; @p red.relaxed.gpu.global.add.u32 [%0], 1;}" ::"l"(p), "r"((int)pred) : "memory");
}
__device__ __forceinline__ void st_key(unsigned int* p, uint32_t v) {
    asm volatile("{.reg .b32 old; atom.relaxed.gpu.global.exch.b32 old, [%0], %1;}" ::"l"(p), "r"(v) : "memory");
}
__device__ __forceinline__ uint32_t tagf(float v, uint32_t par) { return (__float_as_uint(v) & ~1u) | par; }
__device__ __forceinline__ uint4 wait_tags(const unsigned int* p, int bit, uint32_t par) {
    uint32_t n = 0;
    while (true) {
        const uint4 v = ld_relaxed4(p);
        const uint32_t m = par ? (v.x & v.y & v.z & v.w) : ~(v.x | v.y | v.z | v.w);
        if (__all_sync(0xffffffffu, (m >> bit) & 1u)) return v;
        __nanosleep(POLL_NS);
        if (++n > SPIN_LIMIT) __trap();
    }
}
template <int SLEEP>
__device__ __forceinline__ void wait_counters(const unsigned int* p, uint32_t want) {
    uint32_t n = 0;
    while (!__all_sync(0xffffffffu, (int)(ld_relaxed(p) - want) >= 0)) {
        if (SLEEP) __nanosleep(SLEEP);
        if (++n > SPIN_LIMIT) __trap();
    }
    asm volatile("fence.acquire.gpu;" ::: "memory");
}
__device__ __forceinline__ void red_release_add(unsigned int* p, uint32_t v) {
    asm volatile("red.release.gpu.global.add.u32 [%0], %1;" ::"l"(p), "r"(v) : "memory");
}
__device__ __forceinline__ void named_bar(int id, int n) { asm volatile("bar.sync %0, %1;" ::"r"(id), "r"(n) : "memory"); }
template <int OFF>
__device__ __forceinline__ uint4 ldg_nc_off(const void* p) {
    uint4 v;
    asm volatile("ld.global.nc.v4.u32 {%0,%1,%2,%3}, [%4+%5];" : "=r"(v.x), "=r"(v.y), "=r"(v.z), "=r"(v.w) : "l"(p), "n"(OFF));
    return v;
}
template <int OFF>
__device__ __forceinline__ void stg_off_if(void* p, const uint4& v, bool pred) {
    asm volatile("{.reg .pred p; setp.ne.b32 p, %6, 0; @p st.global.v4.u32 [%0+%5], {%1,%2,%3,%4};}"
                 ::"l"(p), "r"(v.x), "r"(v.y), "r"(v.z), "r"(v.w), "n"(OFF), "r"((int)pred) : "memory");
}
template <int OFF>
__device__ __forceinline__ void stg_off(void* p, const uint4& v) {
    asm volatile("st.global.v4.u32 [%0+%5], {%1,%2,%3,%4};" ::"l"(p), "r"(v.x), "r"(v.y), "r"(v.z), "r"(v.w), "n"(OFF) : "memory");
}
__device__ __forceinline__ void sts128(uint32_t a, const uint4& v) {
    asm volatile("st.shared.v4.u32 [%0], {%1,%2,%3,%4};" ::"r"(a), "r"(v.x), "r"(v.y), "r"(v.z), "r"(v.w) : "memory");
}
__device__ __forceinline__ uint4 lds128(uint32_t a) {
    uint4 v;
    asm volatile("ld.shared.v4.u32 {%0,%1,%2,%3}, [%4];" : "=r"(v.x), "=r"(v.y), "=r"(v.z), "=r"(v.w) : "r"(a) : "memory");
    return v;
}
__device__ __forceinline__ float selpf(float a, float b, bool p) {
    float r;
    asm("{.reg .pred q; setp.ne.b32 q, %3, 0; selp.f32 %0, %1, %2, q;}" : "=f"(r) : "f"(a), "f"(b), "r"((int)p));
    return r;
}
template <int N, int MASK, int SZ>
__device__ __forceinline__ void halve(float (&a)[SZ]) {
    const bool up = threadIdx.x & MASK;
#pragma unroll
    for (int j = 0; j < N; j++) a[j] = selpf(a[N + j], a[j], up) + __shfl_xor_sync(0xffffffffu, selpf(a[j], a[N + j], up), MASK);
}
__device__ __forceinline__ float bflo(uint32_t u) { return __uint_as_float(u << 16); }
__device__ __forceinline__ float bfhi(uint32_t u) { return __uint_as_float(u & 0xffff0000u); }
__device__ __forceinline__ uint32_t pack_bf16(float lo, float hi) {
    uint32_t r;
    asm("cvt.rn.bf16x2.f32 %0, %1, %2;" : "=r"(r) : "f"(hi), "f"(lo));
    return r;
}
__device__ __forceinline__ uint32_t hfma2_bf16(uint32_t a, uint32_t b, uint32_t c) {
    uint32_t r;
    asm("fma.rn.bf16x2 %0, %1, %2, %3;" : "=r"(r) : "r"(a), "r"(b), "r"(c));
    return r;
}
__device__ __forceinline__ uint32_t hmul2_bf16(uint32_t a, uint32_t b) {
    uint32_t r;
    asm("mul.rn.bf16x2 %0, %1, %2;" : "=r"(r) : "r"(a), "r"(b));
    return r;
}
__device__ __forceinline__ float sigmoidf_(float v) { return __frcp_rn(1.0f + __expf(-v)); }

__device__ __forceinline__ void wg_fence() { asm volatile("wgmma.fence.sync.aligned;" ::: "memory"); }
__device__ __forceinline__ void wg_commit() { asm volatile("wgmma.commit_group.sync.aligned;" ::: "memory"); }
template <int N> __device__ __forceinline__ void wg_wait() { asm volatile("wgmma.wait_group.sync.aligned %0;" ::"n"(N) : "memory"); }
__device__ __forceinline__ uint64_t desc64_lo(uint32_t lo) { return (uint64_t)lo | (0x80000020ull << 32); }
__device__ __forceinline__ uint64_t desc_lo(uint32_t lo) { return (uint64_t)lo | (0x40000040ull << 32); }
template <int LO, int HI, int N>
__device__ __forceinline__ void fence_regs(float (&d)[N]) {
#pragma unroll
    for (int i = LO; i < HI; i++) asm volatile("" : "+f"(d[i])::"memory");
}
template <int TB = 1>
__device__ __forceinline__ void wgmma128(float (&d)[64], uint64_t da, uint64_t db, int scaleD) {
    asm volatile(
        "{ .reg .pred p; setp.ne.b32 p, %66, 0;\n"
        "wgmma.mma_async.sync.aligned.m64n128k16.f32.bf16.bf16 "
        "{%0,%1,%2,%3,%4,%5,%6,%7,%8,%9,%10,%11,%12,%13,%14,%15,%16,%17,%18,%19,%20,%21,%22,%23,%24,%25,%26,%27,%28,%29,%30,%31,"
        "%32,%33,%34,%35,%36,%37,%38,%39,%40,%41,%42,%43,%44,%45,%46,%47,%48,%49,%50,%51,%52,%53,%54,%55,%56,%57,%58,%59,%60,%61,%62,%63}, "
        "%64, %65, p, 1, 1, 0, %67;\n}"
        : "+f"(d[0]), "+f"(d[1]), "+f"(d[2]), "+f"(d[3]), "+f"(d[4]), "+f"(d[5]), "+f"(d[6]), "+f"(d[7]),
          "+f"(d[8]), "+f"(d[9]), "+f"(d[10]), "+f"(d[11]), "+f"(d[12]), "+f"(d[13]), "+f"(d[14]), "+f"(d[15]),
          "+f"(d[16]), "+f"(d[17]), "+f"(d[18]), "+f"(d[19]), "+f"(d[20]), "+f"(d[21]), "+f"(d[22]), "+f"(d[23]),
          "+f"(d[24]), "+f"(d[25]), "+f"(d[26]), "+f"(d[27]), "+f"(d[28]), "+f"(d[29]), "+f"(d[30]), "+f"(d[31]),
          "+f"(d[32]), "+f"(d[33]), "+f"(d[34]), "+f"(d[35]), "+f"(d[36]), "+f"(d[37]), "+f"(d[38]), "+f"(d[39]),
          "+f"(d[40]), "+f"(d[41]), "+f"(d[42]), "+f"(d[43]), "+f"(d[44]), "+f"(d[45]), "+f"(d[46]), "+f"(d[47]),
          "+f"(d[48]), "+f"(d[49]), "+f"(d[50]), "+f"(d[51]), "+f"(d[52]), "+f"(d[53]), "+f"(d[54]), "+f"(d[55]),
          "+f"(d[56]), "+f"(d[57]), "+f"(d[58]), "+f"(d[59]), "+f"(d[60]), "+f"(d[61]), "+f"(d[62]), "+f"(d[63])
        : "l"(da), "l"(db), "r"(scaleD), "n"(TB));
}

__device__ __forceinline__ void mbar_init_elect(uint32_t bar, uint32_t cnt) {
    asm volatile("{.reg .pred p; elect.sync _|p, 0xffffffff; @p mbarrier.init.shared::cta.b64 [%0], %1;}" ::"r"(bar), "r"(cnt) : "memory");
}
__device__ __forceinline__ void mbar_arrive_elect(uint32_t bar) {
    asm volatile("{.reg .pred p; elect.sync _|p, 0xffffffff; @p mbarrier.arrive.shared::cta.b64 _, [%0];}" ::"r"(bar) : "memory");
}
__device__ __forceinline__ void tma3d_elect(uint32_t dst, const CUtensorMap* m, int row, int chunk, uint32_t bar) {
    asm volatile("{.reg .pred p; elect.sync _|p, 0xffffffff;"
                 " @p cp.async.bulk.tensor.3d.shared::cluster.global.mbarrier::complete_tx::bytes [%0], [%1, {%3,%4,%5}], [%2];}"
                 ::"r"(dst), "l"(m), "r"(bar), "r"(0), "r"(row), "r"(chunk) : "memory");
}
template <int N>
__device__ __forceinline__ void mbar_arrive_n_elect(uint32_t bar) {
    asm volatile("{.reg .pred p; elect.sync _|p, 0xffffffff; @p mbarrier.arrive.shared::cta.b64 _, [%0], %1;}" ::"r"(bar), "n"(N) : "memory");
}
template <int N>
__device__ __forceinline__ void bulk_store_elect(void* dst, uint32_t src) {
    asm volatile("{.reg .pred p; elect.sync _|p, 0xffffffff; @p cp.async.bulk.global.shared::cta.bulk_group [%0], [%1], %2;}"
                 ::"l"(dst), "r"(src), "n"(N) : "memory");
}
__device__ __forceinline__ void bulk_wait_read() {
    asm volatile("cp.async.bulk.commit_group; cp.async.bulk.wait_group.read 0;" ::: "memory");
    __syncwarp();
}
template <int N>
__device__ __forceinline__ void release_pair(uint32_t bar, uint32_t rbar, bool pred) {
    asm volatile("{.reg .pred p; setp.ne.b32 p, %2, 0; @p mbarrier.arrive.shared::cta.b64 _, [%0], %3;"
                 " @p mbarrier.arrive.shared::cluster.b64 _, [%1], %3;}" ::"r"(bar), "r"(rbar), "r"((int)pred), "n"(N) : "memory");
}
template <int OFF>
__device__ __forceinline__ void red_bf16x8(void* p, uint32_t x, uint32_t y, uint32_t z, uint32_t w) {
    asm volatile("red.relaxed.gpu.global.add.noftz.v4.bf16x2 [%0+%5], {%1,%2,%3,%4};"
                 ::"l"(p), "r"(x), "r"(y), "r"(z), "r"(w), "n"(OFF) : "memory");
}
template <int OFF>
__device__ __forceinline__ uint32_t lds32_off(uint32_t a) {
    uint32_t v;
    asm volatile("ld.shared.u32 %0, [%1+%2];" : "=r"(v) : "r"(a), "n"(OFF) : "memory");
    return v;
}
template <int OFF>
__device__ __forceinline__ void sts128_off(uint32_t a, const uint4& v) {
    asm volatile("st.shared.v4.u32 [%0+%5], {%1,%2,%3,%4};" ::"r"(a), "r"(v.x), "r"(v.y), "r"(v.z), "r"(v.w), "n"(OFF) : "memory");
}

__device__ __forceinline__ uint32_t gtime() {
    uint32_t t;
    asm volatile("mov.u32 %0, %%globaltimer_lo;" : "=r"(t));
    return t;
}
__device__ __forceinline__ uint2 ld_relaxed2(const void* p) {
    uint2 v;
    asm volatile("{.reg .b64 t; ld.relaxed.gpu.global.b64 t, [%2]; mov.b64 {%0,%1}, t;}" : "=r"(v.x), "=r"(v.y) : "l"(p) : "memory");
    return v;
}
__device__ __forceinline__ void st_stamp_if(unsigned int* p, uint32_t v, bool pred) {
    asm volatile("{.reg .pred p; .reg .b32 t; .reg .b64 w; setp.ne.b32 p, %2, 0; mov.u32 t, %%globaltimer_lo; mov.b64 w, {%1, t};"
                 " @p st.relaxed.gpu.global.b64 [%0], w;}" ::"l"(p), "r"(v), "r"((int)pred) : "memory");
}
__device__ __forceinline__ uint32_t pin(uint32_t v) { return __shfl_xor_sync(0xffffffffu, v, 0); }
template <class T>
__device__ __forceinline__ T* pin(T* p) { return (T*)__shfl_xor_sync(0xffffffffu, (unsigned long long)p, 0); }
template <class T>
__device__ __forceinline__ T* pin_uniform(T* p) { return (T*)__shfl_sync(0xffffffffu, (unsigned long long)p, 0); }
__device__ __forceinline__ uint32_t stale_tags(uint32_t a, uint32_t par) {
    uint32_t r;
    asm volatile("{.reg .b32 v<16>;\n"
                 "ld.shared.u32 v0, [%1]; ld.shared.u32 v1, [%1+256]; ld.shared.u32 v2, [%1+512]; ld.shared.u32 v3, [%1+768];\n"
                 "ld.shared.u32 v4, [%1+4096]; ld.shared.u32 v5, [%1+4352]; ld.shared.u32 v6, [%1+4608]; ld.shared.u32 v7, [%1+4864];\n"
                 "ld.shared.u32 v8, [%1+8192]; ld.shared.u32 v9, [%1+8448]; ld.shared.u32 v10, [%1+8704]; ld.shared.u32 v11, [%1+8960];\n"
                 "ld.shared.u32 v12, [%1+12288]; ld.shared.u32 v13, [%1+12544]; ld.shared.u32 v14, [%1+12800]; ld.shared.u32 v15, [%1+13056];\n"
                 "lop3.b32 v0, v0, v1, %2, 0x7e; lop3.b32 v2, v2, v3, %2, 0x7e; lop3.b32 v4, v4, v5, %2, 0x7e; lop3.b32 v6, v6, v7, %2, 0x7e;\n"
                 "lop3.b32 v8, v8, v9, %2, 0x7e; lop3.b32 v10, v10, v11, %2, 0x7e; lop3.b32 v12, v12, v13, %2, 0x7e; lop3.b32 v14, v14, v15, %2, 0x7e;\n"
                 "lop3.b32 v0, v0, v2, v4, 0xfe; lop3.b32 v6, v6, v8, v10, 0xfe; lop3.b32 v0, v0, v6, v12, 0xfe; or.b32 %0, v0, v14;}"
                 : "=r"(r) : "r"(a), "r"(par) : "memory");
    return r;
}

__device__ __forceinline__ void wgmma128_rs(float (&d)[64], const uint32_t* a, uint64_t db, int scaleD) {
    asm volatile(
        "{ .reg .pred p; setp.ne.b32 p, %69, 0;\n"
        "wgmma.mma_async.sync.aligned.m64n128k16.f32.bf16.bf16 "
        "{%0,%1,%2,%3,%4,%5,%6,%7,%8,%9,%10,%11,%12,%13,%14,%15,%16,%17,%18,%19,%20,%21,%22,%23,%24,%25,%26,%27,%28,%29,%30,%31,"
        "%32,%33,%34,%35,%36,%37,%38,%39,%40,%41,%42,%43,%44,%45,%46,%47,%48,%49,%50,%51,%52,%53,%54,%55,%56,%57,%58,%59,%60,%61,%62,%63}, "
        "{%64,%65,%66,%67}, %68, p, 1, 1, 0;\n}"
        : "+f"(d[0]), "+f"(d[1]), "+f"(d[2]), "+f"(d[3]), "+f"(d[4]), "+f"(d[5]), "+f"(d[6]), "+f"(d[7]),
          "+f"(d[8]), "+f"(d[9]), "+f"(d[10]), "+f"(d[11]), "+f"(d[12]), "+f"(d[13]), "+f"(d[14]), "+f"(d[15]),
          "+f"(d[16]), "+f"(d[17]), "+f"(d[18]), "+f"(d[19]), "+f"(d[20]), "+f"(d[21]), "+f"(d[22]), "+f"(d[23]),
          "+f"(d[24]), "+f"(d[25]), "+f"(d[26]), "+f"(d[27]), "+f"(d[28]), "+f"(d[29]), "+f"(d[30]), "+f"(d[31]),
          "+f"(d[32]), "+f"(d[33]), "+f"(d[34]), "+f"(d[35]), "+f"(d[36]), "+f"(d[37]), "+f"(d[38]), "+f"(d[39]),
          "+f"(d[40]), "+f"(d[41]), "+f"(d[42]), "+f"(d[43]), "+f"(d[44]), "+f"(d[45]), "+f"(d[46]), "+f"(d[47]),
          "+f"(d[48]), "+f"(d[49]), "+f"(d[50]), "+f"(d[51]), "+f"(d[52]), "+f"(d[53]), "+f"(d[54]), "+f"(d[55]),
          "+f"(d[56]), "+f"(d[57]), "+f"(d[58]), "+f"(d[59]), "+f"(d[60]), "+f"(d[61]), "+f"(d[62]), "+f"(d[63])
        : "r"(a[0]), "r"(a[1]), "r"(a[2]), "r"(a[3]), "l"(db), "r"(scaleD));
}
__device__ __forceinline__ void ldsm4(uint32_t* r, uint32_t a) {
    asm volatile("ldmatrix.sync.aligned.m8n8.x4.shared.b16 {%0,%1,%2,%3}, [%4];" : "=r"(r[0]), "=r"(r[1]), "=r"(r[2]), "=r"(r[3]) : "r"(a) : "memory");
}

__device__ __forceinline__ int tile_of_step(int step, int own, int kh) {
    const int u = step >= 17 ? step - 17 : step - 1 - (step > OLS);
    int e = (u + (u >= ((own - 8 * kh) & 14) ? 2 : 0) + 8 * kh) & 15;
    if (u == 14) e = own ^ 1;
    if (step == 0 || step == OLS) e = own;
    return e + (step >= 17 || step == OLS ? 16 : 0);
}
__device__ __forceinline__ uint32_t router_key(float score, int row) {
    const float r = score + 0.0f;
    uint32_t u = pack_bf16(r, 0.f) & 0xffffu;
    u = (u & 0x8000u) ? (~u & 0xffffu) : (u | 0x8000u);
    if (r != r) u = 0;
    return (u << 16) | (uint32_t)(0x7fff - row);
}

#define g_fb_h ((float*)g_s.part)
#define g_fb_upd (g_fb_h + 2048)
#define g_fb_gate (g_fb_h + 4096)
#define g_fb_keys (g_s.part + 8192)
__global__ void fb_hidden(const bf16* x, const bf16* dre, const bf16* dim, const bf16* gw, const bf16* wr) {
    __shared__ float xs[D_];
    const int s = blockIdx.x, t = threadIdx.x;
    xs[t] = __bfloat162float(x[s * D_ + t]);
    __syncthreads();
    float a = 0.f, b = 0.f;
    for (int d = 0; d < D_; d++) { a = fmaf(xs[d], __bfloat162float(dre[t * D_ + d]), a); b = fmaf(xs[d], __bfloat162float(dim[t * D_ + d]), b); }
    ((bf16*)g_s.ab)[s * 1024 + t] = __float2bfloat16(a);
    ((bf16*)g_s.ab)[s * 1024 + 512 + t] = __float2bfloat16(b);
    if (t == 0) {
        float u = 0.f, v = 0.f;
        for (int d = 0; d < D_; d++) { u = fmaf(xs[d], __bfloat162float(gw[d]), u); v = fmaf(xs[d], __bfloat162float(wr[d]), v); }
        g_fb_gate[s] = sigmoidf_(u);
        g_fb_keys[s] = router_key(v, s);
    }
}
__device__ uint32_t fb_best() {
    uint32_t k = 0;
    for (int i = 0; i < S_; i++) k = max(k, g_fb_keys[i]);
    return k;
}
__global__ void fb_ffn1(const bf16* x, const bf16* wg, const bf16* wu) {
    const int f = blockIdx.x * blockDim.x + threadIdx.x, idx = 0x7fff - (int)(fb_best() & 0x7fffu);
    float a = 0.f, b = 0.f;
    for (int d = 0; d < D_; d++) {
        const float xv = __bfloat162float(x[idx * D_ + d]);
        a = fmaf(xv, __bfloat162float(wg[d * F_ + f]), a); b = fmaf(xv, __bfloat162float(wu[d * F_ + f]), b);
    }
    g_fb_h[f] = a * sigmoidf_(a) * b;
}
__global__ void fb_ffn2(const bf16* wd) {
    const int e = blockIdx.x * blockDim.x + threadIdx.x;
    const uint32_t u = fb_best() >> 16, rb = (u & 0x8000u) ? (u & 0x7fffu) : (~u & 0xffffu);
    float a = 0.f;
    for (int f = 0; f < F_; f++) a = fmaf(g_fb_h[f], __bfloat162float(wd[f * D_ + e]), a);
    g_fb_upd[e] = a * sigmoidf_(__uint_as_float(rb << 16));
}
__global__ void fb_seq(const bf16* x, const bf16* cre, const bf16* cim, bf16* out) {
    __shared__ float c[2][S_];
    __shared__ int idx;
    const int t = blockIdx.x, e = threadIdx.x;
    for (int i = e; i < S_; i += D_) { c[0][i] = __bfloat162float(cre[t * S_ + i]); c[1][i] = __bfloat162float(cim[t * S_ + i]); }
    if (e == 0) idx = 0x7fff - (int)(fb_best() & 0x7fffu);
    __syncthreads();
    float y = 0.f;
    for (int s = 0; s < S_; s++)
        y += c[0][s] * __bfloat162float(((const bf16*)g_s.ab)[s * 1024 + e]) - c[1][s] * __bfloat162float(((const bf16*)g_s.ab)[s * 1024 + 512 + e]);
    const float g = g_fb_gate[t];
    out[t * D_ + e] = __float2bfloat16(g * y + (1.f - g) * (__bfloat162float(x[t * D_ + e]) + (t == idx ? g_fb_upd[e] : 0.f)));
}

__device__ __forceinline__ void spare_job(const Params& p, unsigned char* smem, int sp, uint32_t tstart) {
    const int tid = threadIdx.x, warp = tid >> 5, lane = tid & 31;
    const uint32_t e1 = *(volatile unsigned int*)&p.s->epoch[NCTA + sp] + 1u;
    const uint32_t par = e1 & 1u;
    uint32_t* red = (uint32_t*)smem;
    __syncthreads();
    if (tid == 0) *(volatile unsigned int*)&p.s->epoch[NCTA + sp] = e1;
#pragma unroll 1
    for (int k = 0; k < (PFD ? 0 : 6); k++) {
        const char* src = k < 2 ? (const char*)p.wd + (sp * 2 + k) * 229376
                                : (const char*)((sp & 1) ? p.wu : p.wg) + ((sp >> 1) * 4 + k - 2) * 229376;
        while ((uint32_t)clock64() - tstart < PF_T0 + k * PF_DT) __nanosleep(LOWP ? 200 : 20);
        if (tid >= 448) {
            if (tid < 455) asm volatile("cp.async.bulk.prefetch.L2.global [%0], 16384;" ::"l"(src + (tid - 448) * 16384) : "memory");
        } else {
            prefetch_l2(src + 114688 + tid * 128);
            prefetch_l2(src + 172032 + tid * 128);
        }
        __syncwarp();
    }
    if (tid == 0) PROF(1);
    if (PFD) while ((uint32_t)clock64() - tstart < 10000) __nanosleep(500);
    if (warp == 0) {
        const uint4 k4 = wait_tags(p.s->keys + lane * 4, 15, par);
        const uint32_t k = __reduce_max_sync(0xffffffffu, max(max(k4.x, k4.y), max(k4.z, k4.w)));
        const int idx = 0x7fff - (int)(k & 0x7fffu);
        const uint4 g4 = wait_tags(p.s->gate + (idx & ~3), 0, par);
        const uint32_t gw = (idx & 2) ? ((idx & 1) ? g4.w : g4.z) : ((idx & 1) ? g4.y : g4.x);
        const uint32_t u = k >> 16;
        const uint32_t rb = (u & 0x8000u) ? (u & 0x7fffu) : (~u & 0xffffu);
        if (lane == 0) {
            red[16] = idx;
            red[17] = __float_as_uint((1.f - __uint_as_float(gw & ~1u)) * sigmoidf_(__uint_as_float(rb << 16)));
        }
    }
    while ((uint32_t)clock64() - tstart < SUM_T0) __nanosleep(200);
    float4 s = make_float4(0.f, 0.f, 0.f, 0.f);
    if (warp < 14) {
        uint32_t n = 0;
        while ((int)(ld_relaxed(p.s->phint + (sp * 16 + warp) * 8) - e1 * 8u) < 0) {
            __nanosleep(40);
            if (++n > SPIN_LIMIT) __trap();
        }
        if (tid == 0) PROF(2);
        const unsigned int* src = p.s->part + warp * 4 * D_ + sp * 128 + lane * 4;
        uint4 v[4];
        while (true) {
            uint32_t bad = 0;
#pragma unroll
            for (int i = 0; i < 4; i++) v[i] = ld_relaxed4(src + i * D_);
#pragma unroll
            for (int i = 0; i < 4; i++) bad |= (v[i].x ^ par) | (v[i].y ^ par) | (v[i].z ^ par) | (v[i].w ^ par);
            if (!__any_sync(0xffffffffu, bad & 1u)) break;
            if (++n > SPIN_LIMIT) __trap();
        }
#pragma unroll
        for (int i = 0; i < 4; i++) {
            s.x += __uint_as_float(v[i].x); s.y += __uint_as_float(v[i].y);
            s.z += __uint_as_float(v[i].z); s.w += __uint_as_float(v[i].w);
        }
    } else if (warp == 14) {
        wait_counters<100>(p.s->ready + (lane & 7) * 32, e1 * 16u);
    }
    float* acc = (float*)(smem + 1024);
    *(float4*)&acc[warp * 128 + lane * 4] = s;
    __syncthreads();
    if (tid < 64) {
        float t0 = 0.f, t1 = 0.f;
#pragma unroll
        for (int i = 0; i < 14; i++) {
            const float2 z = *(const float2*)&acc[i * 128 + tid * 2];
            t0 += z.x; t1 += z.y;
        }
        const float f = __uint_as_float(red[17]);
        asm volatile("red.relaxed.gpu.global.add.noftz.bf16x2 [%0], %1;"
                     ::"l"(p.out + red[16] * D_ + sp * 128 + tid * 2), "r"(pack_bf16(t0 * f, t1 * f)) : "memory");
    }
}

__host__ __device__ constexpr int off_d(int c) { return (c < 2 ? 1 : c / 2 + 2) * REGION + (c & 1) * 16384; }
__host__ __device__ constexpr int off_xe(int c) { return (c < 2 ? 6 * REGION : c < 4 ? 16384 : c < 6 ? 0 : 6 * REGION + 16384) + (c & 1) * 8192; }
__host__ __device__ constexpr int off_xl(int c) { return c < 4 ? 2 * REGION + c * 8192 : off_xe(c - 4); }

__global__ void __cluster_dims__(2, 1, 1) __launch_bounds__(NTHREADS, 1)
fused_kernel(const __grid_constant__ Params p) {
    extern __shared__ __align__(1024) unsigned char smem[];
    const uint32_t tstart = (uint32_t)clock64();
    const uint32_t sb = smem_u32(smem);
    const int tid = threadIdx.x, lane = tid & 31;
    const int rank = blockIdx.x & 1;
#define GET_ROLE(smid, role) asm volatile("mov.u32 %0, %%smid;" : "=r"(smid));                                \
    asm("{.reg .pred p, q; .reg .u32 t, a, b; shr.u32 t, %1, 1; mad.lo.u32 a, t, 293, -928; shr.u32 a, a, 8; mad.lo.u32 b, t, 8, -464;" \
        " setp.lt.u32 p, t, 32; setp.lt.u32 q, t, 62; selp.u32 a, a, b, q; selp.u32 %0, t, a, p;}" : "=r"(role) : "r"(smid))
    uint32_t t1 = 0;
    if (__any_sync(0xffffffffu, tid == 0)) {
        uint32_t s0, r0;
        GET_ROLE(s0, r0);
        if (FAST0 == 2) {
            asm volatile("{.reg .pred p; elect.sync _|p, 0xffffffff; @p prefetch.tensormap [%0]; @p prefetch.tensormap [%1]; @p prefetch.tensormap [%2];}"
                         ::"l"(&p.mDre), "l"(&p.mDim), "l"(&p.mX1) : "memory");
        }
        mbar_init_elect(sb + B_F, 1);
        if (r0 < 64) {
#pragma unroll
            for (int c = 0; c < NC0; c++) {
                if (c) {
                    while ((uint32_t)clock64() - t1 < PTIME(c)) {}
                    mbar_init_elect(sb + B_F + 8 * c, 1);
                }
                tma3d_elect(sb + off_d(c), &p.mDre + ((r0 >> 2) & 1), (r0 & 24) * 16, c, sb + B_F + 8 * c);
                tma3d_elect(sb + off_xe(c), &p.mX1, (r0 & 3) * 256 + (r0 & 32) * 4 + rank * 64, c, sb + B_F + 8 * c);
                mbar_expect_tx_elect(sb + B_F + 8 * c, 24576);
                if (!c) t1 = (uint32_t)clock64();
            }
        }
    }
    const int warp = __shfl_sync(0xffffffffu, tid >> 5, 0);
    uint32_t smid, role;
    GET_ROLE(smid, role);
    const int gpc = role & 7;
    const int tn = (role >> 3) & 3;
    const int kh = gpc >> 2;
    const int own = (gpc & 3) * 4 + ((role >> 5) & 1) * 2 + rank;
    const int blk = kh * 4 + tn;
#define TCOL(e) (kh * 1024 + ((e) >> 3) * 256 + ((e) & 3) * 64)
#define TMAT(e) (((e) >> 2) & 1)
#define KROT 0
    const int comp = kh;
    const int xrow = own * 64;
    constexpr int XLATE = 1024;
    const CUtensorMap* mD = &p.mDre + comp;
    const int rot = ROT == 1 ? gpc & 6 : ROT == 2 ? (gpc & 2) * 2 : ROT == 3 ? gpc & 2 : ROT == 4 ? kh * 4 : 0;
    const int cta = gpc * 16 + (role >> 3) * 2 + rank;
    const bool ffn = cta < FFN_CTAS;
    uint32_t epoch = 0;
#define CHUNK_LOAD(c) tma3d_elect(sb + off_d(c), mD, tn * 128, (c) ^ rot, sb + B_F + 8 * (c));                 \
                      tma3d_elect(sb + off_xe(c), &p.mX1, xrow, (c) ^ rot, sb + B_F + 8 * (c));                \
                      mbar_expect_tx_elect(sb + B_F + 8 * (c), 24576)
#define PACE_WAIT(c) while ((uint32_t)clock64() - t1 < PTIME(c)) {}
    if (warp != 0 || role >= 64) {
        const uint32_t b1 = sb + B_F + 8 * warp;
        mbar_init_elect(warp < NC0 ? b1 + 360 : b1, 1);
        if (warp >= NC0 && warp < 5) mbar_init_elect(b1 + 360, 1);
        mbar_init_elect(b1 + 120, warp < 7 ? 5 : warp < 14 ? 4 : 6);
        mbar_init_elect(b1 + 240, 1);
        if (warp == 9 || warp == 15) mbar_expect_tx_elect(b1 + 240, warp == 9 ? 2048 : 4);
        asm volatile("fence.mbarrier_init.release.cluster;" ::: "memory");
        if (tid == 128 && role < 64) epoch = *(volatile unsigned int*)&p.s->epoch[cta];
    } else {
    }
    if (role >= 64) {
        spare_job(p, smem, smid & 3, tstart);
        return;
    }
    __syncthreads();
    asm volatile("barrier.cluster.arrive.relaxed.aligned;" ::: "memory");
    if (warp == 0) {
#pragma unroll
        for (int c = NC0; c < 8; c++) {
            PACE_WAIT(c);
            CHUNK_LOAD(c);
            if (c == XL_AT) {
                tma3d_elect(sb + off_xl(0), &p.mX2, xrow + XLATE, 0 ^ rot, sb + B_G0);
                mbar_expect_tx_elect(sb + B_G0, 16384);
            }
            if (c == 7) {
                PACE_WAIT(8);
                tma3d_elect(sb + off_xl(2), &p.mX2, xrow + XLATE, 2 ^ rot, sb + B_G2);
                mbar_expect_tx_elect(sb + B_G2, 16384);
            }
        }
        if (PFX && tn < 2 && (KC && !MAP4 ? blk < 4 : true)) {
            asm volatile("{.reg .pred p; elect.sync _|p, 0xffffffff; @p cp.async.bulk.prefetch.tensor.3d.L2.global [%0, {%1,%2,%3}];}"
                         ::"l"(&p.mX2), "r"(0), "r"(xrow + XLATE), "r"((4 + 2 * (blk & 1)) ^ rot) : "memory");
        }
    }

    if (warp < 4) {
        if (warp == 0) {
            PROF(2);
            mbar_spin(sb + B_XE, 0);
            tma3d_elect(sb + off_xl(4), &p.mX2, xrow + XLATE, 4 ^ rot, sb + B_G1);
            tma3d_elect(sb + off_xl(6), &p.mX2, xrow + XLATE, 6 ^ rot, sb + B_G1);
            mbar_expect_tx_elect(sb + B_G1, 32768);
            PROF(3);
            const int el = tile_of_step(lane, own, KROT);
            const int taba = el * 64;
#define AMAP(c) &p.mCre + comp, c
            const int tabb = (blk * 32 + el) * 128 + rank * 64;
            const uint32_t dst = sb + 16384 + rank * 8192;
#define LOAD_A() const int c = __shfl_sync(0xffffffffu, taba, step);                                            \
                 const uint32_t bar = sb + 8 * slot;                                                            \
                 mbar_spin(bar + B_EMPTY, ph);                                                                  \
                 tma2d_elect(sb + slot * REGION, AMAP(c), own * 128, bar + B_FULL); \
                 mbar_expect_tx_elect(bar + B_FULL, 16384)
            uint32_t slot = 0, ph = 0;
            int step = 0;
#pragma unroll 1
            for (; step < NSTAGE; step++, slot++) { LOAD_A(); PROFIF(step == 0 ? 4 : 5, step == 0 || step == 5); }
            slot = 0; ph = 1;
#pragma unroll 1
            for (int h = PE; h < 2; h++) {
#pragma unroll 1
                for (; step < 16 + 15 * h; step++) {
                    const int row = __shfl_sync(0xffffffffu, tabb, step);
                    LOAD_A();
                    if (step == 6 || step == 17) mbar_spin(sb + B_SEEN + (step >> 4) * 8, 0);
                    tma2d_pair_elect(dst + slot * REGION, &p.mAB, 0, row, bar + B_BL);
                    mbar_expect_tx_elect(bar + B_BL, 16384);
                    PROF(160 + step);
                    if (++slot == NSTAGE) { slot = 0; ph ^= 1; }
                }
                const int row = __shfl_sync(0xffffffffu, tabb, step);
                LOAD_A();
                tma2d_elect(dst + slot * REGION, &p.mAB, 0, row, bar + B_BL);
                tma2d_elect((dst ^ 8192) + slot * REGION, &p.mAB, 0, row ^ 64, bar + B_BL);
                mbar_expect_tx_elect(bar + B_BL, 16384);
                PROF(160 + step);
                step++; slot++;
            }
        } else if (warp == 1) {
            if (lane < 4) asm volatile("prefetch.tensormap [%0];" ::"l"(&p.mCre + lane) : "memory");
            __syncwarp();
            asm volatile("barrier.cluster.wait.acquire.aligned;" ::: "memory");
            if (lane == 0)
                asm volatile("st.async.weak.shared::cluster.mbarrier::complete_tx::bytes.u32 [%0], %1, [%2];"
                             ::"r"(mapa(sb + M_ROLE, rank ^ 1)), "r"(role), "r"(mapa(sb + B_ROLE, rank ^ 1)) : "memory");
            mbar_wait_cluster(sb + B_ROLE, 0);
            if (*(volatile uint32_t*)(smem + M_ROLE) != role) __trap();
            mbar_wait(sb + B_EPOCH, 0);
            const uint32_t want = *(volatile uint32_t*)(smem + M_EPOCH) + 1u;
            const int el = tile_of_step(lane, own, KROT) & 15;
            const int tab = (blk * 32 + el) * 128 + rank * 64;
            const unsigned int* hp = p.s->hint + (blk * 8 + (el >> 1)) * 32 + (el & 1) * 2;
            uint2 st = ld_relaxed2(hp);
            const uint32_t wante = HINTM ? want * 4u : want;
            uint32_t seen = __ballot_sync(0xffffffffu, st.x == wante);
            mbar_wait(sb + B_EMPTY, 0);
#define POLL() { st = ld_relaxed2(hp); seen = __ballot_sync(0xffffffffu, st.x == wante); }
#pragma unroll 1
            for (int step = PE ? 3 : OLS == 1 ? 2 : 1; step < NSTAGE; step++) {
                const int row = __shfl_sync(0xffffffffu, tab, step);
                const uint32_t bar = sb + 8 * step;
                mbar_expect_tx_elect(bar + B_BL, 16384);
                while (!((seen >> step) & 1u)) POLL();
                const uint32_t due = __shfl_sync(0xffffffffu, st.y, step) + TSD;
                PROFIF(40, step == (PE ? 3 : 3 - OLS));
                mbar_spin(bar + B_EMPTY, 0);
                PROFIF(41, step == (PE ? 3 : 3 - OLS));
                if (!HINTM) while ((int)(gtime() - due) < 0) {}
                tma2d_pair_elect(sb + 16384 + rank * 8192 + step * REGION, &p.mAB, 0, row, bar + B_BL);
                PROF(160 + step);
                if (OLS == 2 && step == 1) step++;
            }
            mbar_wait(sb + B_FULL + 8 * OLS, 0);
            while (~seen) POLL();
            if (!HINTM) while (__any_sync(0xffffffffu, (int)(gtime() - st.y - TSD) < 0)) {}
            mbar_arrive_elect(sb + B_SEEN);
            PROF(7);
            unsigned char* gdst = p.s->ab + (blk * 32 + own + 16) * 16384;
            uint32_t t3 = (uint32_t)clock64() + OL_T0;
#pragma unroll 1
            for (int i = 0; i < 8; i++) {
                while ((int)((uint32_t)clock64() - t3) < 0) { if (LOWP) __nanosleep(64); }
                t3 += OL_DT;
                bulk_store_elect<2048>(gdst + i * 2048, sb + 6 * REGION + i * 2048);
            }
            bulk_wait_read();
            st_relaxed_if(p.s->hint + (blk * 8 + (own >> 1)) * 32 + 4 + rank, want, lane == 0);
            mbar_arrive_n_elect<4>(sb + B_FREE + 8);
            PROF(8);
            wait_counters<100>(hp + 4 - (el & 1), want);
            mbar_arrive_elect(sb + B_SEEN + 8);
            PROF(9);
            mbar_wait(sb + B_PUBI, 0);
            PROF(29);
            if (lane == 0) {
                if (TRED) fence_proxy_async_gmem();
                red_release_add(p.s->ready + blk * 32, 1);
            }
            __syncwarp();
            PROF(30);
            wait_counters<100>(p.s->ready + (lane & 7) * 32, want * 16u);
            mbar_arrive_elect(sb + B_INIT);
            PROF(10);
        } else {
            mbar_arrive_elect(sb + B_BL + 8 * OLS * (warp & 1));
            if (PE && warp == 2) {
                mbar_arrive_elect(sb + B_BL + 8);
                mbar_expect_tx_elect(sb + B_FULL + 8, 16384);
                mbar_arrive_n_elect<3>(sb + B_FULL + 8);
            }
            if (PFA_T && warp == 3) {
                const int e = tile_of_step(PFA_S + tn, own, KROT);
                while ((uint32_t)clock64() - tstart < PFA_T) __nanosleep(20);
                if (lane == 0) tma2d_prefetch(&p.mCre + comp, e * 64, own * 128);
                __syncwarp();
            }
            uint32_t k = 12;
            if (PFD && warp == 3) k = 0;
#define PREFETCH_W() {                                                                                        \
                const char* src = (k >= 8 ? (const char*)p.wd + ((cta >> 5) * 2 + (k >> 1) - 4) * 229376       \
                                          : (const char*)((cta & 32) ? p.wu : p.wg) + ((cta >> 6) * 4 + (k >> 1)) * 229376) + ((cta & 31) * 2 + (k & 1)) * 3584; \
                asm volatile("{.reg .pred p; elect.sync _|p, 0xffffffff; @p cp.async.bulk.prefetch.L2.global [%0], 3584;}" ::"l"(src) : "memory"); \
                k++; }
#pragma unroll 1
            while (k < PF_N0) {
                while ((uint32_t)clock64() - tstart < PF_T0 + k * (PF_DT / 2)) __nanosleep(50);
                __syncwarp();
                PREFETCH_W();
            }
            mbar_wait(sb + B_EPOCH, 0);
            const uint32_t par = (*(volatile uint32_t*)(smem + M_EPOCH) + 1u) & 1u;
            const uint32_t a0 = sb + 16384 + (lane >> 3) * 1028 + ((lane >> 2) & 1) * 144 + (lane & 3) * 32;
            const int tab = (blk * 32 + tile_of_step(lane, own, KROT)) * 128;
            const uint32_t retry = sb + B_RETRY + (warp & 1) * 240;
            uint32_t slot = PE ? 6 - warp : OLS == 1 ? warp : 10 - 3 * warp, ph = 0, rph = 0;
            uint32_t j = ffn ? warp & 1 : 12;
#pragma unroll 1
            for (int step = slot; step < 32 || j < 12; step += 2) {
                if (step < 32) {
                    const uint32_t a = a0 + slot * REGION, bar = sb + 8 * slot;
                    mbar_wait(bar + B_BL, ph);
                    PROF(192 + step);
#pragma unroll 1
                    while (__any_sync(0xffffffffu, stale_tags(a, par) & 1u)) {
                        const int row = __shfl_sync(0xffffffffu, tab, step);
                        mbar_expect_tx_elect(retry, 16384);
                        tma2d_elect(sb + slot * REGION + 16384, &p.mAB, 0, row, retry);
                        tma2d_elect(sb + slot * REGION + 24576, &p.mAB, 0, row + 64, retry);
                        mbar_spin(retry, rph);
                        rph ^= 1u;
                    }
                    mbar_arrive_n_elect<4>(bar + B_FULL);
                    PROF(128 + step);
                }
                if (j < 12 && step >= FFN_S0 + j * FW0 / 4 && __any_sync(0xffffffffu, mbar_test(sb + B_FREE + 2 * (j & 12), 0))) {
                    const uint32_t fb = sb + B_FFN + 4 * (j & 6);
                    if (!(j & 1)) mbar_expect_tx_elect(fb, 8192);
                    tma2d_elect(sb + 6 * REGION + ((j + 4) & 7) * 4096, j < 8 ? &p.mWg + (j & 1) : &p.mWd, j < 8 ? (cta >> 1) * 32 : rank * 256,
                                j < 8 ? rank * 256 + (j >> 1) * 64 : (cta >> 1) * 32 + j * 8 - 64, fb);
                    j += 2;
                }
                if (k < 12) PREFETCH_W();
                if (PFL && step == PFL) {
                    const int e = tile_of_step(28 + tn, own, KROT);
                    if (lane == 0) tma2d_prefetch(&p.mCre + comp, e * 64, own * 128);
                    __syncwarp();
                }
                slot += 2;
                if (slot >= NSTAGE) { slot -= NSTAGE; ph ^= 1; }
            }
        }
    } else if (warp < 8) {
        const int t = tid - 128, w = warp - 4;
        if (t == 0) {
            *(volatile uint32_t*)(smem + M_EPOCH) = epoch;
            *(volatile unsigned int*)&p.s->epoch[cta] = epoch + 1;
            mbar_arrive(sb + B_EPOCH);
        }
        const uint4 gw0 = ldg_nc_off<0>(p.gate_w + lane * 8), gw1 = ldg_nc_off<512>(p.gate_w + lane * 8);
        const uint4 rw0 = ldg_nc_off<0>(p.w_r + lane * 8), rw1 = ldg_nc_off<512>(p.w_r + lane * 8);
        mbar_wait(sb + B_EPOCH, 0);
        const uint32_t par = (*(volatile uint32_t*)(smem + M_EPOCH) + 1u) & 1u;
        mbar_wait(sb + B_F + 8 * ROUTER_C, 0);
        const int row0 = cta * 16 + w * 4;
        uint4 xr[8];
        {
            const char* xp = (const char*)p.x + (uint32_t)row0 * (D_ * 2) + lane * 16;
            xr[0] = ldg_nc_off<0>(xp);    xr[1] = ldg_nc_off<512>(xp);  xr[2] = ldg_nc_off<1024>(xp); xr[3] = ldg_nc_off<1536>(xp);
            xr[4] = ldg_nc_off<2048>(xp); xr[5] = ldg_nc_off<2560>(xp); xr[6] = ldg_nc_off<3072>(xp); xr[7] = ldg_nc_off<3584>(xp);
            float a[8];
#pragma unroll
            for (int i = 0; i < 4; i++) {
                const uint32_t xv[8] = {xr[2 * i].x, xr[2 * i].y, xr[2 * i].z, xr[2 * i].w, xr[2 * i + 1].x, xr[2 * i + 1].y, xr[2 * i + 1].z, xr[2 * i + 1].w};
                const uint32_t gv[8] = {gw0.x, gw0.y, gw0.z, gw0.w, gw1.x, gw1.y, gw1.z, gw1.w};
                const uint32_t rv[8] = {rw0.x, rw0.y, rw0.z, rw0.w, rw1.x, rw1.y, rw1.z, rw1.w};
                float u = 0.f, v = 0.f;
#pragma unroll
                for (int j = 0; j < 8; j++) {
                    u = fmaf(bflo(xv[j]), bflo(gv[j]), u); u = fmaf(bfhi(xv[j]), bfhi(gv[j]), u);
                    v = fmaf(bflo(xv[j]), bflo(rv[j]), v); v = fmaf(bfhi(xv[j]), bfhi(rv[j]), v);
                }
                a[i] = u; a[4 + i] = v;
            }
            if (RSPLIT) mbar_wait(sb + B_FULL + 8 * (RSPLIT - 1), 0);
            halve<4, 16>(a); halve<2, 8>(a); halve<1, 4>(a);
            a[0] += __shfl_xor_sync(0xffffffffu, a[0], 1);
            a[0] += __shfl_xor_sync(0xffffffffu, a[0], 2);
            const int row = row0 + ((lane >> 2) & 3);
            const float gate = sigmoidf_(a[0]);
            if (lane < 16 && (lane & 3) == 0) st_relaxed(&p.s->gate[row], tagf(gate, par));
            const uint32_t best = __reduce_max_sync(0xffffffffu, lane >= 16 ? router_key(a[0], row) : 0u);
            if (lane == 0) *(volatile uint32_t*)(smem + M_RED + w * 4) = best;
            named_bar(1, 128);
            if (t < 8) {
                const uint4 k = *(const uint4*)(smem + M_RED);
                st_key(&p.s->keys[t * NCTA + cta], max(max(k.x, k.y), max(k.z, k.w)) | (par << 15));
            }
            PROFIF(11, t == 0);
            const uint32_t og = pack_bf16(1.f - gate, 1.f - gate);
#pragma unroll
            for (int i = 0; i < 8; i++) {
                const uint32_t o = __shfl_sync(0xffffffffu, og, 4 * (i >> 1));
                xr[i] = make_uint4(hmul2_bf16(o, xr[i].x), hmul2_bf16(o, xr[i].y), hmul2_bf16(o, xr[i].z), hmul2_bf16(o, xr[i].w));
            }
        }
        mbar_wait(sb + B_FULL + 8 * OLS, 0);
        if (w == 0) {
            const uint4 k4 = wait_tags(p.s->keys + gpc * NCTA + lane * 4, 15, par);
            const uint32_t k = __reduce_max_sync(0xffffffffu, max(max(k4.x, k4.y), max(k4.z, k4.w)));
            sts128(sb + M_UPD + lane * 16, ldg_nc_off<0>(p.x + (0x7fff - (k & 0x7fffu)) * D_ + rank * 256 + lane * 8));
        } else if (w == 1) {
            const uint4 g4 = wait_tags(p.s->gate + own * 128 + lane * 4, 0, par);
            *(uint4*)(smem + M_G + lane * 16) = make_uint4(g4.x & ~1u, g4.y & ~1u, g4.z & ~1u, g4.w & ~1u);
            mbar_arrive_warp(sb + B_GATE);
        }
        named_bar(1, 128);
        PROFIF(13, t == 0);
        char* op = (char*)p.out + (uint32_t)row0 * (D_ * 2) + lane * 16;
        float a[16];
#pragma unroll
        for (int i = 0; i < 16; i++) a[i] = 0.f;
#pragma unroll 1
        for (int i = 0; i < 4; i++) {
            if (i >= 2) {
                mbar_wait(sb + B_FREE + 8, 0);
                const uint32_t t2 = (uint32_t)clock64();
#pragma unroll
                for (int j = 0; j < 4; j++) {
                    while ((uint32_t)clock64() - t2 < j * INIT_DT) __nanosleep(50);
                    *(uint4*)(op + j * 512) = xr[j];
                    xr[j] = xr[j + 4];
                }
                op += 2048;
                if (i == 3) mbar_arrive_warp(sb + B_PUBI);
            }
            if (ffn) {
                const float xs0 = __bfloat162float(((const bf16*)(smem + M_UPD))[64 * i + (t >> 2)]);
                const float xs1 = __bfloat162float(((const bf16*)(smem + M_UPD))[64 * i + 32 + (t >> 2)]);
                const uint32_t wa = sb + 6 * REGION + (i ^ 2) * 8192 + t * 16;
                mbar_wait(sb + B_FFN + 8 * i, 0);
                const uint4 v0 = lds128(wa), v1 = lds128(wa + 4096), v2 = lds128(wa + 2048), v3 = lds128(wa + 6144);
                const uint32_t w0[8] = {v0.x, v0.y, v0.z, v0.w, v1.x, v1.y, v1.z, v1.w};
                const uint32_t w1[8] = {v2.x, v2.y, v2.z, v2.w, v3.x, v3.y, v3.z, v3.w};
#pragma unroll
                for (int k = 0; k < 8; k++) {
                    a[2 * k] = fmaf(xs1, bflo(w1[k]), fmaf(xs0, bflo(w0[k]), a[2 * k]));
                    a[2 * k + 1] = fmaf(xs1, bfhi(w1[k]), fmaf(xs0, bfhi(w0[k]), a[2 * k + 1]));
                }
                if (i == 1) {
                    named_bar(1, 128);
                    mbar_arrive_if(sb + B_VD, t == 0);
                }
            }
        }
        if (!ffn) return;
        PROFIF(14, t == 0);
        {
            halve<8, 16>(a); halve<4, 8>(a); halve<2, 4>(a);
            const uint32_t ho = (lane >> 4) * 128 + (lane & 3) * 32 + ((lane >> 2) & 3) * 8;
            asm volatile("barrier.cluster.wait.acquire.aligned;" ::: "memory");
#pragma unroll
            for (int k = 0; k < 2; k++)
                asm volatile("st.async.weak.shared::cluster.mbarrier::complete_tx::bytes.v2.f32 [%0], {%1,%2}, [%3];"
                             ::"r"(mapa(sb + (k ? 6 * REGION + w * 512 : M_HX + w * 256) + ho, rank ^ k ^ 1)), "f"(a[0]), "f"(a[1]),
                               "r"(mapa(sb + B_HX, rank ^ k ^ 1)) : "memory");
            mbar_wait_cluster(sb + B_HX, 0);
            const float *hx = (const float*)(smem + M_HX) + lane, *hy = (const float*)(smem + 6 * REGION) + lane;
            const float gs = ((hx[0] + hy[0]) + (hx[64] + hy[128])) + ((hx[128] + hy[256]) + (hx[192] + hy[384]));
            const float us = ((hx[32] + hy[32]) + (hx[96] + hy[160])) + ((hx[160] + hy[288]) + (hx[224] + hy[416]));
            float* hrow = (float*)(smem + 6 * REGION + 256) + w * 128;
            hrow[lane] = gs * sigmoidf_(gs) * us;
            __syncwarp();
            PROFIF(12, t == 0);
            float o0 = 0.f, o1 = 0.f;
#pragma unroll 1
            for (int i = 0; i < 2; i++) {
                float4 hv[4];
                uint32_t vd[16];
#pragma unroll
                for (int k = 0; k < 4; k++) hv[k] = *(const float4*)&hrow[i * 16 + k * 4];
                mbar_wait(sb + B_FFN + 8 * i, 1);
#pragma unroll
                for (int k = 0; k < 16; k++) vd[k] = *(const volatile uint32_t*)(smem + 6 * REGION + 16384 + i * 8192 + k * 512 + t * 4);
#pragma unroll
                for (int k = 0; k < 4; k++) {
                    o0 = fmaf(hv[k].x, bflo(vd[4 * k]), o0);     o1 = fmaf(hv[k].x, bfhi(vd[4 * k]), o1);
                    o0 = fmaf(hv[k].y, bflo(vd[4 * k + 1]), o0); o1 = fmaf(hv[k].y, bfhi(vd[4 * k + 1]), o1);
                    o0 = fmaf(hv[k].z, bflo(vd[4 * k + 2]), o0); o1 = fmaf(hv[k].z, bfhi(vd[4 * k + 2]), o1);
                    o0 = fmaf(hv[k].w, bflo(vd[4 * k + 3]), o0); o1 = fmaf(hv[k].w, bfhi(vd[4 * k + 3]), o1);
                }
            }
            asm volatile("st.relaxed.gpu.global.v2.u32 [%0], {%1,%2};" ::"l"(&p.s->part[(cta >> 1) * D_ + rank * 256 + t * 2]),
                         "r"(tagf(o0, par)), "r"(tagf(o1, par)) : "memory");
            if (lane == 0) asm volatile("red.relaxed.gpu.global.add.u32 [%0], 1;" ::"l"(p.s->phint + ((rank * 2 + (w >> 1)) * 16 + (cta >> 3)) * 8) : "memory");
            PROFIF(15, t == 0);
        }
    } else {
        const int wg = (warp >> 2) - 2, wq = warp & 3;
        const uint32_t sbd = (sb & 0x3FFFF) >> 4;
        const bool lead = (tid & 127) == 0;
        const bool lead0 = lead && !wg, lead1 = lead && wg;
        const int q = lane & 3;
        float acc[64];
        const uint32_t rE = mapa(sb + B_EMPTY, rank ^ 1);
#define RELEASE(n, slot, pred) release_pair<n>(sb + B_EMPTY + 8 * (slot), rE + 8 * (slot), pred)
        const uint32_t img = sb + 6 * REGION + (wg ? 0 : 16384) + wq * 4096;
        const uint32_t sdst = pin(img + (lane >> 2) * 64 + ((q ^ (lane >> 3)) << 4));
        unsigned char* gdst = pin_uniform(p.s->ab + ((blk * 32 + own) * 4 + wq) * 4096);
        unsigned char* gd2 = pin(gdst + (sdst - img));
        unsigned int* hint = pin(p.s->hint + (blk * 8 + (own >> 1)) * 32 + rank * 2);
        uint32_t e1 = 0;
        asm volatile("barrier.cluster.wait.acquire.aligned;" ::: "memory");
        if (wg) {
            mbar_spin(sb + B_G0, 0);
            PROFIF(20, lead);
            mbar_spin(sb + B_GO1, 0);
        }
#pragma unroll
        for (int c = RS1 ? 2 : 0; c < 8; c++) {
            mbar_spin(sb + (c == 4 && wg ? B_G1 : c == 2 && wg ? B_G2 : PAUSE && c == 1 && wg ? B_XE : B_F + 8 * c), PAUSE && c == 1 && wg);
            if (c == 0) { PROFIF(16 + 5 * wg, lead); PROFL(0); }
            wg_fence();
#pragma unroll
            for (int kk = 0; kk < 4; kk++) {
                wgmma128<0>(acc, desc_lo(sbd + 0x10000 + (wg ? off_xl(c) : off_xe(c)) / 16 + 2 * kk), desc_lo(sbd + 0x10000 + off_d(c) / 16 + 2 * kk), (c | kk) != 0);
                if (c == 7 && kk == GOK - 1) wg_commit();
            }
            wg_commit();
            if (c == 3) {
                mbar_spin(sb + B_EPOCH, 0);
                e1 = *(volatile uint32_t*)(smem + M_EPOCH) + 1u;
            }
            if (c == 7 && wg) mbar_spin(sb + B_FULL, 0);
            if (c == 7 && GO0) { wg_wait<2>(); mbar_arrive_if(sb + B_GO1, lead0); }
            if (c >= 2 && c != 3 && c != 5) wg_wait<1>();
            if (c == 2) RELEASE(2, 1, lead1);
            if (c == 4) { mbar_arrive_if(sb + B_XE, lead0); RELEASE(2, 2, lead1); RELEASE(2, 3, lead1); }
            if (c == 6 && !HINTM) st_stamp_if(hint, e1, lead0);
            if (c == 6) RELEASE(2, 4 * wg, lead);
            if (c == 7) mbar_arrive_if(sb + B_GO1 + 8 * wg, GO0 ? lead1 : lead);
        }
        const uint32_t neg = comp && !KC ? 0x80008000u : 0u, negp = neg | (e1 & 1u);
        const int rh = RSW ? wg ^ kh : wg;
        const uint32_t da0 = sbd + 0x10000 + rh * 512, db0 = sbd + 0x400000 + 1024;
#define STEP(da, db, first) wg_fence();                                                                     \
        _Pragma("unroll") for (int kk = 0; kk < 4; kk++)                                                    \
            wgmma128(acc, desc_lo((da) + kk * 2), desc64_lo((db) + kk * 256), !((first) && kk == 0));       \
        wg_commit()
#define PROFSTEP(s) PROFIF(64 + wg * 32 + (s), lead)
        const uint32_t dbe = db0 + 6 * (REGION / 16), dbl = dbe - 1024;
#define PW(i, j) pack_bf16(acc[16 * ((i) >> 1) + 2 * ((i) & 1) + 4 * (j)], acc[16 * ((i) >> 1) + 2 * ((i) & 1) + 4 * (j) + 1])
#define PT(i, j) ((j) == ((i) >> 1) ? (PW(i, j) & ~1u) ^ negp : PW(i, j) ^ neg)
#define PIECE(i) make_uint4(PT(i, 0), PT(i, 1), PT(i, 2), PT(i, 3))
        if (wg) {
            wg_wait<0>();
            fence_regs<0, 64>(acc);
            PROFIF(22, lead); PROFL(1);
#define STS1(i) sts128_off<(i) * 512>(sdst, PIECE(i))
            STS1(0); STS1(1); STS1(2); STS1(3); STS1(4); STS1(5); STS1(6); STS1(7);
            if (W1FIRST == 1) { PROFL(3); STEP(da0, dbe, true); }
            fence_proxy_async_smem();
            __syncwarp();
            mbar_arrive_if(sb + B_FULL + 8 * OLS, lane == 0);
            PROFL(2);
            if (!W1FIRST) { PROFL(3); STEP(da0, dbe, true); }
            PROFIF(23, lead);
            RELEASE(1, 5, lead);
        } else {
            wg_wait<0>();
            fence_regs<0, 64>(acc);
            PROFIF(17, lead); PROFL(1);
            uint4 v[8];
#define STG0(i) v[i] = PIECE(i); stg_off<(i) * 512>(gd2, v[i]); red_inc_if(hint, HINTM == (i) + 1 && lane == 0); if (PAUSE == (i) + 1) mbar_arrive_if(sb + B_XE, lead)
            STG0(0); STG0(1); STG0(2); STG0(3); STG0(4); STG0(5); STG0(6); STG0(7);
            PROFIF(48 + wq, lane == 0);
#define STS0(i) if (THR && (i) % THR == 0) mbar_spin(sb + B_EPOCH, 0); sts128_off<(i) * 512>(sdst, v[i])
            STS0(0); STS0(1); STS0(2); STS0(3); STS0(4); STS0(5); STS0(6); STS0(7);
            if (PE) mbar_spin(sb + B_EMPTY + 8, 0);
            fence_proxy_async_smem();
            __syncwarp();
            if (PE)
                asm volatile("{.reg .pred p; elect.sync _|p, 0xffffffff;"
                             " @p cp.async.bulk.shared::cluster.shared::cta.mbarrier::complete_tx::bytes [%0], [%1], 4096, [%2];}"
                             ::"r"(rE - B_EMPTY + REGION + 16384 + wq * 4096), "r"(img), "r"(rE - B_EMPTY + B_FULL + 8) : "memory");
            mbar_arrive_if(sb + B_FULL, lane == 0);
            PROFIF(19, lead); PROFL(2);
            RELEASE(1, 5, lead);
            mbar_arrive_if(sb + B_FREE, lane == 0);
            mbar_spin(sb + B_FULL, 0);
            mbar_spin(sb + B_SKEW0, 0);
            PROFSTEP(0); PROFL(3);
            STEP(da0, dbe, true);
        }
#pragma unroll
        for (int step = 1; step < 4; step++) {
            mbar_spin(sb + B_FULL + 8 * step, 0);
            PROFSTEP(step); PROFL(3 + step);
            STEP(da0 + step * (REGION / 16), step == OLS ? dbl : db0 + step * (REGION / 16), false);
            wg_wait<1>();
            RELEASE(1, step - 1, lead);
            if (step == 1) mbar_arrive_if(sb + B_FREE, lead);
            if (step == OLS + 1) mbar_arrive_if(sb + B_FREE + 8, lead);
        }
        PROFL(7);
        int slot = 4, ph = 0, pslot = 3;
#pragma unroll 1
        for (int step = 4; step < 26; step++) {
            mbar_wait(sb + B_FULL + 8 * slot, ph);
            PROFSTEP(step);
            STEP(da0 + slot * (REGION / 16), db0 + slot * (REGION / 16), false);
            wg_wait<1>();
            RELEASE(1, pslot, lead);
            pslot = slot;
            if (++slot == NSTAGE) { slot = 0; ph ^= 1; }
        }
        PROFL(8);
        float g0 = 0.f, g1 = 0.f;
        char* op = nullptr;
        const int r0 = rh * 64 + wq * 16 + (lane >> 2);
        const bool odd = lane & 4;
#define OUT_SETUP() mbar_wait(sb + B_GATE, 0);                                                              \
        g0 = ((const volatile float*)(smem + M_G))[r0];                                                     \
        g1 = ((const volatile float*)(smem + M_G))[r0 + 8];                                                 \
        if (KC && comp) { g0 = -g0; g1 = -g1; }                                                             \
        op = pin((char*)p.out + (uint32_t)((own * 128 + (SHUF ? r0 & ~1 : r0)) * D_ + tn * 128 + (lane & (SHUF ? 7 : 3)) * 8) * 2u)
        if (SK == 6 && wg) {
            wg_wait<0>();
        } else {
            mbar_wait(sb + B_FULL + 8 * 2, 0);
            STEP(da0 + 2 * (REGION / 16), db0 + 2 * (REGION / 16), false);
            wg_wait<1>();
            slot = 3;
        }
        RELEASE(1, 1, lead);
#pragma unroll 1
        for (int step = 24 + slot; step < 32; step++) {
            if (step == (wg ? 32 - SK : 30)) {
                OUT_SETUP();
                mbar_wait(sb + (wg ? B_TAIL : B_INIT), 0);
            }
            if (!wg || step < 32 - SK) mbar_wait(sb + B_FULL + 8 * slot, ph);
            STEP(da0 + slot * (REGION / 16), db0 + slot * (REGION / 16), false);
            if (++slot == NSTAGE) { slot = 0; ph ^= 1; }
        }
        if (!wg) {
            wg_wait<1>();
            mbar_arrive_if(sb + B_TAIL, lead);
        }
        if (!wg || TRED == 2) {
            const int sr = ((lane >> 2) & 1) * 4 + (lane >> 3);
            const uint32_t st0 = sb + rh * 8192 + wq * 2048, sa = st0 + sr * 128 + ((q ^ sr) << 4);
            wg_wait<0>();
            fence_regs<0, 64>(acc);
            PROFIF(24 + 2 * wg, lead); PROFL(9);
#define OW(i, j) pack_bf16((((i) & 1) ? g1 : g0) * acc[16 * ((i) >> 1) + 2 * ((i) & 1) + 4 * (j)], (((i) & 1) ? g1 : g0) * acc[16 * ((i) >> 1) + 2 * ((i) & 1) + 4 * (j) + 1])
#define OSTS(i) sts128_off<((i) >> 2) * REGION + ((i) & 1) * 1024>(((i) & 2) ? sa ^ 64 : sa, make_uint4(OW(i, 0), OW(i, 1), OW(i, 2), OW(i, 3)))
#define ORED(h) fence_proxy_async_smem(); __syncwarp();                                                     \
            asm volatile("{.reg .pred p; elect.sync _|p, 0xffffffff;"                                       \
                         " @p cp.reduce.async.bulk.tensor.4d.global.shared::cta.add.tile.bulk_group [%0, {%2,%3,%3,%4}], [%1];}" \
                         ::"l"(&p.mOut), "r"(st0 + (h) * REGION), "r"(tn * 128 + (h) * 64), "r"(0), "r"(own * 16 + rh * 8 + wq * 2) : "memory")
            OSTS(0); OSTS(1); OSTS(2); OSTS(3);
            ORED(0);
            OSTS(4); OSTS(5); OSTS(6); OSTS(7);
            ORED(1);
            bulk_wait_read();
        } else {
        char* opb = op + (odd ? 1024 - 64 : 1024 + 64);
        wg_wait<0>();
        fence_regs<0, 64>(acc);
        PROFIF(24 + 2 * wg, lead); PROFL(9);
        uint32_t k[4][4], r[4][4];
#define PACKLINE(i) _Pragma("unroll") for (int j = 0; j < 4; j++) {                                         \
            const int o = 32 * ((i) >> 1) + 2 * ((i) & 1) + 4 * j;                                          \
            const float g = ((i) & 1) ? g1 : g0;                                                            \
            r[i][j] = __shfl_xor_sync(0xffffffffu, pack_bf16(g * acc[o + 16], g * acc[o + 17]), 4);         \
            k[i][j] = pack_bf16(g * acc[o], g * acc[o + 1]); }
#define REDLINE(i)                                                                                          \
        red_bf16x8<((i) & 1) * 8192 + ((i) >> 1) * 128>(op, odd ? r[i][0] : k[i][0], odd ? r[i][1] : k[i][1], odd ? r[i][2] : k[i][2], odd ? r[i][3] : k[i][3]); \
        red_bf16x8<((i) & 1) * 8192 + ((i) >> 1) * 128>(opb, odd ? k[i][0] : r[i][0], odd ? k[i][1] : r[i][1], odd ? k[i][2] : r[i][2], odd ? k[i][3] : r[i][3])
        PACKLINE(0) __syncwarp(); PACKLINE(1) __syncwarp();
        REDLINE(0); __syncwarp(); PACKLINE(2) __syncwarp();
        REDLINE(1); __syncwarp(); PACKLINE(3) __syncwarp();
        REDLINE(2); REDLINE(3);
        }
    }
}

typedef CUresult (*EncodeTiledFn)(CUtensorMap*, CUtensorMapDataType, cuuint32_t, void*, const cuuint64_t*, const cuuint64_t*,
                                  const cuuint32_t*, const cuuint32_t*, CUtensorMapInterleave, CUtensorMapSwizzle,
                                  CUtensorMapL2promotion, CUtensorMapFloatOOBfill);

static void make_map(EncodeTiledFn enc, CUtensorMap* m, const void* base, uint64_t cols, uint64_t rows, uint32_t box_rows,
                     CUtensorMapSwizzle sw = CU_TENSOR_MAP_SWIZZLE_128B, uint32_t box_cols = 64,
                     CUtensorMapL2promotion promo = CU_TENSOR_MAP_L2_PROMOTION_L2_128B) {
    cuuint64_t dims[2] = {cols, rows};
    cuuint64_t str[1] = {cols * 2};
    cuuint32_t box[2] = {box_cols, box_rows};
    cuuint32_t es[2] = {1, 1};
    enc(m, CU_TENSOR_MAP_DATA_TYPE_BFLOAT16, 2, (void*)base, dims, str, box, es, CU_TENSOR_MAP_INTERLEAVE_NONE,
        sw, promo, CU_TENSOR_MAP_FLOAT_OOB_FILL_NONE);
}

static void make_map_chunks(EncodeTiledFn enc, CUtensorMap* m, const void* base, uint64_t rows, uint32_t box_rows, uint32_t n = 1) {
    cuuint64_t dims[3] = {64, rows, 8};
    cuuint64_t str[2] = {D_ * 2, 128};
    cuuint32_t box[3] = {64, box_rows, n};
    cuuint32_t es[3] = {1, 1, 1};
    enc(m, CU_TENSOR_MAP_DATA_TYPE_BFLOAT16, 3, (void*)base, dims, str, box, es, CU_TENSOR_MAP_INTERLEAVE_NONE,
        CU_TENSOR_MAP_SWIZZLE_128B, CU_TENSOR_MAP_L2_PROMOTION_L2_128B, CU_TENSOR_MAP_FLOAT_OOB_FILL_NONE);
}

static void make_map_out(EncodeTiledFn enc, CUtensorMap* m, const void* base) {
    cuuint64_t dims[4] = {D_, 4, 2, S_ / 8};
    cuuint64_t str[3] = {2 * D_ * 2, D_ * 2, 8 * D_ * 2};
    cuuint32_t box[4] = {64, 4, 2, 2};
    cuuint32_t es[4] = {1, 1, 1, 1};
    enc(m, CU_TENSOR_MAP_DATA_TYPE_BFLOAT16, 4, (void*)base, dims, str, box, es, CU_TENSOR_MAP_INTERLEAVE_NONE,
        CU_TENSOR_MAP_SWIZZLE_128B, CU_TENSOR_MAP_L2_PROMOTION_NONE, CU_TENSOR_MAP_FLOAT_OOB_FILL_NONE);
}

extern "C" void kernel_launch(void* const* d_in, const int* in_sizes, int n_in, void* d_out, int out_size) {
    (void)in_sizes; (void)n_in; (void)out_size;
    static EncodeTiledFn enc = nullptr;
    static bool fused_ok = false;
    static void* ab_ptr = nullptr;
    if (!enc) {
        void* fn = nullptr;
        cudaDriverEntryPointQueryResult q;
        cudaGetDriverEntryPoint("cuTensorMapEncodeTiled", &fn, cudaEnableDefault, &q);
        enc = (EncodeTiledFn)fn;
        cudaGetSymbolAddress(&ab_ptr, g_s);
        cudaFuncSetAttribute(fused_kernel, cudaFuncAttributeMaxDynamicSharedMemorySize, SMEM_BYTES);
        int dev = 0, nsm = 0, ncl = 0;
        cudaGetDevice(&dev);
        cudaDeviceGetAttribute(&nsm, cudaDevAttrMultiProcessorCount, dev);
        cudaLaunchConfig_t cfg = {};
        cfg.gridDim = dim3(132); cfg.blockDim = dim3(NTHREADS); cfg.dynamicSmemBytes = SMEM_BYTES;
        cudaLaunchAttribute at;
        at.id = cudaLaunchAttributeClusterDimension;
        at.val.clusterDim.x = 2; at.val.clusterDim.y = 1; at.val.clusterDim.z = 1;
        cfg.attrs = &at; cfg.numAttrs = 1;
        fused_ok = cudaOccupancyMaxActiveClusters(&ncl, fused_kernel, &cfg) == cudaSuccess && nsm == 132 && ncl == 66;
        (void)cudaGetLastError();
    }
    if (!fused_ok) {
        const bf16* const* in = (const bf16* const*)d_in;
        fb_hidden<<<S_, D_, 0, cudaStreamPerThread>>>(in[0], in[3], in[4], in[10], in[6]);
        fb_ffn1<<<F_ / 128, 128, 0, cudaStreamPerThread>>>(in[0], in[7], in[8]);
        fb_ffn2<<<D_ / 64, 64, 0, cudaStreamPerThread>>>(in[9]);
        fb_seq<<<S_, D_, 0, cudaStreamPerThread>>>(in[0], in[1], in[2], (bf16*)d_out);
        return;
    }
    Params p;
    p.s = (Scratch*)ab_ptr;
    p.x = (const bf16*)d_in[0];
    p.w_r = (const bf16*)d_in[6];
    p.wg = (const bf16*)d_in[7];
    p.wu = (const bf16*)d_in[8];
    p.wd = (const bf16*)d_in[9];
    p.gate_w = (const bf16*)d_in[10];
    p.out = (bf16*)d_out;
    make_map_chunks(enc, &p.mX1, d_in[0], S_, 64);
    make_map_chunks(enc, &p.mX2, d_in[0], S_, 64, 2);
    make_map(enc, &p.mCre, d_in[1], S_, S_, 128);
    make_map(enc, &p.mCim, d_in[2], S_, S_, 128);
    make_map_chunks(enc, &p.mDre, d_in[3], D_, 128);
    make_map_chunks(enc, &p.mDim, d_in[4], D_, 128);
    make_map(enc, &p.mAB, ab_ptr, 64, 8 * 32 * 128, 64, CU_TENSOR_MAP_SWIZZLE_NONE);
    make_map_out(enc, &p.mOut, d_out);
    make_map(enc, &p.mWg, d_in[7], F_, D_, 64, CU_TENSOR_MAP_SWIZZLE_NONE, 32, WPROMO);
    make_map(enc, &p.mWu, d_in[8], F_, D_, 64, CU_TENSOR_MAP_SWIZZLE_NONE, 32, WPROMO);
    make_map(enc, &p.mWd, d_in[9], D_, F_, 8, CU_TENSOR_MAP_SWIZZLE_NONE, 256);
    fused_kernel<<<132, NTHREADS, SMEM_BYTES, cudaStreamPerThread>>>(p);
}
```

```cpp
#include <cuda_runtime.h>
#include <cuda.h>
#include <cuda_bf16.h>
#include <stdint.h>

typedef __nv_bfloat16 bf16;

#define PACE 250
#define ORD 0
#define PE 0
#define OLS 1
#define HINT_AT 400
#define PRIO 0
#define SK 5
#define PF_T0 3000
#define PF_DT 1700
#define FFN_S0 4
#define FFN_S1 11
#define NI0 0
#define INIT_T0 0
#define INIT_DT 400
#define W1FIRST 1
#define THR 1
#define TSD 1500
#define KC 1
#define PAUSE 0
#define PFA_T 0
#define PFA_S 0
#define HINTM 5
#define GOK 1
#define PFX 1
#define ROT 0
#define LOWP 1
#define PFL 0
#define TRED 1
#define RSW 1
#define MAP4 1
#define PFD 1
#define PF_N0 4
#define FW0 7
#define FW1 3
#define VDT 0
#define WPROMO CU_TENSOR_MAP_L2_PROMOTION_L2_128B
#define GO0 1
#define NC0 2
#define FAST0 1
#define PK 8
#define PACE2 200
#define PTIME(c) ((c) <= PK ? (c) * PACE : PK * PACE + ((c) - PK) * PACE2)
#define POLL_AT 3
#define BFIRST 0
#define MPOLL 0
#define POLL_D 0
#define BGAP 350
#define LATEH 0
#define INITH 500
#define INITS 200
#define NARROW 1
#define TS_D 200
#define ADEL 300
#define ALN 0
#define ALW 48
#define NOMC 0
#define TORD 1
#define ECUT 0x54
#define NOFW 1
#define FILL 0
#define RDT 0
#define KEYS_NS 500
#define TT 0
#define TOFF 1850
#define TPER 512
#define FSP 2
#define ESTG 5
#define XL_AT 7
#define PD0 500
#define PD1 200
#define OL_T0 0
#define OL_DT 480
#define RS1 0
#define RSPLIT 1
#define GO_LATE 0
#define SUM_T0 15000
#define ROUTER_C 4
#define SHUF 1
#define POLL_NS 100

constexpr int S_ = 2048, D_ = 512, F_ = 1792;
constexpr int NCTA = 128;
constexpr int NTHREADS = 512;
constexpr int NSTAGE = 6;
constexpr int REGION = 32768;
constexpr int FFN_CTAS = F_ / 16;
constexpr uint32_t SPIN_LIMIT = 1u << 22;

constexpr int OFF_MISC = 7 * REGION;
constexpr int B_F = OFF_MISC;
constexpr int B_G0 = B_F + 64;
constexpr int B_G1 = B_G0 + 8;
constexpr int B_XE = B_G1 + 8;
constexpr int B_GO1 = B_XE + 8;
constexpr int B_SKEW0 = B_GO1 + 8;
constexpr int B_EPOCH = B_SKEW0 + 8;
constexpr int B_RETRY = B_EPOCH + 8;
constexpr int B_INIT = B_RETRY + 8;
constexpr int B_FULL = B_INIT + 8;
constexpr int B_EMPTY = B_FULL + 48;
constexpr int B_PUBI = B_EMPTY + 48;
constexpr int B_FREE = B_PUBI + 8;
constexpr int B_VD = B_FREE + 16;
constexpr int B_BL = B_VD + 8;
constexpr int B_TAIL = B_BL + 48;
constexpr int B_HX = B_TAIL + 8;
constexpr int B_FFN = B_HX + 8;
constexpr int B_ROLE = B_FFN + 40;
constexpr int B_SEEN = B_ROLE + 8;
constexpr int B_GATE = B_SEEN + 16;
constexpr int B_G2 = B_GATE + 8;
constexpr int B_FILL = B_G2 + 8;
constexpr int M_EPOCH = B_FILL + 8;
constexpr int M_T0 = OFF_MISC + 432;
constexpr int M_ROLE = M_EPOCH + 4;
constexpr int M_RED = OFF_MISC + 416;
constexpr int M_HX = OFF_MISC + 512;
constexpr int M_G = M_HX + 1024;
constexpr int M_UPD = M_G + 512;
constexpr int M_PROF = M_UPD + 512;
constexpr int SMEM_BYTES = 232448;
static_assert(M_ROLE + 4 <= M_RED && M_UPD + 512 <= SMEM_BYTES, "smem");

struct Scratch {
    unsigned char ab[8 * 32 * 16384];
    unsigned int hint[8 * 16 * 32];
    unsigned int sync[8 * 32];
    unsigned int ready[8 * 32];
    unsigned int gate[S_];
    unsigned int part[FFN_CTAS / 2 * D_];
    unsigned int phint[4 * 16 * 8];
    unsigned int keys[8 * NCTA];
    unsigned int epoch[NCTA + 4];
};
__device__ __align__(1024) Scratch g_s;

struct Params {
    Scratch* s;
    bf16* out;
    const bf16 *x, *gate_w, *w_r, *wg, *wu, *wd;
    CUtensorMap mDre, mDim, mX1, mX2, mCre, mCim, mAB, mOut, mWg, mWu, mWd;
};

__device__ __forceinline__ uint32_t smem_u32(const void* p) { return (uint32_t)__cvta_generic_to_shared(p); }
#define PROFL(i) do {} while (0)
#define PROFIF(slot, pred) do {} while (0)
#define PROF(slot) do {} while (0)
#define PROFG(slot) do {} while (0)

__device__ __forceinline__ void mbar_init(uint32_t bar, uint32_t cnt) {
    asm volatile("mbarrier.init.shared::cta.b64 [%0], %1;" ::"r"(bar), "r"(cnt) : "memory");
}
__device__ __forceinline__ void mbar_expect_tx(uint32_t bar, uint32_t bytes) {
    asm volatile("mbarrier.arrive.expect_tx.shared::cta.b64 _, [%0], %1;" ::"r"(bar), "r"(bytes) : "memory");
}
__device__ __forceinline__ void mbar_arrive(uint32_t bar) {
    asm volatile("mbarrier.arrive.shared::cta.b64 _, [%0];" ::"r"(bar) : "memory");
}
__device__ __forceinline__ void mbar_arrive_if(uint32_t bar, bool pred) {
    asm volatile("{.reg .pred p; setp.ne.b32 p, %1, 0; @p mbarrier.arrive.shared::cta.b64 _, [%0];}" ::"r"(bar), "r"((int)pred) : "memory");
}
__device__ __forceinline__ void mbar_arrive_warp(uint32_t bar) {
    __syncwarp();
    mbar_arrive_if(bar, (threadIdx.x & 31) == 0);
}
__device__ __forceinline__ void mbar_arrive_cluster_if(uint32_t bar, bool pred) {
    asm volatile("{.reg .pred p; setp.ne.b32 p, %1, 0; @p mbarrier.arrive.shared::cluster.b64 _, [%0], 1;}"
                 ::"r"(bar), "r"((int)pred) : "memory");
}
__device__ __forceinline__ uint32_t mapa(uint32_t a, uint32_t cta) {
    uint32_t r;
    asm volatile("mapa.shared::cluster.u32 %0, %1, %2;" : "=r"(r) : "r"(a), "r"(cta));
    return r;
}
__device__ __forceinline__ bool mbar_try(uint32_t bar, uint32_t parity) {
    uint32_t ok;
    asm volatile("{.reg .pred p; mbarrier.try_wait.parity.shared::cta.b64 p, [%1], %2; selp.u32 %0,1,0,p;}"
                 : "=r"(ok) : "r"(bar), "r"(parity) : "memory");
    return ok;
}
__device__ __forceinline__ bool mbar_test(uint32_t bar, uint32_t parity) {
    uint32_t ok;
    asm volatile("{.reg .pred p; mbarrier.test_wait.parity.shared::cta.b64 p, [%1], %2; selp.u32 %0,1,0,p;}"
                 : "=r"(ok) : "r"(bar), "r"(parity) : "memory");
    return ok;
}
__device__ __forceinline__ void mbar_wait(uint32_t bar, uint32_t parity) {
    asm volatile("{.reg .pred p, q; .reg .u32 n; mov.u32 n, 0;\n"
                 "W%=: mbarrier.try_wait.parity.shared::cta.b64 p, [%0], %1;\n"
                 "add.u32 n, n, 1; setp.lt.and.u32 q, n, %2, !p; @q bra W%=; @!p trap;}" ::"r"(bar), "r"(parity), "n"(SPIN_LIMIT) : "memory");
}
__device__ __forceinline__ void mbar_spin(uint32_t bar, uint32_t parity) {
    asm volatile("{.reg .pred p;\nW%=: mbarrier.try_wait.parity.shared::cta.b64 p, [%0], %1; @!p bra W%=;}" ::"r"(bar), "r"(parity) : "memory");
}
__device__ __forceinline__ void mbar_wait_cluster(uint32_t bar, uint32_t parity) {
    uint32_t n = 0, ok;
    do {
        asm volatile("{.reg .pred p; mbarrier.try_wait.parity.acquire.cluster.shared::cta.b64 p, [%1], %2; selp.u32 %0,1,0,p;}"
                     : "=r"(ok) : "r"(bar), "r"(parity) : "memory");
        if (++n > SPIN_LIMIT) __trap();
    } while (!ok);
}
__device__ __forceinline__ void tma2d(uint32_t dst, const CUtensorMap* m, int c0, int c1, uint32_t bar) {
    asm volatile("cp.async.bulk.tensor.2d.shared::cluster.global.mbarrier::complete_tx::bytes [%0], [%1, {%3,%4}], [%2];"
                 ::"r"(dst), "l"(m), "r"(bar), "r"(c0), "r"(c1) : "memory");
}
__device__ __forceinline__ void tma2d_elect(uint32_t dst, const CUtensorMap* m, int c0, int c1, uint32_t bar) {
    asm volatile("{.reg .pred p; elect.sync _|p, 0xffffffff;"
                 " @p cp.async.bulk.tensor.2d.shared::cluster.global.mbarrier::complete_tx::bytes [%0], [%1, {%3,%4}], [%2];}"
                 ::"r"(dst), "l"(m), "r"(bar), "r"(c0), "r"(c1) : "memory");
}
__device__ __forceinline__ void tma2d_pair_elect(uint32_t dst, const CUtensorMap* m, int c0, int c1, uint32_t bar) {
    asm volatile("{.reg .pred p; elect.sync _|p, 0xffffffff;"
                 " @p cp.async.bulk.tensor.2d.shared::cluster.global.mbarrier::complete_tx::bytes.multicast::cluster"
                 " [%0], [%1, {%3,%4}], [%2], %5;}" ::"r"(dst), "l"(m), "r"(bar), "r"(c0), "r"(c1), "h"((uint16_t)3) : "memory");
}
__device__ __forceinline__ void mbar_expect_tx_elect(uint32_t bar, uint32_t bytes) {
    asm volatile("{.reg .pred p; elect.sync _|p, 0xffffffff; @p mbarrier.arrive.expect_tx.shared::cta.b64 _, [%0], %1;}"
                 ::"r"(bar), "r"(bytes) : "memory");
}
__device__ __forceinline__ void tma3d(uint32_t dst, const CUtensorMap* m, int row, int chunk, uint32_t bar) {
    asm volatile("cp.async.bulk.tensor.3d.shared::cluster.global.mbarrier::complete_tx::bytes [%0], [%1, {%3,%4,%5}], [%2];"
                 ::"r"(dst), "l"(m), "r"(bar), "r"(0), "r"(row), "r"(chunk) : "memory");
}
__device__ __forceinline__ void tma2d_prefetch(const CUtensorMap* m, int c0, int c1) {
    asm volatile("cp.async.bulk.prefetch.tensor.2d.L2.global [%0, {%1,%2}];" ::"l"(m), "r"(c0), "r"(c1) : "memory");
}
__device__ __forceinline__ void fence_proxy_async_smem() { asm volatile("fence.proxy.async.shared::cta;" ::: "memory"); }
__device__ __forceinline__ void fence_proxy_async_gmem() { asm volatile("fence.proxy.async.global;" ::: "memory"); }
__device__ __forceinline__ void prefetch_l2(const void* p) { asm volatile("prefetch.global.L2 [%0];" ::"l"(p)); }
__device__ __forceinline__ uint32_t ld_relaxed(const void* p) {
    uint32_t v;
    asm volatile("ld.relaxed.gpu.global.u32 %0, [%1];" : "=r"(v) : "l"(p) : "memory");
    return v;
}
__device__ __forceinline__ uint4 ld_relaxed4(const void* p) {
    uint4 v;
    asm volatile("ld.relaxed.gpu.global.v4.u32 {%0,%1,%2,%3}, [%4];" : "=r"(v.x), "=r"(v.y), "=r"(v.z), "=r"(v.w) : "l"(p) : "memory");
    return v;
}
__device__ __forceinline__ uint4 ld_relaxed_b128(const void* p) {
    uint4 v;
    asm volatile("{.reg .b128 t; ld.relaxed.gpu.global.b128 t, [%4]; mov.b128 {%0,%1,%2,%3}, t;}"
                 : "=r"(v.x), "=r"(v.y), "=r"(v.z), "=r"(v.w) : "l"(p) : "memory");
    return v;
}
__device__ __forceinline__ uint4 ld_relaxed_b128_if(const void* p, bool pred) {
    uint4 v = make_uint4(0, 0, 0, 0);
    asm volatile("{.reg .b128 t; .reg .pred p; setp.ne.b32 p, %5, 0; mov.b128 t, {%0,%1,%2,%3};"
                 " @p ld.relaxed.gpu.global.b128 t, [%4]; mov.b128 {%0,%1,%2,%3}, t;}"
                 : "+r"(v.x), "+r"(v.y), "+r"(v.z), "+r"(v.w) : "l"(p), "r"((int)pred) : "memory");
    return v;
}
__device__ __forceinline__ void st_relaxed_b128(void* p, uint32_t x, uint32_t y, uint32_t z, uint32_t w) {
    asm volatile("{.reg .b128 t; .reg .b64 a, b; mov.b64 a, {%1,%2}; mov.b64 b, {%3,%4}; mov.b128 t, {a, b};"
                 " st.relaxed.gpu.global.b128 [%0], t;}" ::"l"(p), "r"(x), "r"(y), "r"(z), "r"(w) : "memory");
}
__device__ __forceinline__ void st_relaxed(unsigned int* p, uint32_t v) {
    asm volatile("st.relaxed.gpu.global.u32 [%0], %1;" ::"l"(p), "r"(v) : "memory");
}
__device__ __forceinline__ void st_relaxed_if(unsigned int* p, uint32_t v, bool pred) {
    asm volatile("{.reg .pred p; setp.ne.b32 p, %2, 0; @p st.relaxed.gpu.global.u32 [%0], %1;}" ::"l"(p), "r"(v), "r"((int)pred) : "memory");
}
__device__ __forceinline__ void red_inc_if(unsigned int* p, bool pred) {
    asm volatile("{.reg .pred p; setp.ne.b32 p, %1, 0; @p red.relaxed.gpu.global.inc.u32 [%0], 0xffffffff;}" ::"l"(p), "r"((int)pred) : "memory");
}
__device__ __forceinline__ void st_key(unsigned int* p, uint32_t v) {
    asm volatile("{.reg .b32 old; atom.relaxed.gpu.global.exch.b32 old, [%0], %1;}" ::"l"(p), "r"(v) : "memory");
}
__device__ __forceinline__ uint32_t tagf(float v, uint32_t par) { return (__float_as_uint(v) & ~1u) | par; }
__device__ __forceinline__ uint4 wait_tags(const unsigned int* p, int bit, uint32_t par) {
    uint32_t n = 0;
    while (true) {
        const uint4 v = ld_relaxed4(p);
        const uint32_t m = par ? (v.x & v.y & v.z & v.w) : ~(v.x | v.y | v.z | v.w);
        if (__all_sync(0xffffffffu, (m >> bit) & 1u)) return v;
        __nanosleep(POLL_NS);
        if (++n > SPIN_LIMIT) __trap();
    }
}
template <int SLEEP>
__device__ __forceinline__ void wait_counters(const unsigned int* p, uint32_t want) {
    uint32_t n = 0;
    while (!__all_sync(0xffffffffu, (int)(ld_relaxed(p) - want) >= 0)) {
        if (SLEEP) __nanosleep(SLEEP);
        if (++n > SPIN_LIMIT) __trap();
    }
    asm volatile("fence.acquire.gpu;" ::: "memory");
}
__device__ __forceinline__ void red_release_add(unsigned int* p, uint32_t v) {
    asm volatile("red.release.gpu.global.add.u32 [%0], %1;" ::"l"(p), "r"(v) : "memory");
}
__device__ __forceinline__ void named_bar(int id, int n) { asm volatile("bar.sync %0, %1;" ::"r"(id), "r"(n) : "memory"); }
template <int OFF>
__device__ __forceinline__ uint4 ldg_nc_off(const void* p) {
    uint4 v;
    asm volatile("ld.global.nc.v4.u32 {%0,%1,%2,%3}, [%4+%5];" : "=r"(v.x), "=r"(v.y), "=r"(v.z), "=r"(v.w) : "l"(p), "n"(OFF));
    return v;
}
template <int OFF>
__device__ __forceinline__ void stg_off_if(void* p, const uint4& v, bool pred) {
    asm volatile("{.reg .pred p; setp.ne.b32 p, %6, 0; @p st.global.v4.u32 [%0+%5], {%1,%2,%3,%4};}"
                 ::"l"(p), "r"(v.x), "r"(v.y), "r"(v.z), "r"(v.w), "n"(OFF), "r"((int)pred) : "memory");
}
template <int OFF>
__device__ __forceinline__ void stg_off(void* p, const uint4& v) {
    asm volatile("st.global.v4.u32 [%0+%5], {%1,%2,%3,%4};" ::"l"(p), "r"(v.x), "r"(v.y), "r"(v.z), "r"(v.w), "n"(OFF) : "memory");
}
__device__ __forceinline__ void sts128(uint32_t a, const uint4& v) {
    asm volatile("st.shared.v4.u32 [%0], {%1,%2,%3,%4};" ::"r"(a), "r"(v.x), "r"(v.y), "r"(v.z), "r"(v.w) : "memory");
}
__device__ __forceinline__ uint4 lds128(uint32_t a) {
    uint4 v;
    asm volatile("ld.shared.v4.u32 {%0,%1,%2,%3}, [%4];" : "=r"(v.x), "=r"(v.y), "=r"(v.z), "=r"(v.w) : "r"(a) : "memory");
    return v;
}
__device__ __forceinline__ float selpf(float a, float b, bool p) {
    float r;
    asm("{.reg .pred q; setp.ne.b32 q, %3, 0; selp.f32 %0, %1, %2, q;}" : "=f"(r) : "f"(a), "f"(b), "r"((int)p));
    return r;
}
template <int N, int MASK, int SZ>
__device__ __forceinline__ void halve(float (&a)[SZ]) {
    const bool up = threadIdx.x & MASK;
#pragma unroll
    for (int j = 0; j < N; j++) a[j] = selpf(a[N + j], a[j], up) + __shfl_xor_sync(0xffffffffu, selpf(a[j], a[N + j], up), MASK);
}
__device__ __forceinline__ float bflo(uint32_t u) { return __uint_as_float(u << 16); }
__device__ __forceinline__ float bfhi(uint32_t u) { return __uint_as_float(u & 0xffff0000u); }
__device__ __forceinline__ uint32_t pack_bf16(float lo, float hi) {
    uint32_t r;
    asm("cvt.rn.bf16x2.f32 %0, %1, %2;" : "=r"(r) : "f"(hi), "f"(lo));
    return r;
}
__device__ __forceinline__ uint32_t hfma2_bf16(uint32_t a, uint32_t b, uint32_t c) {
    uint32_t r;
    asm("fma.rn.bf16x2 %0, %1, %2, %3;" : "=r"(r) : "r"(a), "r"(b), "r"(c));
    return r;
}
__device__ __forceinline__ uint32_t hmul2_bf16(uint32_t a, uint32_t b) {
    uint32_t r;
    asm("mul.rn.bf16x2 %0, %1, %2;" : "=r"(r) : "r"(a), "r"(b));
    return r;
}
__device__ __forceinline__ float sigmoidf_(float v) { return __frcp_rn(1.0f + __expf(-v)); }

__device__ __forceinline__ void wg_fence() { asm volatile("wgmma.fence.sync.aligned;" ::: "memory"); }
__device__ __forceinline__ void wg_commit() { asm volatile("wgmma.commit_group.sync.aligned;" ::: "memory"); }
template <int N> __device__ __forceinline__ void wg_wait() { asm volatile("wgmma.wait_group.sync.aligned %0;" ::"n"(N) : "memory"); }
__device__ __forceinline__ uint64_t desc64_lo(uint32_t lo) { return (uint64_t)lo | (0x80000020ull << 32); }
__device__ __forceinline__ uint64_t desc_lo(uint32_t lo) { return (uint64_t)lo | (0x40000040ull << 32); }
template <int LO, int HI, int N>
__device__ __forceinline__ void fence_regs(float (&d)[N]) {
#pragma unroll
    for (int i = LO; i < HI; i++) asm volatile("" : "+f"(d[i])::"memory");
}
template <int TB = 1>
__device__ __forceinline__ void wgmma128(float (&d)[64], uint64_t da, uint64_t db, int scaleD) {
    asm volatile(
        "{ .reg .pred p; setp.ne.b32 p, %66, 0;\n"
        "wgmma.mma_async.sync.aligned.m64n128k16.f32.bf16.bf16 "
        "{%0,%1,%2,%3,%4,%5,%6,%7,%8,%9,%10,%11,%12,%13,%14,%15,%16,%17,%18,%19,%20,%21,%22,%23,%24,%25,%26,%27,%28,%29,%30,%31,"
        "%32,%33,%34,%35,%36,%37,%38,%39,%40,%41,%42,%43,%44,%45,%46,%47,%48,%49,%50,%51,%52,%53,%54,%55,%56,%57,%58,%59,%60,%61,%62,%63}, "
        "%64, %65, p, 1, 1, 0, %67;\n}"
        : "+f"(d[0]), "+f"(d[1]), "+f"(d[2]), "+f"(d[3]), "+f"(d[4]), "+f"(d[5]), "+f"(d[6]), "+f"(d[7]),
          "+f"(d[8]), "+f"(d[9]), "+f"(d[10]), "+f"(d[11]), "+f"(d[12]), "+f"(d[13]), "+f"(d[14]), "+f"(d[15]),
          "+f"(d[16]), "+f"(d[17]), "+f"(d[18]), "+f"(d[19]), "+f"(d[20]), "+f"(d[21]), "+f"(d[22]), "+f"(d[23]),
          "+f"(d[24]), "+f"(d[25]), "+f"(d[26]), "+f"(d[27]), "+f"(d[28]), "+f"(d[29]), "+f"(d[30]), "+f"(d[31]),
          "+f"(d[32]), "+f"(d[33]), "+f"(d[34]), "+f"(d[35]), "+f"(d[36]), "+f"(d[37]), "+f"(d[38]), "+f"(d[39]),
          "+f"(d[40]), "+f"(d[41]), "+f"(d[42]), "+f"(d[43]), "+f"(d[44]), "+f"(d[45]), "+f"(d[46]), "+f"(d[47]),
          "+f"(d[48]), "+f"(d[49]), "+f"(d[50]), "+f"(d[51]), "+f"(d[52]), "+f"(d[53]), "+f"(d[54]), "+f"(d[55]),
          "+f"(d[56]), "+f"(d[57]), "+f"(d[58]), "+f"(d[59]), "+f"(d[60]), "+f"(d[61]), "+f"(d[62]), "+f"(d[63])
        : "l"(da), "l"(db), "r"(scaleD), "n"(TB));
}

__device__ __forceinline__ void mbar_init_elect(uint32_t bar, uint32_t cnt) {
    asm volatile("{.reg .pred p; elect.sync _|p, 0xffffffff; @p mbarrier.init.shared::cta.b64 [%0], %1;}" ::"r"(bar), "r"(cnt) : "memory");
}
__device__ __forceinline__ void mbar_arrive_elect(uint32_t bar) {
    asm volatile("{.reg .pred p; elect.sync _|p, 0xffffffff; @p mbarrier.arrive.shared::cta.b64 _, [%0];}" ::"r"(bar) : "memory");
}
__device__ __forceinline__ void tma3d_elect(uint32_t dst, const CUtensorMap* m, int row, int chunk, uint32_t bar) {
    asm volatile("{.reg .pred p; elect.sync _|p, 0xffffffff;"
                 " @p cp.async.bulk.tensor.3d.shared::cluster.global.mbarrier::complete_tx::bytes [%0], [%1, {%3,%4,%5}], [%2];}"
                 ::"r"(dst), "l"(m), "r"(bar), "r"(0), "r"(row), "r"(chunk) : "memory");
}
template <int N>
__device__ __forceinline__ void mbar_arrive_n_elect(uint32_t bar) {
    asm volatile("{.reg .pred p; elect.sync _|p, 0xffffffff; @p mbarrier.arrive.shared::cta.b64 _, [%0], %1;}" ::"r"(bar), "n"(N) : "memory");
}
template <int N>
__device__ __forceinline__ void bulk_store_elect(void* dst, uint32_t src) {
    asm volatile("{.reg .pred p; elect.sync _|p, 0xffffffff; @p cp.async.bulk.global.shared::cta.bulk_group [%0], [%1], %2;}"
                 ::"l"(dst), "r"(src), "n"(N) : "memory");
}
__device__ __forceinline__ void bulk_wait_read() {
    asm volatile("cp.async.bulk.commit_group; cp.async.bulk.wait_group.read 0;" ::: "memory");
    __syncwarp();
}
template <int N>
__device__ __forceinline__ void release_pair(uint32_t bar, uint32_t rbar, bool pred) {
    asm volatile("{.reg .pred p; setp.ne.b32 p, %2, 0; @p mbarrier.arrive.shared::cta.b64 _, [%0], %3;"
                 " @p mbarrier.arrive.shared::cluster.b64 _, [%1], %3;}" ::"r"(bar), "r"(rbar), "r"((int)pred), "n"(N) : "memory");
}
template <int OFF>
__device__ __forceinline__ void red_bf16x8(void* p, uint32_t x, uint32_t y, uint32_t z, uint32_t w) {
    asm volatile("red.relaxed.gpu.global.add.noftz.v4.bf16x2 [%0+%5], {%1,%2,%3,%4};"
                 ::"l"(p), "r"(x), "r"(y), "r"(z), "r"(w), "n"(OFF) : "memory");
}
template <int OFF>
__device__ __forceinline__ uint32_t lds32_off(uint32_t a) {
    uint32_t v;
    asm volatile("ld.shared.u32 %0, [%1+%2];" : "=r"(v) : "r"(a), "n"(OFF) : "memory");
    return v;
}
template <int OFF>
__device__ __forceinline__ void sts128_off(uint32_t a, const uint4& v) {
    asm volatile("st.shared.v4.u32 [%0+%5], {%1,%2,%3,%4};" ::"r"(a), "r"(v.x), "r"(v.y), "r"(v.z), "r"(v.w), "n"(OFF) : "memory");
}

__device__ __forceinline__ uint32_t gtime() {
    uint32_t t;
    asm volatile("mov.u32 %0, %%globaltimer_lo;" : "=r"(t));
    return t;
}
__device__ __forceinline__ uint2 ld_relaxed2(const void* p) {
    uint2 v;
    asm volatile("{.reg .b64 t; ld.relaxed.gpu.global.b64 t, [%2]; mov.b64 {%0,%1}, t;}" : "=r"(v.x), "=r"(v.y) : "l"(p) : "memory");
    return v;
}
__device__ __forceinline__ void st_stamp_if(unsigned int* p, uint32_t v, bool pred) {
    asm volatile("{.reg .pred p; .reg .b32 t; .reg .b64 w; setp.ne.b32 p, %2, 0; mov.u32 t, %%globaltimer_lo; mov.b64 w, {%1, t};"
                 " @p st.relaxed.gpu.global.b64 [%0], w;}" ::"l"(p), "r"(v), "r"((int)pred) : "memory");
}
__device__ __forceinline__ void sched_cut() {
    asm volatile("{.reg .pred p; .reg .u64 t; .reg .u32 a, b;\nC%=: mov.u64 t, %%clock64; mov.b64 {a, b}, t; setp.eq.u32 p, a, %0; @p bra C%=;}" ::"n"(0) : "memory");
}
__device__ __forceinline__ uint32_t pin(uint32_t v) { return __shfl_xor_sync(0xffffffffu, v, 0); }
template <class T>
__device__ __forceinline__ T* pin(T* p) { return (T*)__shfl_xor_sync(0xffffffffu, (unsigned long long)p, 0); }
template <class T>
__device__ __forceinline__ T* pin_uniform(T* p) { return (T*)__shfl_sync(0xffffffffu, (unsigned long long)p, 0); }
__device__ __forceinline__ uint32_t stale_tags(uint32_t a, uint32_t par) {
    uint32_t r;
    asm volatile("{.reg .b32 v<16>;\n"
                 "ld.shared.u32 v0, [%1]; ld.shared.u32 v1, [%1+256]; ld.shared.u32 v2, [%1+512]; ld.shared.u32 v3, [%1+768];\n"
                 "ld.shared.u32 v4, [%1+4096]; ld.shared.u32 v5, [%1+4352]; ld.shared.u32 v6, [%1+4608]; ld.shared.u32 v7, [%1+4864];\n"
                 "ld.shared.u32 v8, [%1+8192]; ld.shared.u32 v9, [%1+8448]; ld.shared.u32 v10, [%1+8704]; ld.shared.u32 v11, [%1+8960];\n"
                 "ld.shared.u32 v12, [%1+12288]; ld.shared.u32 v13, [%1+12544]; ld.shared.u32 v14, [%1+12800]; ld.shared.u32 v15, [%1+13056];\n"
                 "lop3.b32 v0, v0, v1, %2, 0x7e; lop3.b32 v2, v2, v3, %2, 0x7e; lop3.b32 v4, v4, v5, %2, 0x7e; lop3.b32 v6, v6, v7, %2, 0x7e;\n"
                 "lop3.b32 v8, v8, v9, %2, 0x7e; lop3.b32 v10, v10, v11, %2, 0x7e; lop3.b32 v12, v12, v13, %2, 0x7e; lop3.b32 v14, v14, v15, %2, 0x7e;\n"
                 "lop3.b32 v0, v0, v2, v4, 0xfe; lop3.b32 v6, v6, v8, v10, 0xfe; lop3.b32 v0, v0, v6, v12, 0xfe; or.b32 %0, v0, v14;}"
                 : "=r"(r) : "r"(a), "r"(par) : "memory");
    return r;
}

__device__ __forceinline__ void wgmma128_rs(float (&d)[64], const uint32_t* a, uint64_t db, int scaleD) {
    asm volatile(
        "{ .reg .pred p; setp.ne.b32 p, %69, 0;\n"
        "wgmma.mma_async.sync.aligned.m64n128k16.f32.bf16.bf16 "
        "{%0,%1,%2,%3,%4,%5,%6,%7,%8,%9,%10,%11,%12,%13,%14,%15,%16,%17,%18,%19,%20,%21,%22,%23,%24,%25,%26,%27,%28,%29,%30,%31,"
        "%32,%33,%34,%35,%36,%37,%38,%39,%40,%41,%42,%43,%44,%45,%46,%47,%48,%49,%50,%51,%52,%53,%54,%55,%56,%57,%58,%59,%60,%61,%62,%63}, "
        "{%64,%65,%66,%67}, %68, p, 1, 1, 0;\n}"
        : "+f"(d[0]), "+f"(d[1]), "+f"(d[2]), "+f"(d[3]), "+f"(d[4]), "+f"(d[5]), "+f"(d[6]), "+f"(d[7]),
          "+f"(d[8]), "+f"(d[9]), "+f"(d[10]), "+f"(d[11]), "+f"(d[12]), "+f"(d[13]), "+f"(d[14]), "+f"(d[15]),
          "+f"(d[16]), "+f"(d[17]), "+f"(d[18]), "+f"(d[19]), "+f"(d[20]), "+f"(d[21]), "+f"(d[22]), "+f"(d[23]),
          "+f"(d[24]), "+f"(d[25]), "+f"(d[26]), "+f"(d[27]), "+f"(d[28]), "+f"(d[29]), "+f"(d[30]), "+f"(d[31]),
          "+f"(d[32]), "+f"(d[33]), "+f"(d[34]), "+f"(d[35]), "+f"(d[36]), "+f"(d[37]), "+f"(d[38]), "+f"(d[39]),
          "+f"(d[40]), "+f"(d[41]), "+f"(d[42]), "+f"(d[43]), "+f"(d[44]), "+f"(d[45]), "+f"(d[46]), "+f"(d[47]),
          "+f"(d[48]), "+f"(d[49]), "+f"(d[50]), "+f"(d[51]), "+f"(d[52]), "+f"(d[53]), "+f"(d[54]), "+f"(d[55]),
          "+f"(d[56]), "+f"(d[57]), "+f"(d[58]), "+f"(d[59]), "+f"(d[60]), "+f"(d[61]), "+f"(d[62]), "+f"(d[63])
        : "r"(a[0]), "r"(a[1]), "r"(a[2]), "r"(a[3]), "l"(db), "r"(scaleD));
}
__device__ __forceinline__ void ldsm4(uint32_t* r, uint32_t a) {
    asm volatile("ldmatrix.sync.aligned.m8n8.x4.shared.b16 {%0,%1,%2,%3}, [%4];" : "=r"(r[0]), "=r"(r[1]), "=r"(r[2]), "=r"(r[3]) : "r"(a) : "memory");
}

__device__ __forceinline__ void load_b(uint32_t dst, const CUtensorMap* m, int row, uint32_t bar) {
    tma2d_pair_elect(dst, m, 0, row, bar);
}
__device__ __forceinline__ int tile_of_step(int step, int own, int kh) {
    const int u = step >= 17 ? step - 17 : step - 1 - (step > OLS);
    int e = (u + (u >= ((own - 8 * kh) & 14) ? 2 : 0) + 8 * kh) & 15;
    if (u == 14) e = own ^ 1;
    if (step == 0 || step == OLS) e = own;
    return e + (step >= 17 || step == OLS ? 16 : 0);
}
__device__ __forceinline__ uint32_t router_key(float score, int row) {
    const float r = score + 0.0f;
    uint32_t u = pack_bf16(r, 0.f) & 0xffffu;
    u = (u & 0x8000u) ? (~u & 0xffffu) : (u | 0x8000u);
    if (r != r) u = 0;
    return (u << 16) | (uint32_t)(0x7fff - row);
}

#define g_fb_h ((float*)g_s.part)
#define g_fb_upd (g_fb_h + 2048)
#define g_fb_gate (g_fb_h + 4096)
#define g_fb_keys (g_s.part + 8192)
__global__ void fb_hidden(const bf16* x, const bf16* dre, const bf16* dim, const bf16* gw, const bf16* wr) {
    __shared__ float xs[D_];
    const int s = blockIdx.x, t = threadIdx.x;
    xs[t] = __bfloat162float(x[s * D_ + t]);
    __syncthreads();
    float a = 0.f, b = 0.f;
    for (int d = 0; d < D_; d++) { a = fmaf(xs[d], __bfloat162float(dre[t * D_ + d]), a); b = fmaf(xs[d], __bfloat162float(dim[t * D_ + d]), b); }
    ((bf16*)g_s.ab)[s * 1024 + t] = __float2bfloat16(a);
    ((bf16*)g_s.ab)[s * 1024 + 512 + t] = __float2bfloat16(b);
    if (t == 0) {
        float u = 0.f, v = 0.f;
        for (int d = 0; d < D_; d++) { u = fmaf(xs[d], __bfloat162float(gw[d]), u); v = fmaf(xs[d], __bfloat162float(wr[d]), v); }
        g_fb_gate[s] = sigmoidf_(u);
        g_fb_keys[s] = router_key(v, s);
    }
}
__device__ uint32_t fb_best() {
    uint32_t k = 0;
    for (int i = 0; i < S_; i++) k = max(k, g_fb_keys[i]);
    return k;
}
__global__ void fb_ffn1(const bf16* x, const bf16* wg, const bf16* wu) {
    const int f = blockIdx.x * blockDim.x + threadIdx.x, idx = 0x7fff - (int)(fb_best() & 0x7fffu);
    float a = 0.f, b = 0.f;
    for (int d = 0; d < D_; d++) {
        const float xv = __bfloat162float(x[idx * D_ + d]);
        a = fmaf(xv, __bfloat162float(wg[d * F_ + f]), a); b = fmaf(xv, __bfloat162float(wu[d * F_ + f]), b);
    }
    g_fb_h[f] = a * sigmoidf_(a) * b;
}
__global__ void fb_ffn2(const bf16* wd) {
    const int e = blockIdx.x * blockDim.x + threadIdx.x;
    const uint32_t u = fb_best() >> 16, rb = (u & 0x8000u) ? (u & 0x7fffu) : (~u & 0xffffu);
    float a = 0.f;
    for (int f = 0; f < F_; f++) a = fmaf(g_fb_h[f], __bfloat162float(wd[f * D_ + e]), a);
    g_fb_upd[e] = a * sigmoidf_(__uint_as_float(rb << 16));
}
__global__ void fb_seq(const bf16* x, const bf16* cre, const bf16* cim, bf16* out) {
    __shared__ float c[2][S_];
    __shared__ int idx;
    const int t = blockIdx.x, e = threadIdx.x;
    for (int i = e; i < S_; i += D_) { c[0][i] = __bfloat162float(cre[t * S_ + i]); c[1][i] = __bfloat162float(cim[t * S_ + i]); }
    if (e == 0) idx = 0x7fff - (int)(fb_best() & 0x7fffu);
    __syncthreads();
    float y = 0.f;
    for (int s = 0; s < S_; s++)
        y += c[0][s] * __bfloat162float(((const bf16*)g_s.ab)[s * 1024 + e]) - c[1][s] * __bfloat162float(((const bf16*)g_s.ab)[s * 1024 + 512 + e]);
    const float g = g_fb_gate[t];
    out[t * D_ + e] = __float2bfloat16(g * y + (1.f - g) * (__bfloat162float(x[t * D_ + e]) + (t == idx ? g_fb_upd[e] : 0.f)));
}

__device__ __forceinline__ void spare_job(const Params& p, unsigned char* smem, int sp, uint32_t tstart) {
    const int tid = threadIdx.x, warp = tid >> 5, lane = tid & 31;
    const uint32_t e1 = *(volatile unsigned int*)&p.s->epoch[NCTA + sp] + 1u;
    const uint32_t par = e1 & 1u;
    uint32_t* red = (uint32_t*)smem;
    __syncthreads();
    if (tid == 0) *(volatile unsigned int*)&p.s->epoch[NCTA + sp] = e1;
#pragma unroll 1
    for (int k = 0; k < (PFD ? 0 : 6); k++) {
        const char* src = k < 2 ? (const char*)p.wd + (sp * 2 + k) * 229376
                                : (const char*)((sp & 1) ? p.wu : p.wg) + ((sp >> 1) * 4 + k - 2) * 229376;
        while ((uint32_t)clock64() - tstart < PF_T0 + k * PF_DT) __nanosleep(LOWP ? 200 : 20);
        if (tid >= 448) {
            if (tid < 455) asm volatile("cp.async.bulk.prefetch.L2.global [%0], 16384;" ::"l"(src + (tid - 448) * 16384) : "memory");
        } else {
            prefetch_l2(src + 114688 + tid * 128);
            prefetch_l2(src + 172032 + tid * 128);
        }
        __syncwarp();
    }
    if (tid == 0) PROF(1);
    if (PFD) while ((uint32_t)clock64() - tstart < 13000) __nanosleep(500);
    if (warp == 0) {
        const uint4 k4 = wait_tags(p.s->keys + lane * 4, 15, par);
        const uint32_t k = __reduce_max_sync(0xffffffffu, max(max(k4.x, k4.y), max(k4.z, k4.w)));
        const int idx = 0x7fff - (int)(k & 0x7fffu);
        const uint4 g4 = wait_tags(p.s->gate + (idx & ~3), 0, par);
        const uint32_t gw = (idx & 2) ? ((idx & 1) ? g4.w : g4.z) : ((idx & 1) ? g4.y : g4.x);
        const uint32_t u = k >> 16;
        const uint32_t rb = (u & 0x8000u) ? (u & 0x7fffu) : (~u & 0xffffu);
        if (lane == 0) {
            red[16] = idx;
            red[17] = __float_as_uint((1.f - __uint_as_float(gw & ~1u)) * sigmoidf_(__uint_as_float(rb << 16)));
        }
    }
    while ((uint32_t)clock64() - tstart < SUM_T0) __nanosleep(200);
    float4 s = make_float4(0.f, 0.f, 0.f, 0.f);
    if (warp < 14) {
        uint32_t n = 0;
        while ((int)(ld_relaxed(p.s->phint + (sp * 16 + warp) * 8) - e1 * 8u) < 0) {
            __nanosleep(40);
            if (++n > SPIN_LIMIT) __trap();
        }
        if (tid == 0) PROF(2);
        const unsigned int* src = p.s->part + warp * 4 * D_ + sp * 128 + lane * 4;
        uint4 v[4];
        while (true) {
            uint32_t bad = 0;
#pragma unroll
            for (int i = 0; i < 4; i++) v[i] = ld_relaxed4(src + i * D_);
#pragma unroll
            for (int i = 0; i < 4; i++) bad |= (v[i].x ^ par) | (v[i].y ^ par) | (v[i].z ^ par) | (v[i].w ^ par);
            if (!__any_sync(0xffffffffu, bad & 1u)) break;
            if (++n > SPIN_LIMIT) __trap();
        }
#pragma unroll
        for (int i = 0; i < 4; i++) {
            s.x += __uint_as_float(v[i].x); s.y += __uint_as_float(v[i].y);
            s.z += __uint_as_float(v[i].z); s.w += __uint_as_float(v[i].w);
        }
    } else if (warp == 14) {
        wait_counters<100>(p.s->ready + (lane & 7) * 32, e1 * 16u);
    }
    float* acc = (float*)(smem + 1024);
    *(float4*)&acc[warp * 128 + lane * 4] = s;
    __syncthreads();
    if (tid < 64) {
        float t0 = 0.f, t1 = 0.f;
#pragma unroll
        for (int i = 0; i < 14; i++) {
            const float2 z = *(const float2*)&acc[i * 128 + tid * 2];
            t0 += z.x; t1 += z.y;
        }
        const float f = __uint_as_float(red[17]);
        asm volatile("red.relaxed.gpu.global.add.noftz.bf16x2 [%0], %1;"
                     ::"l"(p.out + red[16] * D_ + sp * 128 + tid * 2), "r"(pack_bf16(t0 * f, t1 * f)) : "memory");
    }
}

__host__ __device__ constexpr int off_d(int c) { return (c < 2 ? 1 : c / 2 + 2) * REGION + (c & 1) * 16384; }
__host__ __device__ constexpr int off_xe(int c) { return (c < 2 ? 6 * REGION : c < 4 ? 16384 : c < 6 ? 0 : 6 * REGION + 16384) + (c & 1) * 8192; }
__host__ __device__ constexpr int off_xl(int c) { return c < 4 ? 2 * REGION + c * 8192 : off_xe(c - 4); }

__global__ void __cluster_dims__(2, 1, 1) __launch_bounds__(NTHREADS, 1)
fused_kernel(const __grid_constant__ Params p) {
    extern __shared__ __align__(1024) unsigned char smem[];
    const uint32_t tstart = (uint32_t)clock64();
    const uint32_t sb = smem_u32(smem);
    const int tid = threadIdx.x, lane = tid & 31;
    const int rank = blockIdx.x & 1;
#define GET_ROLE(smid, role) asm volatile("mov.u32 %0, %%smid;" : "=r"(smid));                                \
    asm("{.reg .pred p, q; .reg .u32 t, a, b; shr.u32 t, %1, 1; mad.lo.u32 a, t, 293, -928; shr.u32 a, a, 8; mad.lo.u32 b, t, 8, -464;" \
        " setp.lt.u32 p, t, 32; setp.lt.u32 q, t, 62; selp.u32 a, a, b, q; selp.u32 %0, t, a, p;}" : "=r"(role) : "r"(smid))
    uint32_t t1 = 0;
    if (__any_sync(0xffffffffu, tid == 0)) {
        uint32_t s0, r0;
        GET_ROLE(s0, r0);
        if (FAST0 == 2) {
            asm volatile("{.reg .pred p; elect.sync _|p, 0xffffffff; @p prefetch.tensormap [%0]; @p prefetch.tensormap [%1]; @p prefetch.tensormap [%2];}"
                         ::"l"(&p.mDre), "l"(&p.mDim), "l"(&p.mX1) : "memory");
        }
        mbar_init_elect(sb + B_F, 1);
        if (r0 < 64) {
#pragma unroll
            for (int c = 0; c < NC0; c++) {
                if (c) {
                    while ((uint32_t)clock64() - t1 < PTIME(c)) {}
                    mbar_init_elect(sb + B_F + 8 * c, 1);
                }
                tma3d_elect(sb + off_d(c), &p.mDre + ((r0 >> 2) & 1), (r0 & 24) * 16, c, sb + B_F + 8 * c);
                tma3d_elect(sb + off_xe(c), &p.mX1, (r0 & 3) * 256 + (r0 & 32) * 4 + rank * 64, c, sb + B_F + 8 * c);
                mbar_expect_tx_elect(sb + B_F + 8 * c, 24576);
                if (c == FILL - 1) {
                    mbar_init_elect(sb + B_FILL, 1);
                    tma3d_elect(sb + off_xl(0), &p.mX1, (r0 & 3) * 256 + (r0 & 32) * 4 + rank * 64 + 1024, 0, sb + B_FILL);
                    mbar_expect_tx_elect(sb + B_FILL, 8192);
                }
                if (!c) t1 = (uint32_t)clock64();
            }
        }
    }
    const int warp = __shfl_sync(0xffffffffu, tid >> 5, 0);
    uint32_t smid, role;
    GET_ROLE(smid, role);
    const int gpc = role & 7;
    const int tn = (role >> 3) & 3;
    const int kh = gpc >> 2;
    const int own = (gpc & 3) * 4 + ((role >> 5) & 1) * 2 + rank;
    const int blk = kh * 4 + tn;
#define TCOL(e) (kh * 1024 + ((e) >> 3) * 256 + ((e) & 3) * 64)
#define TMAT(e) (((e) >> 2) & 1)
#define KROT 0
    const int comp = kh;
    const int xrow = own * 64;
    constexpr int XLATE = 1024;
    const CUtensorMap* mD = &p.mDre + comp;
    const int rot = ROT == 1 ? gpc & 6 : ROT == 2 ? (gpc & 2) * 2 : ROT == 3 ? gpc & 2 : ROT == 4 ? kh * 4 : 0;
    const int cta = gpc * 16 + (role >> 3) * 2 + rank;
    const bool ffn = FSP ? role < 56 : cta < FFN_CTAS;
    const int fp = FSP == 2 ? gpc * 7 + (role >> 3) : FSP ? role : cta >> 1;
    uint32_t epoch = 0;
#define CHUNK_LOAD(c) tma3d_elect(sb + off_d(c), mD, tn * 128, (c) ^ rot, sb + B_F + 8 * (c));                 \
                      tma3d_elect(sb + off_xe(c), &p.mX1, xrow, (c) ^ rot, sb + B_F + 8 * (c));                \
                      mbar_expect_tx_elect(sb + B_F + 8 * (c), 24576)
#define PACE_WAIT(c) while ((uint32_t)clock64() - t1 < PTIME(c)) {}
    if (warp != 0 || role >= 64) {
        const uint32_t b1 = sb + B_F + 8 * warp;
        mbar_init_elect(warp < NC0 ? b1 + 360 : b1, 1);
        if (warp >= NC0 && warp < 5) mbar_init_elect(b1 + 360, 1);
        mbar_init_elect(b1 + 120, warp < 7 ? 5 : warp < 14 ? 4 : 6);
        mbar_init_elect(b1 + 240, 1);
        if (warp == 9 || warp == 15) mbar_expect_tx_elect(b1 + 240, warp == 9 ? 2048 : 4);
        asm volatile("fence.mbarrier_init.release.cluster;" ::: "memory");
        if (tid == 128 && role < 64) epoch = *(volatile unsigned int*)&p.s->epoch[cta];
    } else {
    }
    if (role >= 64) {
        spare_job(p, smem, smid & 3, tstart);
        return;
    }
    __syncthreads();
    asm volatile("barrier.cluster.arrive.relaxed.aligned;" ::: "memory");
    if (warp == 0) {
#pragma unroll
        for (int c = NC0; c < 8; c++) {
            PACE_WAIT(c);
            CHUNK_LOAD(c);
            if (c == XL_AT) {
                if (FILL) tma3d_elect(sb + off_xl(1), &p.mX1, xrow + XLATE, 1, sb + B_G0);
                else tma3d_elect(sb + off_xl(0), &p.mX2, xrow + XLATE, 0 ^ rot, sb + B_G0);
                mbar_expect_tx_elect(sb + B_G0, FILL ? 8192 : 16384);
            }
            if (c == 7) {
                PACE_WAIT(8);
                tma3d_elect(sb + off_xl(2), &p.mX2, xrow + XLATE, 2 ^ rot, sb + B_G2);
                mbar_expect_tx_elect(sb + B_G2, 16384);
            }
        }
        if (PFX && tn < 2 && (KC && !MAP4 ? blk < 4 : true)) {
            asm volatile("{.reg .pred p; elect.sync _|p, 0xffffffff; @p cp.async.bulk.prefetch.tensor.3d.L2.global [%0, {%1,%2,%3}];}"
                         ::"l"(&p.mX2), "r"(0), "r"(xrow + XLATE), "r"((4 + 2 * (blk & 1)) ^ rot) : "memory");
        }
    }

    if (warp < 4) {
        if (warp == 0) {
            PROF(2);
            mbar_spin(sb + B_XE, 0);
            tma3d_elect(sb + off_xl(4), &p.mX2, xrow + XLATE, 4 ^ rot, sb + B_G1);
            tma3d_elect(sb + off_xl(6), &p.mX2, xrow + XLATE, 6 ^ rot, sb + B_G1);
            mbar_expect_tx_elect(sb + B_G1, 32768);
            PROF(3);
            const int el = tile_of_step(lane, own, KROT);
            const int taba = el * 64;
#define AMAP(c) &p.mCre + comp, c
            const int tabb = (blk * 32 + el) * 128 + rank * 64;
            const uint32_t dst = sb + 16384 + rank * 8192;
#define ABAR B_FULL
#define LOAD_A() const int c = __shfl_sync(0xffffffffu, taba, step);                                            \
                 const uint32_t bar = sb + 8 * slot;                                                            \
                 mbar_spin(bar + B_EMPTY, ph);                                                                  \
                 if (TT && step == TT) { mbar_spin(sb + B_SEEN, 0); due = *(volatile uint32_t*)(smem + M_T0) + TT * 512; } \
                 if (TT && step >= TT) { while ((int)((uint32_t)clock64() - due) < 0) {} due += TPER; }         \
                 tma2d_elect(sb + slot * REGION, AMAP(c), own * 128, bar + ABAR);   \
                 mbar_expect_tx_elect(bar + ABAR, 16384)
            uint32_t slot = 0, ph = 0, due = 0;
            int step = 0;
#pragma unroll 1
            for (; step < NSTAGE; step++, slot++) {
                LOAD_A();
                PROFIF(step == 0 ? 4 : 5, step == 0 || step == 5);
                if (ADEL && (step == 2 || step == 3)) { const uint32_t t4 = (uint32_t)clock64(); while ((uint32_t)clock64() - t4 < ADEL) {} }
            }
            slot = 0; ph = 1;
#pragma unroll 1
            for (int h = PE; h < 2; h++) {
#pragma unroll 1
                for (; step < 16 + 15 * h; step++) {
                    const int row = __shfl_sync(0xffffffffu, tabb, step);
                    LOAD_A();
                    if (!NARROW && (step == 6 || step == 17)) mbar_spin(sb + B_SEEN + (step >> 4) * 8, 0);
                    load_b(dst + slot * REGION, &p.mAB, row, bar + B_BL);
                    mbar_expect_tx_elect(bar + B_BL, 16384);
                    PROF(160 + step);
                    if (++slot == NSTAGE) { slot = 0; ph ^= 1; }
                }
                const int row = __shfl_sync(0xffffffffu, tabb, step);
                LOAD_A();
                tma2d_elect(dst + slot * REGION, &p.mAB, 0, row, bar + B_BL);
                tma2d_elect((dst ^ 8192) + slot * REGION, &p.mAB, 0, row ^ 64, bar + B_BL);
                mbar_expect_tx_elect(bar + B_BL, 16384);
                PROF(160 + step);
                step++; slot++;
            }
        } else if (warp == 1) {
            if (lane < 4) asm volatile("prefetch.tensormap [%0];" ::"l"(&p.mCre + lane) : "memory");
            __syncwarp();
            asm volatile("barrier.cluster.wait.acquire.aligned;" ::: "memory");
            if (lane == 0)
                asm volatile("st.async.weak.shared::cluster.mbarrier::complete_tx::bytes.u32 [%0], %1, [%2];"
                             ::"r"(mapa(sb + M_ROLE, rank ^ 1)), "r"(role), "r"(mapa(sb + B_ROLE, rank ^ 1)) : "memory");
            mbar_wait_cluster(sb + B_ROLE, 0);
            if (*(volatile uint32_t*)(smem + M_ROLE) != role) __trap();
            mbar_wait(sb + B_EPOCH, 0);
            const uint32_t want = *(volatile uint32_t*)(smem + M_EPOCH) + 1u;
            const int el = tile_of_step(lane, own, KROT) & 15;
            const int tab = (blk * 32 + el) * 128 + rank * 64;
            const int li = (lane - 2) & 3;
            const int eh = NARROW ? __shfl_sync(0xffffffffu, el, li + 1 + (li + 1 >= OLS)) : el;
            const unsigned int* hp = p.s->hint + (blk * 8 + (eh >> 1)) * 32 + (eh & 1) * 2;
            uint2 st = ld_relaxed2(hp);
            if (TT) (void)ld_relaxed2(p.s->sync + gpc * 32 + (lane & 15) * 2);
            const uint32_t wante = HINTM ? want * 4u : want;
            uint32_t seen = __ballot_sync(0xffffffffu, st.x == wante);
#define POLL() { st = ld_relaxed2(hp); seen = __ballot_sync(0xffffffffu, st.x == wante); }
#define RS(i) ((i) + 1 + ((i) + 1 >= OLS))
            int rows[4];
#pragma unroll
            for (int i = 0; i < 4; i++) {
                rows[i] = __shfl_sync(0xffffffffu, tab, RS(i));
                mbar_expect_tx_elect(sb + B_BL + 8 * RS(i), 16384);
            }
            mbar_wait(sb + B_EMPTY + 8 * POLL_AT, 0);
            if (POLL_AT < 3) POLL();
            mbar_spin(sb + B_EMPTY + 8 * RS(0), 0);
            if (POLL_D) { const uint32_t t4 = (uint32_t)clock64(); while ((uint32_t)clock64() - t4 < POLL_D) {} }
            uint32_t t5 = 0;
#pragma unroll
            for (int i = 0; i < 4; i++) {
                while (!((seen >> (2 + i)) & 1u)) POLL();
                if (BGAP && i) while ((uint32_t)clock64() - t5 < BGAP) {}
                t5 = (uint32_t)clock64();
                if (i >= 1) mbar_spin(sb + B_EMPTY + 8 * RS(i), 0);
                load_b(sb + 16384 + rank * 8192 + RS(i) * REGION, &p.mAB, rows[i], sb + B_BL + 8 * RS(i));
                PROF(160 + RS(i));
            }
            mbar_wait(sb + B_FULL + 8 * OLS, 0);
            if (!TT) mbar_arrive_elect(sb + B_SEEN);
            PROF(7);
            unsigned char* gdst = p.s->ab + (blk * 32 + own + 16) * 16384;
            uint32_t t3 = (uint32_t)clock64() + OL_T0;
#pragma unroll 1
            for (int i = 0; i < 8; i++) {
                while ((int)((uint32_t)clock64() - t3) < 0) { if (LOWP) __nanosleep(64); }
                t3 += OL_DT;
                bulk_store_elect<2048>(gdst + i * 2048, sb + 6 * REGION + i * 2048);
                if (TT && i == 1) {
                    uint2 z;
                    do z = ld_relaxed2(p.s->sync + gpc * 32 + (lane & 15) * 2); while (__any_sync(0xffffffffu, z.x != want));
                    const uint32_t mine = __shfl_sync(0xffffffffu, z.y, cta & 15);
                    const uint32_t d = z.y - mine;
                    const uint32_t m = __reduce_max_sync(0xffffffffu, d < 1500u ? d : 0u);
                    if (lane == 0) *(volatile uint32_t*)(smem + M_T0) = mine + m - TOFF;
                    __syncwarp();
                    mbar_arrive_elect(sb + B_SEEN);
                }
            }
            bulk_wait_read();
            if (LATEH) st_relaxed_if(p.s->hint + (blk * 8 + (own >> 1)) * 32 + 4 + rank, want, lane == 0);
            mbar_arrive_n_elect<4>(sb + B_FREE + 8);
            PROF(8);
            if (LATEH) {
                if (LATEH > 1) __nanosleep(LATEH);
                wait_counters<100>(hp + 4 - (el & 1), want);
            }
            mbar_arrive_elect(sb + B_SEEN + 8);
            PROF(9);
            mbar_wait(sb + B_PUBI, 0);
            PROF(29);
            if (lane == 0) {
                if (TRED) fence_proxy_async_gmem();
                red_release_add(p.s->ready + blk * 32, 1);
            }
            __syncwarp();
            PROF(30);
            if (INITH) __nanosleep(INITH);
            wait_counters<INITS>(p.s->ready + (lane & 7) * 32, want * 16u);
            mbar_arrive_elect(sb + B_INIT);
            PROF(10);
        } else {
            mbar_arrive_elect(sb + B_BL + 8 * OLS * (warp & 1));
            if (PE && warp == 2) {
                mbar_arrive_elect(sb + B_BL + 8);
                mbar_expect_tx_elect(sb + B_FULL + 8, 16384);
                mbar_arrive_n_elect<3>(sb + B_FULL + 8);
            }
            if (PFA_T && warp == 3) {
                const int e = tile_of_step(PFA_S + tn, own, KROT);
                while ((uint32_t)clock64() - tstart < PFA_T) __nanosleep(20);
                if (lane == 0) tma2d_prefetch(&p.mCre + comp, e * 64, own * 128);
                __syncwarp();
            }
            uint32_t k = 12;
            if (PFD && warp == 3) k = 0;
#define PREFETCH_W() {                                                                                        \
                const char* src = (k >= 8 ? (const char*)p.wd + ((cta >> 5) * 2 + (k >> 1) - 4) * 229376       \
                                          : (const char*)((cta & 32) ? p.wu : p.wg) + ((cta >> 6) * 4 + (k >> 1)) * 229376) + ((cta & 31) * 2 + (k & 1)) * 3584; \
                asm volatile("{.reg .pred p; elect.sync _|p, 0xffffffff; @p cp.async.bulk.prefetch.L2.global [%0], 3584;}" ::"l"(src) : "memory"); \
                k++; }
#pragma unroll 1
            while (k < PF_N0) {
                while ((uint32_t)clock64() - tstart < PF_T0 + k * (PF_DT / 2)) __nanosleep(50);
                __syncwarp();
                PREFETCH_W();
            }
            mbar_wait(sb + B_EPOCH, 0);
            const uint32_t par = (*(volatile uint32_t*)(smem + M_EPOCH) + 1u) & 1u;
            const uint32_t a0 = sb + 16384 + (lane >> 3) * 1028 + ((lane >> 2) & 1) * 144 + (lane & 3) * 32;
            const int tab = (blk * 32 + tile_of_step(lane, own, KROT)) * 128;
            const uint32_t retry = sb + B_RETRY + (warp & 1) * 240;
            uint32_t slot = PE ? 6 - warp : OLS == 1 ? warp : OLS == 2 ? 10 - 3 * warp : 4 - warp, ph = 0, rph = 0;
            uint32_t j = ffn ? warp & 1 : 12;
#pragma unroll 1
            for (int step = slot; step < 32 || j < 12; step += 2) {
                if (step < 32 && (OLS < 3 || step != OLS)) {
                    const uint32_t a = a0 + slot * REGION, bar = sb + 8 * slot;
                    mbar_wait(bar + B_BL, ph);
                    PROF(192 + step);
#pragma unroll 1
                    while (__any_sync(0xffffffffu, stale_tags(a, par) & 1u)) {
                        const int row = __shfl_sync(0xffffffffu, tab, step);
                        mbar_expect_tx_elect(retry, 16384);
                        tma2d_elect(sb + slot * REGION + 16384, &p.mAB, 0, row, retry);
                        tma2d_elect(sb + slot * REGION + 24576, &p.mAB, 0, row + 64, retry);
                        mbar_spin(retry, rph);
                        rph ^= 1u;
                    }
                    mbar_arrive_n_elect<4>(bar + B_FULL);
                    PROF(128 + step);
                }
                if (j < 12 && step >= FFN_S0 + j * FW0 / 4 && __any_sync(0xffffffffu, mbar_test(sb + B_FREE + 2 * (j & 12), 0))) {
                    const uint32_t fb = sb + B_FFN + 4 * (j & 6);
                    if (!(j & 1)) mbar_expect_tx_elect(fb, 8192);
                    tma2d_elect(sb + 6 * REGION + ((j + 4) & 7) * 4096, j < 8 ? &p.mWg + (j & 1) : &p.mWd, j < 8 ? fp * 32 : rank * 256,
                                j < 8 ? rank * 256 + (j >> 1) * 64 : fp * 32 + j * 8 - 64, fb);
                    j += 2;
                }
                if (k < 12) PREFETCH_W();
                if (PFL && step == PFL) {
                    const int e = tile_of_step(28 + tn, own, KROT);
                    if (lane == 0) tma2d_prefetch(&p.mCre + comp, e * 64, own * 128);
                    __syncwarp();
                }
                slot += 2;
                if (slot >= NSTAGE) { slot -= NSTAGE; ph ^= 1; }
            }
        }
    } else if (warp < 8) {
        const int t = tid - 128, w = warp - 4;
        if (t == 0) {
            *(volatile uint32_t*)(smem + M_EPOCH) = epoch;
            *(volatile unsigned int*)&p.s->epoch[cta] = epoch + 1;
            mbar_arrive(sb + B_EPOCH);
        }
        const uint4 gw0 = ldg_nc_off<0>(p.gate_w + lane * 8), gw1 = ldg_nc_off<512>(p.gate_w + lane * 8);
        const uint4 rw0 = ldg_nc_off<0>(p.w_r + lane * 8), rw1 = ldg_nc_off<512>(p.w_r + lane * 8);
        mbar_wait(sb + B_EPOCH, 0);
        const uint32_t par = (*(volatile uint32_t*)(smem + M_EPOCH) + 1u) & 1u;
        mbar_wait(sb + B_F + 8 * ROUTER_C, 0);
        const int row0 = cta * 16 + w * 4;
        uint4 xr[8];
        {
            const char* xp = (const char*)p.x + (uint32_t)row0 * (D_ * 2) + lane * 16;
            const uint32_t t6 = (uint32_t)clock64();
#define RWAIT(n) if (RDT) while ((uint32_t)clock64() - t6 < (n) * RDT) __nanosleep(40)
            xr[0] = ldg_nc_off<0>(xp);    xr[1] = ldg_nc_off<512>(xp);  RWAIT(1); xr[2] = ldg_nc_off<1024>(xp); xr[3] = ldg_nc_off<1536>(xp); RWAIT(2);
            xr[4] = ldg_nc_off<2048>(xp); xr[5] = ldg_nc_off<2560>(xp); RWAIT(3); xr[6] = ldg_nc_off<3072>(xp); xr[7] = ldg_nc_off<3584>(xp);
            float a[8];
#pragma unroll
            for (int i = 0; i < 4; i++) {
                const uint32_t xv[8] = {xr[2 * i].x, xr[2 * i].y, xr[2 * i].z, xr[2 * i].w, xr[2 * i + 1].x, xr[2 * i + 1].y, xr[2 * i + 1].z, xr[2 * i + 1].w};
                const uint32_t gv[8] = {gw0.x, gw0.y, gw0.z, gw0.w, gw1.x, gw1.y, gw1.z, gw1.w};
                const uint32_t rv[8] = {rw0.x, rw0.y, rw0.z, rw0.w, rw1.x, rw1.y, rw1.z, rw1.w};
                float u = 0.f, v = 0.f;
#pragma unroll
                for (int j = 0; j < 8; j++) {
                    u = fmaf(bflo(xv[j]), bflo(gv[j]), u); u = fmaf(bfhi(xv[j]), bfhi(gv[j]), u);
                    v = fmaf(bflo(xv[j]), bflo(rv[j]), v); v = fmaf(bfhi(xv[j]), bfhi(rv[j]), v);
                }
                a[i] = u; a[4 + i] = v;
            }
            if (RSPLIT && ROUTER_C < 16) mbar_wait(sb + B_FULL + 8 * (RSPLIT - 1), 0);
            halve<4, 16>(a); halve<2, 8>(a); halve<1, 4>(a);
            a[0] += __shfl_xor_sync(0xffffffffu, a[0], 1);
            a[0] += __shfl_xor_sync(0xffffffffu, a[0], 2);
            const int row = row0 + ((lane >> 2) & 3);
            const float gate = sigmoidf_(a[0]);
            if (lane < 16 && (lane & 3) == 0) st_relaxed(&p.s->gate[row], tagf(gate, par));
            const uint32_t best = __reduce_max_sync(0xffffffffu, lane >= 16 ? router_key(a[0], row) : 0u);
            if (lane == 0) *(volatile uint32_t*)(smem + M_RED + w * 4) = best;
            named_bar(1, 128);
            if (t < 8) {
                const uint4 k = *(const uint4*)(smem + M_RED);
                st_key(&p.s->keys[t * NCTA + cta], max(max(k.x, k.y), max(k.z, k.w)) | (par << 15));
            }
            PROFIF(11, t == 0);
            const uint32_t og = pack_bf16(1.f - gate, 1.f - gate);
#pragma unroll
            for (int i = 0; i < 8; i++) {
                const uint32_t o = __shfl_sync(0xffffffffu, og, 4 * (i >> 1));
                xr[i] = make_uint4(hmul2_bf16(o, xr[i].x), hmul2_bf16(o, xr[i].y), hmul2_bf16(o, xr[i].z), hmul2_bf16(o, xr[i].w));
            }
        }
        if (ROUTER_C < 16) mbar_wait(sb + B_FULL + 8 * OLS, 0);
        else __nanosleep(KEYS_NS);
        if (w == 0) {
            const uint4 k4 = wait_tags(p.s->keys + gpc * NCTA + lane * 4, 15, par);
            const uint32_t k = __reduce_max_sync(0xffffffffu, max(max(k4.x, k4.y), max(k4.z, k4.w)));
            sts128(sb + M_UPD + lane * 16, ldg_nc_off<0>(p.x + (0x7fff - (k & 0x7fffu)) * D_ + rank * 256 + lane * 8));
        } else if (w == 1) {
            const uint4 g4 = wait_tags(p.s->gate + own * 128 + lane * 4, 0, par);
            *(uint4*)(smem + M_G + lane * 16) = make_uint4(g4.x & ~1u, g4.y & ~1u, g4.z & ~1u, g4.w & ~1u);
            mbar_arrive_warp(sb + B_GATE);
        }
        named_bar(1, 128);
        PROFIF(13, t == 0);
        char* op = (char*)p.out + (uint32_t)row0 * (D_ * 2) + lane * 16;
        float a[16];
#pragma unroll
        for (int i = 0; i < 16; i++) a[i] = 0.f;
#pragma unroll 1
        for (int i = 0; i < 4; i++) {
            if (i >= 2) {
                mbar_wait(sb + B_FREE + 8, 0);
                const uint32_t t2 = (uint32_t)clock64();
#pragma unroll
                for (int j = 0; j < 4; j++) {
                    while ((uint32_t)clock64() - t2 < j * INIT_DT) __nanosleep(50);
                    *(uint4*)(op + j * 512) = xr[j];
                    xr[j] = xr[j + 4];
                }
                op += 2048;
                if (i == 3) mbar_arrive_warp(sb + B_PUBI);
            }
            if (ffn) {
                const float xs0 = __bfloat162float(((const bf16*)(smem + M_UPD))[64 * i + (t >> 2)]);
                const float xs1 = __bfloat162float(((const bf16*)(smem + M_UPD))[64 * i + 32 + (t >> 2)]);
                const uint32_t wa = sb + 6 * REGION + (i ^ 2) * 8192 + t * 16;
                mbar_wait(sb + B_FFN + 8 * i, 0);
                const uint4 v0 = lds128(wa), v1 = lds128(wa + 4096), v2 = lds128(wa + 2048), v3 = lds128(wa + 6144);
                const uint32_t w0[8] = {v0.x, v0.y, v0.z, v0.w, v1.x, v1.y, v1.z, v1.w};
                const uint32_t w1[8] = {v2.x, v2.y, v2.z, v2.w, v3.x, v3.y, v3.z, v3.w};
#pragma unroll
                for (int k = 0; k < 8; k++) {
                    a[2 * k] = fmaf(xs1, bflo(w1[k]), fmaf(xs0, bflo(w0[k]), a[2 * k]));
                    a[2 * k + 1] = fmaf(xs1, bfhi(w1[k]), fmaf(xs0, bfhi(w0[k]), a[2 * k + 1]));
                }
                if (i == 1) {
                    named_bar(1, 128);
                    mbar_arrive_if(sb + B_VD, t == 0);
                }
            }
        }
        if (!ffn) return;
        PROFIF(14, t == 0);
        {
            halve<8, 16>(a); halve<4, 8>(a); halve<2, 4>(a);
            const uint32_t ho = (lane >> 4) * 128 + (lane & 3) * 32 + ((lane >> 2) & 3) * 8;
            asm volatile("barrier.cluster.wait.acquire.aligned;" ::: "memory");
#pragma unroll
            for (int k = 0; k < 2; k++)
                asm volatile("st.async.weak.shared::cluster.mbarrier::complete_tx::bytes.v2.f32 [%0], {%1,%2}, [%3];"
                             ::"r"(mapa(sb + (k ? 6 * REGION + w * 512 : M_HX + w * 256) + ho, rank ^ k ^ 1)), "f"(a[0]), "f"(a[1]),
                               "r"(mapa(sb + B_HX, rank ^ k ^ 1)) : "memory");
            mbar_wait_cluster(sb + B_HX, 0);
            const float *hx = (const float*)(smem + M_HX) + lane, *hy = (const float*)(smem + 6 * REGION) + lane;
            const float gs = ((hx[0] + hy[0]) + (hx[64] + hy[128])) + ((hx[128] + hy[256]) + (hx[192] + hy[384]));
            const float us = ((hx[32] + hy[32]) + (hx[96] + hy[160])) + ((hx[160] + hy[288]) + (hx[224] + hy[416]));
            float* hrow = (float*)(smem + 6 * REGION + 256) + w * 128;
            hrow[lane] = gs * sigmoidf_(gs) * us;
            __syncwarp();
            PROFIF(12, t == 0);
            float o0 = 0.f, o1 = 0.f;
#pragma unroll 1
            for (int i = 0; i < 2; i++) {
                float4 hv[4];
                uint32_t vd[16];
#pragma unroll
                for (int k = 0; k < 4; k++) hv[k] = *(const float4*)&hrow[i * 16 + k * 4];
                mbar_wait(sb + B_FFN + 8 * i, 1);
#pragma unroll
                for (int k = 0; k < 16; k++) vd[k] = *(const volatile uint32_t*)(smem + 6 * REGION + 16384 + i * 8192 + k * 512 + t * 4);
#pragma unroll
                for (int k = 0; k < 4; k++) {
                    o0 = fmaf(hv[k].x, bflo(vd[4 * k]), o0);     o1 = fmaf(hv[k].x, bfhi(vd[4 * k]), o1);
                    o0 = fmaf(hv[k].y, bflo(vd[4 * k + 1]), o0); o1 = fmaf(hv[k].y, bfhi(vd[4 * k + 1]), o1);
                    o0 = fmaf(hv[k].z, bflo(vd[4 * k + 2]), o0); o1 = fmaf(hv[k].z, bfhi(vd[4 * k + 2]), o1);
                    o0 = fmaf(hv[k].w, bflo(vd[4 * k + 3]), o0); o1 = fmaf(hv[k].w, bfhi(vd[4 * k + 3]), o1);
                }
            }
            asm volatile("st.relaxed.gpu.global.v2.u32 [%0], {%1,%2};" ::"l"(&p.s->part[fp * D_ + rank * 256 + t * 2]),
                         "r"(tagf(o0, par)), "r"(tagf(o1, par)) : "memory");
            if (lane == 0) asm volatile("red.relaxed.gpu.global.add.u32 [%0], 1;" ::"l"(p.s->phint + ((rank * 2 + (w >> 1)) * 16 + (fp >> 2)) * 8) : "memory");
            PROFIF(15, t == 0);
        }
    } else {
        const int wg = (warp >> 2) - 2, wq = warp & 3;
        const uint32_t sbd = (sb & 0x3FFFF) >> 4;
        const bool lead = (tid & 127) == 0;
        const bool lead0 = lead && !wg, lead1 = lead && wg;
        const int q = lane & 3;
        float acc[64];
        const uint32_t rE = mapa(sb + B_EMPTY, rank ^ 1);
#define RELEASE(n, slot, pred) release_pair<n>(sb + B_EMPTY + 8 * (slot), rE + 8 * (slot), pred)
        const uint32_t img = sb + 6 * REGION + (wg ? 0 : 16384) + wq * 4096;
        const uint32_t sdst = pin(img + (lane >> 2) * 64 + ((q ^ (lane >> 3)) << 4));
        unsigned char* gdst = pin_uniform(p.s->ab + ((blk * 32 + own) * 4 + wq) * 4096);
        unsigned char* gd2 = pin(gdst + (sdst - img));
        unsigned int* hint = pin(p.s->hint + (blk * 8 + (own >> 1)) * 32 + rank * 2 + lane);
#define HINT(pred) red_inc_if(hint, (pred) && (!NARROW || (ORD ? !(own & 2) : own < 6)) && lane == 0)
        uint32_t e1 = 0;
        asm volatile("barrier.cluster.wait.acquire.aligned;" ::: "memory");
        if (wg) {
            if (NOFW) {
                mbar_spin(sb + B_EPOCH, 0);
                e1 = *(volatile uint32_t*)(smem + M_EPOCH) + 1u;
            }
            if (FILL) { mbar_spin(sb + B_F, 0); mbar_spin(sb + B_FILL, 0); }
            else mbar_spin(sb + B_G0, 0);
            PROFIF(20, lead);
            if (!FILL) mbar_spin(sb + B_GO1, 0);
        }
#pragma unroll
        for (int c = RS1 ? 2 : 0; c < 8; c++) {
            if (!NOFW || !wg || c == 2 || c == 4) mbar_spin(sb + (c == 4 && wg ? B_G1 : c == 2 && wg ? B_G2 : PAUSE && c == 1 && wg ? B_XE : B_F + 8 * c), PAUSE && c == 1 && wg);
            if (FILL && c == 1 && wg) { mbar_spin(sb + B_G0, 0); mbar_spin(sb + B_GO1, 0); PROFL(0); }
            if (c == 0) { PROFIF(16 + 5 * wg, lead); PROFL(0); }
            wg_fence();
#pragma unroll
            for (int kk = 0; kk < 4; kk++) {
                wgmma128<0>(acc, desc_lo(sbd + 0x10000 + (wg ? off_xl(c) : off_xe(c)) / 16 + 2 * kk), desc_lo(sbd + 0x10000 + off_d(c) / 16 + 2 * kk), (c | kk) != 0);
                if (c == 7 && kk == GOK - 1) wg_commit();
            }
            wg_commit();
            if (c == 3 && (!NOFW || !wg)) {
                mbar_spin(sb + B_EPOCH, 0);
                e1 = *(volatile uint32_t*)(smem + M_EPOCH) + 1u;
            }
            if (c == 7 && wg) mbar_spin(sb + B_FULL, 0);
            if (c == 7 && GO0) { wg_wait<2>(); mbar_arrive_if(sb + B_GO1, lead0); }
            if (c >= 2 && c != 3 && c != 5) wg_wait<1>();
            if (c == 2) RELEASE(2, 1, lead1);
            if (c == 4) { mbar_arrive_if(sb + B_XE, lead0); RELEASE(2, 2, lead1); RELEASE(2, 3, lead1); }
            if (c == 6 && !HINTM) st_stamp_if(hint, e1, lead0 && (ORD ? !(own & 2) : own < 6));
            if (c == 6) RELEASE(2, 4 * wg, lead);
            if (c == 7) mbar_arrive_if(sb + B_GO1 + 8 * wg, GO0 ? lead1 : lead);
        }
        const uint32_t neg = comp && !KC ? 0x80008000u : 0u, negp = neg | (e1 & 1u);
        const int rh = RSW ? wg ^ kh : wg;
        const uint32_t da0 = sbd + 0x10000 + rh * 512, db0 = sbd + 0x400000 + 1024;
#define STEP(da, db, first) wg_fence();                                                                     \
        _Pragma("unroll") for (int kk = 0; kk < 4; kk++)                                                    \
            wgmma128(acc, desc_lo((da) + kk * 2), desc64_lo((db) + kk * 256), !((first) && kk == 0));       \
        wg_commit()
#define PROFSTEP(s) PROFIF(64 + wg * 32 + (s), lead)
        const uint32_t dbe = db0 + 6 * (REGION / 16), dbl = dbe - 1024;
#define PW(i, j) pack_bf16(acc[16 * ((i) >> 1) + 2 * ((i) & 1) + 4 * (j)], acc[16 * ((i) >> 1) + 2 * ((i) & 1) + 4 * (j) + 1])
#define PT(i, j) ((j) == ((i) >> 1) ? (PW(i, j) & ~1u) ^ negp : PW(i, j) ^ neg)
#define CUT(n) if ((ECUT >> (n)) & 1) sched_cut()
#define PIECE(i) make_uint4(PT(i, 0), PT(i, 1), PT(i, 2), PT(i, 3))
        if (wg) {
            wg_wait<0>();
            fence_regs<0, 64>(acc);
            PROFIF(22, lead); PROFL(1);
            const uint32_t tl = TT ? (uint32_t)clock64() : 0;
#define STS1(i) sts128_off<(i) * 512>(sdst, PIECE(i))
            STS1(0); CUT(1); STS1(1); CUT(2); STS1(2); CUT(3); STS1(3); CUT(4); STS1(4); CUT(5); STS1(5); CUT(6); STS1(6); CUT(7); STS1(7);
            if (W1FIRST == 1) { PROFL(3); STEP(da0, dbe, true); }
            fence_proxy_async_smem();
            __syncwarp();
            mbar_arrive_if(sb + B_FULL + 8 * OLS, lane == 0);
            PROFL(2);
            if (!W1FIRST) { PROFL(3); STEP(da0, dbe, true); }
            PROFIF(23, lead);
            RELEASE(1, 5, lead);
            if (TT && lead) asm volatile("st.relaxed.gpu.global.v2.u32 [%0], {%1,%2};" ::"l"(p.s->sync + cta * 2), "r"(e1), "r"(tl) : "memory");
        } else {
            wg_wait<0>();
            fence_regs<0, 64>(acc);
            PROFIF(17, lead); PROFL(1);
            uint4 v[8];
#define STG0(i) v[i] = PIECE(i); stg_off<(i) * 512>(gd2, v[i]); if (HINTM == (i) + 1) HINT(true); if (PAUSE == (i) + 1) mbar_arrive_if(sb + B_XE, lead)
            STG0(0); CUT(1); STG0(1); CUT(2); STG0(2); CUT(3); STG0(3); CUT(4); STG0(4); CUT(5); STG0(5); CUT(6); STG0(6); CUT(7); STG0(7);
            PROFIF(48 + wq, lane == 0);
#define STS0(i) if (THR && (i) % THR == 0) mbar_spin(sb + B_EPOCH, 0); sts128_off<(i) * 512>(sdst, v[i])
            STS0(0); STS0(1); STS0(2); STS0(3); STS0(4); STS0(5); STS0(6); STS0(7);
            if (PE) mbar_spin(sb + B_EMPTY + 8, 0);
            fence_proxy_async_smem();
            __syncwarp();
            if (PE)
                asm volatile("{.reg .pred p; elect.sync _|p, 0xffffffff;"
                             " @p cp.async.bulk.shared::cluster.shared::cta.mbarrier::complete_tx::bytes [%0], [%1], 4096, [%2];}"
                             ::"r"(rE - B_EMPTY + REGION + 16384 + wq * 4096), "r"(img), "r"(rE - B_EMPTY + B_FULL + 8) : "memory");
            mbar_arrive_if(sb + B_FULL, lane == 0);
            PROFIF(19, lead); PROFL(2);
            RELEASE(1, 5, lead);
            mbar_arrive_if(sb + B_FREE, lane == 0);
            mbar_spin(sb + B_FULL, 0);
            mbar_spin(sb + B_SKEW0, 0);
            PROFSTEP(0); PROFL(3);
            STEP(da0, dbe, true);
        }
        constexpr int NU = OLS + 2;
#pragma unroll
        for (int step = 1; step < NU; step++) {
            mbar_spin(sb + B_FULL + 8 * step, 0);
            PROFSTEP(step);
            if (step < 4) PROFL(3 + step);
            STEP(da0 + step * (REGION / 16), step == OLS ? dbl : db0 + step * (REGION / 16), false);
            wg_wait<1>();
            RELEASE(1, step - 1, lead);
            if (step == 1) mbar_arrive_if(sb + B_FREE, lead);
            if (step == OLS + 1) mbar_arrive_if(sb + B_FREE + 8, lead);
            if (step == 4) PROFL(7);
        }
        int slot = NU % NSTAGE, ph = NU / NSTAGE, pslot = NU - 1;
#pragma unroll 1
        for (int step = NU; step < 26; step++) {
            mbar_wait(sb + B_FULL + 8 * slot, ph);
            PROFSTEP(step);
            STEP(da0 + slot * (REGION / 16), db0 + slot * (REGION / 16), false);
            wg_wait<1>();
            RELEASE(1, pslot, lead);
            pslot = slot;
            if (++slot == NSTAGE) { slot = 0; ph ^= 1; }
        }
        PROFL(8);
        float g0 = 0.f, g1 = 0.f;
        char* op = nullptr;
        const int r0 = rh * 64 + wq * 16 + (lane >> 2);
        const bool odd = lane & 4;
#define OUT_SETUP() mbar_wait(sb + B_GATE, 0);                                                              \
        g0 = ((const volatile float*)(smem + M_G))[r0];                                                     \
        g1 = ((const volatile float*)(smem + M_G))[r0 + 8];                                                 \
        if (KC && comp) { g0 = -g0; g1 = -g1; }                                                             \
        op = pin((char*)p.out + (uint32_t)((own * 128 + (SHUF ? r0 & ~1 : r0)) * D_ + tn * 128 + (lane & (SHUF ? 7 : 3)) * 8) * 2u)
        if (SK == 6 && wg) {
            wg_wait<0>();
        } else {
            mbar_wait(sb + B_FULL + 8 * 2, 0);
            STEP(da0 + 2 * (REGION / 16), db0 + 2 * (REGION / 16), false);
            wg_wait<1>();
            slot = 3;
        }
        RELEASE(1, 1, lead);
#pragma unroll 1
        for (int step = 24 + slot; step < 32; step++) {
            if (step == (wg ? 32 - SK : 30)) {
                OUT_SETUP();
                mbar_wait(sb + (wg ? B_TAIL : B_INIT), 0);
            }
            if (!wg || step < 32 - SK) mbar_wait(sb + B_FULL + 8 * slot, ph);
            STEP(da0 + slot * (REGION / 16), db0 + slot * (REGION / 16), false);
            if (++slot == NSTAGE) { slot = 0; ph ^= 1; }
        }
        if (!wg) {
            wg_wait<1>();
            mbar_arrive_if(sb + B_TAIL, lead);
        }
        if (!wg || TRED == 2) {
            const int sr = ((lane >> 2) & 1) * 4 + (lane >> 3);
            const uint32_t st0 = sb + rh * 8192 + wq * 2048, sa = pin(st0 + sr * 128 + ((q ^ sr) << 4));
            if (TORD) sched_cut();
            wg_wait<0>();
            fence_regs<0, 64>(acc);
            PROFIF(24 + 2 * wg, lead); PROFL(9);
#define OW(i, j) pack_bf16((((i) & 1) ? g1 : g0) * acc[16 * ((i) >> 1) + 2 * ((i) & 1) + 4 * (j)], (((i) & 1) ? g1 : g0) * acc[16 * ((i) >> 1) + 2 * ((i) & 1) + 4 * (j) + 1])
#define OSTS(i) sts128_off<((i) >> 2) * REGION + ((i) & 1) * 1024>(((i) & 2) ? sa ^ 64 : sa, make_uint4(OW(i, 0), OW(i, 1), OW(i, 2), OW(i, 3)))
#define ORED(h) fence_proxy_async_smem(); __syncwarp();                                                     \
            asm volatile("{.reg .pred p; elect.sync _|p, 0xffffffff;"                                       \
                         " @p cp.reduce.async.bulk.tensor.4d.global.shared::cta.add.tile.bulk_group [%0, {%2,%3,%3,%4}], [%1];}" \
                         ::"l"(&p.mOut), "r"(st0 + (h) * REGION), "r"(tn * 128 + (h) * 64), "r"(0), "r"(own * 16 + rh * 8 + wq * 2) : "memory")
            OSTS(0); OSTS(1); OSTS(2); OSTS(3);
            ORED(0);
            if (TORD) sched_cut();
            OSTS(4); OSTS(5); OSTS(6); OSTS(7);
            ORED(1);
            bulk_wait_read();
        } else {
        char* opb = pin(op + (odd ? 1024 - 64 : 1024 + 64));
        if (TORD) sched_cut();
        wg_wait<0>();
        fence_regs<0, 64>(acc);
        PROFIF(24 + 2 * wg, lead); PROFL(9);
        uint32_t k[4][4], r[4][4];
#define PACKLINE(i) _Pragma("unroll") for (int j = 0; j < 4; j++) {                                         \
            const int o = 32 * ((i) >> 1) + 2 * ((i) & 1) + 4 * j;                                          \
            const float g = ((i) & 1) ? g1 : g0;                                                            \
            r[i][j] = __shfl_xor_sync(0xffffffffu, pack_bf16(g * acc[o + 16], g * acc[o + 17]), 4);         \
            k[i][j] = pack_bf16(g * acc[o], g * acc[o + 1]); }
#define REDLINE(i)                                                                                          \
        red_bf16x8<((i) & 1) * 8192 + ((i) >> 1) * 128>(op, odd ? r[i][0] : k[i][0], odd ? r[i][1] : k[i][1], odd ? r[i][2] : k[i][2], odd ? r[i][3] : k[i][3]); \
        red_bf16x8<((i) & 1) * 8192 + ((i) >> 1) * 128>(opb, odd ? k[i][0] : r[i][0], odd ? k[i][1] : r[i][1], odd ? k[i][2] : r[i][2], odd ? k[i][3] : r[i][3])
        PACKLINE(0) REDLINE(0);
        if (TORD) sched_cut();
        PACKLINE(1) REDLINE(1);
        if (TORD > 1) sched_cut();
        PACKLINE(2) REDLINE(2);
        if (TORD > 2) sched_cut();
        PACKLINE(3) REDLINE(3);
        }
    }
}

typedef CUresult (*EncodeTiledFn)(CUtensorMap*, CUtensorMapDataType, cuuint32_t, void*, const cuuint64_t*, const cuuint64_t*,
                                  const cuuint32_t*, const cuuint32_t*, CUtensorMapInterleave, CUtensorMapSwizzle,
                                  CUtensorMapL2promotion, CUtensorMapFloatOOBfill);

static void make_map(EncodeTiledFn enc, CUtensorMap* m, const void* base, uint64_t cols, uint64_t rows, uint32_t box_rows,
                     CUtensorMapSwizzle sw = CU_TENSOR_MAP_SWIZZLE_128B, uint32_t box_cols = 64,
                     CUtensorMapL2promotion promo = CU_TENSOR_MAP_L2_PROMOTION_L2_128B) {
    cuuint64_t dims[2] = {cols, rows};
    cuuint64_t str[1] = {cols * 2};
    cuuint32_t box[2] = {box_cols, box_rows};
    cuuint32_t es[2] = {1, 1};
    enc(m, CU_TENSOR_MAP_DATA_TYPE_BFLOAT16, 2, (void*)base, dims, str, box, es, CU_TENSOR_MAP_INTERLEAVE_NONE,
        sw, promo, CU_TENSOR_MAP_FLOAT_OOB_FILL_NONE);
}

static void make_map_chunks(EncodeTiledFn enc, CUtensorMap* m, const void* base, uint64_t rows, uint32_t box_rows, uint32_t n = 1) {
    cuuint64_t dims[3] = {64, rows, 8};
    cuuint64_t str[2] = {D_ * 2, 128};
    cuuint32_t box[3] = {64, box_rows, n};
    cuuint32_t es[3] = {1, 1, 1};
    enc(m, CU_TENSOR_MAP_DATA_TYPE_BFLOAT16, 3, (void*)base, dims, str, box, es, CU_TENSOR_MAP_INTERLEAVE_NONE,
        CU_TENSOR_MAP_SWIZZLE_128B, CU_TENSOR_MAP_L2_PROMOTION_L2_128B, CU_TENSOR_MAP_FLOAT_OOB_FILL_NONE);
}

static void make_map_out(EncodeTiledFn enc, CUtensorMap* m, const void* base) {
    cuuint64_t dims[4] = {D_, 4, 2, S_ / 8};
    cuuint64_t str[3] = {2 * D_ * 2, D_ * 2, 8 * D_ * 2};
    cuuint32_t box[4] = {64, 4, 2, 2};
    cuuint32_t es[4] = {1, 1, 1, 1};
    enc(m, CU_TENSOR_MAP_DATA_TYPE_BFLOAT16, 4, (void*)base, dims, str, box, es, CU_TENSOR_MAP_INTERLEAVE_NONE,
        CU_TENSOR_MAP_SWIZZLE_128B, CU_TENSOR_MAP_L2_PROMOTION_NONE, CU_TENSOR_MAP_FLOAT_OOB_FILL_NONE);
}

extern "C" void kernel_launch(void* const* d_in, const int* in_sizes, int n_in, void* d_out, int out_size) {
    (void)in_sizes; (void)n_in; (void)out_size;
    static EncodeTiledFn enc = nullptr;
    static bool fused_ok = false;
    static void* ab_ptr = nullptr;
    if (!enc) {
        void* fn = nullptr;
        cudaDriverEntryPointQueryResult q;
        cudaGetDriverEntryPoint("cuTensorMapEncodeTiled", &fn, cudaEnableDefault, &q);
        enc = (EncodeTiledFn)fn;
        cudaGetSymbolAddress(&ab_ptr, g_s);
        cudaFuncSetAttribute(fused_kernel, cudaFuncAttributeMaxDynamicSharedMemorySize, SMEM_BYTES);
        int dev = 0, nsm = 0, ncl = 0;
        cudaGetDevice(&dev);
        cudaDeviceGetAttribute(&nsm, cudaDevAttrMultiProcessorCount, dev);
        cudaLaunchConfig_t cfg = {};
        cfg.gridDim = dim3(132); cfg.blockDim = dim3(NTHREADS); cfg.dynamicSmemBytes = SMEM_BYTES;
        cudaLaunchAttribute at;
        at.id = cudaLaunchAttributeClusterDimension;
        at.val.clusterDim.x = 2; at.val.clusterDim.y = 1; at.val.clusterDim.z = 1;
        cfg.attrs = &at; cfg.numAttrs = 1;
        fused_ok = cudaOccupancyMaxActiveClusters(&ncl, fused_kernel, &cfg) == cudaSuccess && nsm == 132 && ncl == 66;
        (void)cudaGetLastError();
    }
    if (!fused_ok) {
        const bf16* const* in = (const bf16* const*)d_in;
        fb_hidden<<<S_, D_, 0, cudaStreamPerThread>>>(in[0], in[3], in[4], in[10], in[6]);
        fb_ffn1<<<F_ / 128, 128, 0, cudaStreamPerThread>>>(in[0], in[7], in[8]);
        fb_ffn2<<<D_ / 64, 64, 0, cudaStreamPerThread>>>(in[9]);
        fb_seq<<<S_, D_, 0, cudaStreamPerThread>>>(in[0], in[1], in[2], (bf16*)d_out);
        return;
    }
    Params p;
    p.s = (Scratch*)ab_ptr;
    p.x = (const bf16*)d_in[0];
    p.w_r = (const bf16*)d_in[6];
    p.wg = (const bf16*)d_in[7];
    p.wu = (const bf16*)d_in[8];
    p.wd = (const bf16*)d_in[9];
    p.gate_w = (const bf16*)d_in[10];
    p.out = (bf16*)d_out;
    make_map_chunks(enc, &p.mX1, d_in[0], S_, 64);
    make_map_chunks(enc, &p.mX2, d_in[0], S_, 64, 2);
    make_map(enc, &p.mCre, d_in[1], S_, S_, 128);
    make_map(enc, &p.mCim, d_in[2], S_, S_, 128);
    make_map_chunks(enc, &p.mDre, d_in[3], D_, 128);
    make_map_chunks(enc, &p.mDim, d_in[4], D_, 128);
    make_map(enc, &p.mAB, ab_ptr, 64, 8 * 32 * 128, 64, CU_TENSOR_MAP_SWIZZLE_NONE);
    make_map_out(enc, &p.mOut, d_out);
    make_map(enc, &p.mWg, d_in[7], F_, D_, 64, CU_TENSOR_MAP_SWIZZLE_NONE, 32, WPROMO);
    make_map(enc, &p.mWu, d_in[8], F_, D_, 64, CU_TENSOR_MAP_SWIZZLE_NONE, 32, WPROMO);
    make_map(enc, &p.mWd, d_in[9], D_, F_, 8, CU_TENSOR_MAP_SWIZZLE_NONE, 256);
    fused_kernel<<<132, NTHREADS, SMEM_BYTES, cudaStreamPerThread>>>(p);
}
```

```cpp
#include <cuda_runtime.h>
#include <cuda.h>
#include <cuda_bf16.h>
#include <stdint.h>

typedef __nv_bfloat16 bf16;

#define PACE 250
#define ORD 0
#define PE 0
#define OLS 1
#define HINT_AT 400
#define PRIO 0
#define SK 5
#define PF_T0 3000
#define PF_DT 1700
#define FFN_S0 4
#define FFN_S1 11
#define NI0 0
#define INIT_T0 0
#define INIT_DT 400
#define W1FIRST 1
#define THR 1
#define TSD 1500
#define KC 1
#define PAUSE 0
#define PFA_T 0
#define PFA_S 0
#define HINTM 5
#define GOK 1
#define PFX 1
#define ROT 0
#define LOWP 1
#define PFL 0
#define TRED 1
#define RSW 1
#define MAP4 1
#define PFD 1
#define PF_N0 4
#define FW0 7
#define FW1 3
#define VDT 0
#define WPROMO CU_TENSOR_MAP_L2_PROMOTION_L2_128B
#define GO0 1
#define NC0 2
#define FAST0 1
#define PK 8
#define PACE2 200
#define PTIME(c) ((c) <= PK ? (c) * PACE : PK * PACE + ((c) - PK) * PACE2)
#define POLL_AT 3
#define BFIRST 0
#define MPOLL 0
#define POLL_D 0
#define BGAP 350
#define LATEH 0
#define INITH 500
#define INITS 200
#define NARROW 1
#define TS_D 200
#define ADEL 300
#define ALN 0
#define ALW 48
#define NOMC 0
#define TORD 1
#define ECUT 0x54
#define NOFW 1
#define FILL 0
#define RDT 0
#define KEYS_NS 500
#define TT 0
#define TOFF 1850
#define TPER 512
#define FSP 0
#define ESTG 5
#define XL_AT 7
#define PD0 500
#define PD1 200
#define OL_T0 0
#define OL_DT 480
#define RS1 0
#define RSPLIT 1
#define GO_LATE 0
#define SUM_T0 15000
#define ROUTER_C 4
#define SHUF 1
#define POLL_NS 100

constexpr int S_ = 2048, D_ = 512, F_ = 1792;
constexpr int NCTA = 128;
constexpr int NTHREADS = 512;
constexpr int NSTAGE = 6;
constexpr int REGION = 32768;
constexpr int FFN_CTAS = F_ / 16;
constexpr uint32_t SPIN_LIMIT = 1u << 22;

constexpr int OFF_MISC = 7 * REGION;
constexpr int B_F = OFF_MISC;
constexpr int B_G0 = B_F + 64;
constexpr int B_G1 = B_G0 + 8;
constexpr int B_XE = B_G1 + 8;
constexpr int B_GO1 = B_XE + 8;
constexpr int B_SKEW0 = B_GO1 + 8;
constexpr int B_EPOCH = B_SKEW0 + 8;
constexpr int B_RETRY = B_EPOCH + 8;
constexpr int B_INIT = B_RETRY + 8;
constexpr int B_FULL = B_INIT + 8;
constexpr int B_EMPTY = B_FULL + 48;
constexpr int B_PUBI = B_EMPTY + 48;
constexpr int B_FREE = B_PUBI + 8;
constexpr int B_VD = B_FREE + 16;
constexpr int B_BL = B_VD + 8;
constexpr int B_TAIL = B_BL + 48;
constexpr int B_HX = B_TAIL + 8;
constexpr int B_FFN = B_HX + 8;
constexpr int B_ROLE = B_FFN + 40;
constexpr int B_SEEN = B_ROLE + 8;
constexpr int B_GATE = B_SEEN + 16;
constexpr int B_G2 = B_GATE + 8;
constexpr int B_FILL = B_G2 + 8;
constexpr int M_EPOCH = B_FILL + 8;
constexpr int M_T0 = OFF_MISC + 432;
constexpr int M_ROLE = M_EPOCH + 4;
constexpr int M_RED = OFF_MISC + 416;
constexpr int M_HX = OFF_MISC + 512;
constexpr int M_G = M_HX + 1024;
constexpr int M_UPD = M_G + 512;
constexpr int M_PROF = M_UPD + 512;
constexpr int SMEM_BYTES = 232448;
static_assert(M_ROLE + 4 <= M_RED && M_UPD + 512 <= SMEM_BYTES, "smem");

struct Scratch {
    unsigned char ab[8 * 32 * 16384];
    unsigned int hint[8 * 16 * 32];
    unsigned int sync[8 * 32];
    unsigned int ready[8 * 32];
    unsigned int gate[S_];
    unsigned int part[FFN_CTAS / 2 * D_];
    unsigned int phint[4 * 16 * 8];
    unsigned int keys[8 * NCTA];
    unsigned int epoch[NCTA + 4];
};
__device__ __align__(1024) Scratch g_s;

struct Params {
    Scratch* s;
    bf16* out;
    const bf16 *x, *gate_w, *w_r, *wg, *wu, *wd;
    CUtensorMap mDre, mDim, mX1, mX2, mCre, mCim, mAB, mOut, mWg, mWu, mWd;
};

__device__ __forceinline__ uint32_t smem_u32(const void* p) { return (uint32_t)__cvta_generic_to_shared(p); }
#define PROFL(i) do {} while (0)
#define PROFIF(slot, pred) do {} while (0)
#define PROF(slot) do {} while (0)
#define PROFG(slot) do {} while (0)

__device__ __forceinline__ void mbar_init(uint32_t bar, uint32_t cnt) {
    asm volatile("mbarrier.init.shared::cta.b64 [%0], %1;" ::"r"(bar), "r"(cnt) : "memory");
}
__device__ __forceinline__ void mbar_expect_tx(uint32_t bar, uint32_t bytes) {
    asm volatile("mbarrier.arrive.expect_tx.shared::cta.b64 _, [%0], %1;" ::"r"(bar), "r"(bytes) : "memory");
}
__device__ __forceinline__ void mbar_arrive(uint32_t bar) {
    asm volatile("mbarrier.arrive.shared::cta.b64 _, [%0];" ::"r"(bar) : "memory");
}
__device__ __forceinline__ void mbar_arrive_if(uint32_t bar, bool pred) {
    asm volatile("{.reg .pred p; setp.ne.b32 p, %1, 0; @p mbarrier.arrive.shared::cta.b64 _, [%0];}" ::"r"(bar), "r"((int)pred) : "memory");
}
__device__ __forceinline__ void mbar_arrive_warp(uint32_t bar) {
    __syncwarp();
    mbar_arrive_if(bar, (threadIdx.x & 31) == 0);
}
__device__ __forceinline__ void mbar_arrive_cluster_if(uint32_t bar, bool pred) {
    asm volatile("{.reg .pred p; setp.ne.b32 p, %1, 0; @p mbarrier.arrive.shared::cluster.b64 _, [%0], 1;}"
                 ::"r"(bar), "r"((int)pred) : "memory");
}
__device__ __forceinline__ uint32_t mapa(uint32_t a, uint32_t cta) {
    uint32_t r;
    asm volatile("mapa.shared::cluster.u32 %0, %1, %2;" : "=r"(r) : "r"(a), "r"(cta));
    return r;
}
__device__ __forceinline__ bool mbar_try(uint32_t bar, uint32_t parity) {
    uint32_t ok;
    asm volatile("{.reg .pred p; mbarrier.try_wait.parity.shared::cta.b64 p, [%1], %2; selp.u32 %0,1,0,p;}"
                 : "=r"(ok) : "r"(bar), "r"(parity) : "memory");
    return ok;
}
__device__ __forceinline__ bool mbar_test(uint32_t bar, uint32_t parity) {
    uint32_t ok;
    asm volatile("{.reg .pred p; mbarrier.test_wait.parity.shared::cta.b64 p, [%1], %2; selp.u32 %0,1,0,p;}"
                 : "=r"(ok) : "r"(bar), "r"(parity) : "memory");
    return ok;
}
__device__ __forceinline__ void mbar_wait(uint32_t bar, uint32_t parity) {
    asm volatile("{.reg .pred p, q; .reg .u32 n; mov.u32 n, 0;\n"
                 "W%=: mbarrier.try_wait.parity.shared::cta.b64 p, [%0], %1;\n"
                 "add.u32 n, n, 1; setp.lt.and.u32 q, n, %2, !p; @q bra W%=; @!p trap;}" ::"r"(bar), "r"(parity), "n"(SPIN_LIMIT) : "memory");
}
__device__ __forceinline__ void mbar_spin(uint32_t bar, uint32_t parity) {
    asm volatile("{.reg .pred p;\nW%=: mbarrier.try_wait.parity.shared::cta.b64 p, [%0], %1; @!p bra W%=;}" ::"r"(bar), "r"(parity) : "memory");
}
__device__ __forceinline__ void mbar_wait_cluster(uint32_t bar, uint32_t parity) {
    uint32_t n = 0, ok;
    do {
        asm volatile("{.reg .pred p; mbarrier.try_wait.parity.acquire.cluster.shared::cta.b64 p, [%1], %2; selp.u32 %0,1,0,p;}"
                     : "=r"(ok) : "r"(bar), "r"(parity) : "memory");
        if (++n > SPIN_LIMIT) __trap();
    } while (!ok);
}
__device__ __forceinline__ void tma2d(uint32_t dst, const CUtensorMap* m, int c0, int c1, uint32_t bar) {
    asm volatile("cp.async.bulk.tensor.2d.shared::cluster.global.mbarrier::complete_tx::bytes [%0], [%1, {%3,%4}], [%2];"
                 ::"r"(dst), "l"(m), "r"(bar), "r"(c0), "r"(c1) : "memory");
}
__device__ __forceinline__ void tma2d_elect(uint32_t dst, const CUtensorMap* m, int c0, int c1, uint32_t bar) {
    asm volatile("{.reg .pred p; elect.sync _|p, 0xffffffff;"
                 " @p cp.async.bulk.tensor.2d.shared::cluster.global.mbarrier::complete_tx::bytes [%0], [%1, {%3,%4}], [%2];}"
                 ::"r"(dst), "l"(m), "r"(bar), "r"(c0), "r"(c1) : "memory");
}
__device__ __forceinline__ void tma2d_pair_elect(uint32_t dst, const CUtensorMap* m, int c0, int c1, uint32_t bar) {
    asm volatile("{.reg .pred p; elect.sync _|p, 0xffffffff;"
                 " @p cp.async.bulk.tensor.2d.shared::cluster.global.mbarrier::complete_tx::bytes.multicast::cluster"
                 " [%0], [%1, {%3,%4}], [%2], %5;}" ::"r"(dst), "l"(m), "r"(bar), "r"(c0), "r"(c1), "h"((uint16_t)3) : "memory");
}
__device__ __forceinline__ void mbar_expect_tx_elect(uint32_t bar, uint32_t bytes) {
    asm volatile("{.reg .pred p; elect.sync _|p, 0xffffffff; @p mbarrier.arrive.expect_tx.shared::cta.b64 _, [%0], %1;}"
                 ::"r"(bar), "r"(bytes) : "memory");
}
__device__ __forceinline__ void tma3d(uint32_t dst, const CUtensorMap* m, int row, int chunk, uint32_t bar) {
    asm volatile("cp.async.bulk.tensor.3d.shared::cluster.global.mbarrier::complete_tx::bytes [%0], [%1, {%3,%4,%5}], [%2];"
                 ::"r"(dst), "l"(m), "r"(bar), "r"(0), "r"(row), "r"(chunk) : "memory");
}
__device__ __forceinline__ void tma2d_prefetch(const CUtensorMap* m, int c0, int c1) {
    asm volatile("cp.async.bulk.prefetch.tensor.2d.L2.global [%0, {%1,%2}];" ::"l"(m), "r"(c0), "r"(c1) : "memory");
}
__device__ __forceinline__ void fence_proxy_async_smem() { asm volatile("fence.proxy.async.shared::cta;" ::: "memory"); }
__device__ __forceinline__ void fence_proxy_async_gmem() { asm volatile("fence.proxy.async.global;" ::: "memory"); }
__device__ __forceinline__ void prefetch_l2(const void* p) { asm volatile("prefetch.global.L2 [%0];" ::"l"(p)); }
__device__ __forceinline__ uint32_t ld_relaxed(const void* p) {
    uint32_t v;
    asm volatile("ld.relaxed.gpu.global.u32 %0, [%1];" : "=r"(v) : "l"(p) : "memory");
    return v;
}
__device__ __forceinline__ uint4 ld_relaxed4(const void* p) {
    uint4 v;
    asm volatile("ld.relaxed.gpu.global.v4.u32 {%0,%1,%2,%3}, [%4];" : "=r"(v.x), "=r"(v.y), "=r"(v.z), "=r"(v.w) : "l"(p) : "memory");
    return v;
}
__device__ __forceinline__ uint4 ld_relaxed_b128(const void* p) {
    uint4 v;
    asm volatile("{.reg .b128 t; ld.relaxed.gpu.global.b128 t, [%4]; mov.b128 {%0,%1,%2,%3}, t;}"
                 : "=r"(v.x), "=r"(v.y), "=r"(v.z), "=r"(v.w) : "l"(p) : "memory");
    return v;
}
__device__ __forceinline__ uint4 ld_relaxed_b128_if(const void* p, bool pred) {
    uint4 v = make_uint4(0, 0, 0, 0);
    asm volatile("{.reg .b128 t; .reg .pred p; setp.ne.b32 p, %5, 0; mov.b128 t, {%0,%1,%2,%3};"
                 " @p ld.relaxed.gpu.global.b128 t, [%4]; mov.b128 {%0,%1,%2,%3}, t;}"
                 : "+r"(v.x), "+r"(v.y), "+r"(v.z), "+r"(v.w) : "l"(p), "r"((int)pred) : "memory");
    return v;
}
__device__ __forceinline__ void st_relaxed_b128(void* p, uint32_t x, uint32_t y, uint32_t z, uint32_t w) {
    asm volatile("{.reg .b128 t; .reg .b64 a, b; mov.b64 a, {%1,%2}; mov.b64 b, {%3,%4}; mov.b128 t, {a, b};"
                 " st.relaxed.gpu.global.b128 [%0], t;}" ::"l"(p), "r"(x), "r"(y), "r"(z), "r"(w) : "memory");
}
__device__ __forceinline__ void st_relaxed(unsigned int* p, uint32_t v) {
    asm volatile("st.relaxed.gpu.global.u32 [%0], %1;" ::"l"(p), "r"(v) : "memory");
}
__device__ __forceinline__ void st_relaxed_if(unsigned int* p, uint32_t v, bool pred) {
    asm volatile("{.reg .pred p; setp.ne.b32 p, %2, 0; @p st.relaxed.gpu.global.u32 [%0], %1;}" ::"l"(p), "r"(v), "r"((int)pred) : "memory");
}
__device__ __forceinline__ void red_inc_if(unsigned int* p, bool pred) {
    asm volatile("{.reg .pred p; setp.ne.b32 p, %1, 0; @p red.relaxed.gpu.global.inc.u32 [%0], 0xffffffff;}" ::"l"(p), "r"((int)pred) : "memory");
}
__device__ __forceinline__ void st_key(unsigned int* p, uint32_t v) {
    asm volatile("{.reg .b32 old; atom.relaxed.gpu.global.exch.b32 old, [%0], %1;}" ::"l"(p), "r"(v) : "memory");
}
__device__ __forceinline__ uint32_t tagf(float v, uint32_t par) { return (__float_as_uint(v) & ~1u) | par; }
__device__ __forceinline__ uint4 wait_tags(const unsigned int* p, int bit, uint32_t par) {
    uint32_t n = 0;
    while (true) {
        const uint4 v = ld_relaxed4(p);
        const uint32_t m = par ? (v.x & v.y & v.z & v.w) : ~(v.x | v.y | v.z | v.w);
        if (__all_sync(0xffffffffu, (m >> bit) & 1u)) return v;
        __nanosleep(POLL_NS);
        if (++n > SPIN_LIMIT) __trap();
    }
}
template <int SLEEP>
__device__ __forceinline__ void wait_counters(const unsigned int* p, uint32_t want) {
    uint32_t n = 0;
    while (!__all_sync(0xffffffffu, (int)(ld_relaxed(p) - want) >= 0)) {
        if (SLEEP) __nanosleep(SLEEP);
        if (++n > SPIN_LIMIT) __trap();
    }
    asm volatile("fence.acquire.gpu;" ::: "memory");
}
__device__ __forceinline__ void red_release_add(unsigned int* p, uint32_t v) {
    asm volatile("red.release.gpu.global.add.u32 [%0], %1;" ::"l"(p), "r"(v) : "memory");
}
__device__ __forceinline__ void named_bar(int id, int n) { asm volatile("bar.sync %0, %1;" ::"r"(id), "r"(n) : "memory"); }
template <int OFF>
__device__ __forceinline__ uint4 ldg_nc_off(const void* p) {
    uint4 v;
    asm volatile("ld.global.nc.v4.u32 {%0,%1,%2,%3}, [%4+%5];" : "=r"(v.x), "=r"(v.y), "=r"(v.z), "=r"(v.w) : "l"(p), "n"(OFF));
    return v;
}
template <int OFF>
__device__ __forceinline__ void stg_off_if(void* p, const uint4& v, bool pred) {
    asm volatile("{.reg .pred p; setp.ne.b32 p, %6, 0; @p st.global.v4.u32 [%0+%5], {%1,%2,%3,%4};}"
                 ::"l"(p), "r"(v.x), "r"(v.y), "r"(v.z), "r"(v.w), "n"(OFF), "r"((int)pred) : "memory");
}
template <int OFF>
__device__ __forceinline__ void stg_off(void* p, const uint4& v) {
    asm volatile("st.global.v4.u32 [%0+%5], {%1,%2,%3,%4};" ::"l"(p), "r"(v.x), "r"(v.y), "r"(v.z), "r"(v.w), "n"(OFF) : "memory");
}
__device__ __forceinline__ void sts128(uint32_t a, const uint4& v) {
    asm volatile("st.shared.v4.u32 [%0], {%1,%2,%3,%4};" ::"r"(a), "r"(v.x), "r"(v.y), "r"(v.z), "r"(v.w) : "memory");
}
__device__ __forceinline__ uint4 lds128(uint32_t a) {
    uint4 v;
    asm volatile("ld.shared.v4.u32 {%0,%1,%2,%3}, [%4];" : "=r"(v.x), "=r"(v.y), "=r"(v.z), "=r"(v.w) : "r"(a) : "memory");
    return v;
}
__device__ __forceinline__ float selpf(float a, float b, bool p) {
    float r;
    asm("{.reg .pred q; setp.ne.b32 q, %3, 0; selp.f32 %0, %1, %2, q;}" : "=f"(r) : "f"(a), "f"(b), "r"((int)p));
    return r;
}
template <int N, int MASK, int SZ>
__device__ __forceinline__ void halve(float (&a)[SZ]) {
    const bool up = threadIdx.x & MASK;
#pragma unroll
    for (int j = 0; j < N; j++) a[j] = selpf(a[N + j], a[j], up) + __shfl_xor_sync(0xffffffffu, selpf(a[j], a[N + j], up), MASK);
}
__device__ __forceinline__ float bflo(uint32_t u) { return __uint_as_float(u << 16); }
__device__ __forceinline__ float bfhi(uint32_t u) { return __uint_as_float(u & 0xffff0000u); }
__device__ __forceinline__ uint32_t pack_bf16(float lo, float hi) {
    uint32_t r;
    asm("cvt.rn.bf16x2.f32 %0, %1, %2;" : "=r"(r) : "f"(hi), "f"(lo));
    return r;
}
__device__ __forceinline__ uint32_t hfma2_bf16(uint32_t a, uint32_t b, uint32_t c) {
    uint32_t r;
    asm("fma.rn.bf16x2 %0, %1, %2, %3;" : "=r"(r) : "r"(a), "r"(b), "r"(c));
    return r;
}
__device__ __forceinline__ uint32_t hmul2_bf16(uint32_t a, uint32_t b) {
    uint32_t r;
    asm("mul.rn.bf16x2 %0, %1, %2;" : "=r"(r) : "r"(a), "r"(b));
    return r;
}
__device__ __forceinline__ float rbf(float v) { return bflo(pack_bf16(v, 0.f)); }
__device__ __forceinline__ float sigmoidf_(float v) { return __frcp_rn(1.0f + __expf(-v)); }

__device__ __forceinline__ void wg_fence() { asm volatile("wgmma.fence.sync.aligned;" ::: "memory"); }
__device__ __forceinline__ void wg_commit() { asm volatile("wgmma.commit_group.sync.aligned;" ::: "memory"); }
template <int N> __device__ __forceinline__ void wg_wait() { asm volatile("wgmma.wait_group.sync.aligned %0;" ::"n"(N) : "memory"); }
__device__ __forceinline__ uint64_t desc64_lo(uint32_t lo) { return (uint64_t)lo | (0x80000020ull << 32); }
__device__ __forceinline__ uint64_t desc_lo(uint32_t lo) { return (uint64_t)lo | (0x40000040ull << 32); }
template <int LO, int HI, int N>
__device__ __forceinline__ void fence_regs(float (&d)[N]) {
#pragma unroll
    for (int i = LO; i < HI; i++) asm volatile("" : "+f"(d[i])::"memory");
}
template <int TB = 1>
__device__ __forceinline__ void wgmma128(float (&d)[64], uint64_t da, uint64_t db, int scaleD) {
    asm volatile(
        "{ .reg .pred p; setp.ne.b32 p, %66, 0;\n"
        "wgmma.mma_async.sync.aligned.m64n128k16.f32.bf16.bf16 "
        "{%0,%1,%2,%3,%4,%5,%6,%7,%8,%9,%10,%11,%12,%13,%14,%15,%16,%17,%18,%19,%20,%21,%22,%23,%24,%25,%26,%27,%28,%29,%30,%31,"
        "%32,%33,%34,%35,%36,%37,%38,%39,%40,%41,%42,%43,%44,%45,%46,%47,%48,%49,%50,%51,%52,%53,%54,%55,%56,%57,%58,%59,%60,%61,%62,%63}, "
        "%64, %65, p, 1, 1, 0, %67;\n}"
        : "+f"(d[0]), "+f"(d[1]), "+f"(d[2]), "+f"(d[3]), "+f"(d[4]), "+f"(d[5]), "+f"(d[6]), "+f"(d[7]),
          "+f"(d[8]), "+f"(d[9]), "+f"(d[10]), "+f"(d[11]), "+f"(d[12]), "+f"(d[13]), "+f"(d[14]), "+f"(d[15]),
          "+f"(d[16]), "+f"(d[17]), "+f"(d[18]), "+f"(d[19]), "+f"(d[20]), "+f"(d[21]), "+f"(d[22]), "+f"(d[23]),
          "+f"(d[24]), "+f"(d[25]), "+f"(d[26]), "+f"(d[27]), "+f"(d[28]), "+f"(d[29]), "+f"(d[30]), "+f"(d[31]),
          "+f"(d[32]), "+f"(d[33]), "+f"(d[34]), "+f"(d[35]), "+f"(d[36]), "+f"(d[37]), "+f"(d[38]), "+f"(d[39]),
          "+f"(d[40]), "+f"(d[41]), "+f"(d[42]), "+f"(d[43]), "+f"(d[44]), "+f"(d[45]), "+f"(d[46]), "+f"(d[47]),
          "+f"(d[48]), "+f"(d[49]), "+f"(d[50]), "+f"(d[51]), "+f"(d[52]), "+f"(d[53]), "+f"(d[54]), "+f"(d[55]),
          "+f"(d[56]), "+f"(d[57]), "+f"(d[58]), "+f"(d[59]), "+f"(d[60]), "+f"(d[61]), "+f"(d[62]), "+f"(d[63])
        : "l"(da), "l"(db), "r"(scaleD), "n"(TB));
}

__device__ __forceinline__ void mbar_init_elect(uint32_t bar, uint32_t cnt) {
    asm volatile("{.reg .pred p; elect.sync _|p, 0xffffffff; @p mbarrier.init.shared::cta.b64 [%0], %1;}" ::"r"(bar), "r"(cnt) : "memory");
}
__device__ __forceinline__ void mbar_arrive_elect(uint32_t bar) {
    asm volatile("{.reg .pred p; elect.sync _|p, 0xffffffff; @p mbarrier.arrive.shared::cta.b64 _, [%0];}" ::"r"(bar) : "memory");
}
__device__ __forceinline__ void tma3d_elect(uint32_t dst, const CUtensorMap* m, int row, int chunk, uint32_t bar) {
    asm volatile("{.reg .pred p; elect.sync _|p, 0xffffffff;"
                 " @p cp.async.bulk.tensor.3d.shared::cluster.global.mbarrier::complete_tx::bytes [%0], [%1, {%3,%4,%5}], [%2];}"
                 ::"r"(dst), "l"(m), "r"(bar), "r"(0), "r"(row), "r"(chunk) : "memory");
}
template <int N>
__device__ __forceinline__ void mbar_arrive_n_elect(uint32_t bar) {
    asm volatile("{.reg .pred p; elect.sync _|p, 0xffffffff; @p mbarrier.arrive.shared::cta.b64 _, [%0], %1;}" ::"r"(bar), "n"(N) : "memory");
}
template <int N>
__device__ __forceinline__ void bulk_store_elect(void* dst, uint32_t src) {
    asm volatile("{.reg .pred p; elect.sync _|p, 0xffffffff; @p cp.async.bulk.global.shared::cta.bulk_group [%0], [%1], %2;}"
                 ::"l"(dst), "r"(src), "n"(N) : "memory");
}
__device__ __forceinline__ void bulk_wait_read() {
    asm volatile("cp.async.bulk.commit_group; cp.async.bulk.wait_group.read 0;" ::: "memory");
    __syncwarp();
}
template <int N>
__device__ __forceinline__ void release_pair(uint32_t bar, uint32_t rbar, bool pred) {
    asm volatile("{.reg .pred p; setp.ne.b32 p, %2, 0; @p mbarrier.arrive.shared::cta.b64 _, [%0], %3;"
                 " @p mbarrier.arrive.shared::cluster.b64 _, [%1], %3;}" ::"r"(bar), "r"(rbar), "r"((int)pred), "n"(N) : "memory");
}
template <int OFF>
__device__ __forceinline__ void red_bf16x8(void* p, uint32_t x, uint32_t y, uint32_t z, uint32_t w) {
    asm volatile("red.relaxed.gpu.global.add.noftz.v4.bf16x2 [%0+%5], {%1,%2,%3,%4};"
                 ::"l"(p), "r"(x), "r"(y), "r"(z), "r"(w), "n"(OFF) : "memory");
}
template <int OFF>
__device__ __forceinline__ uint32_t lds32_off(uint32_t a) {
    uint32_t v;
    asm volatile("ld.shared.u32 %0, [%1+%2];" : "=r"(v) : "r"(a), "n"(OFF) : "memory");
    return v;
}
template <int OFF>
__device__ __forceinline__ void sts128_off(uint32_t a, const uint4& v) {
    asm volatile("st.shared.v4.u32 [%0+%5], {%1,%2,%3,%4};" ::"r"(a), "r"(v.x), "r"(v.y), "r"(v.z), "r"(v.w), "n"(OFF) : "memory");
}

__device__ __forceinline__ uint32_t gtime() {
    uint32_t t;
    asm volatile("mov.u32 %0, %%globaltimer_lo;" : "=r"(t));
    return t;
}
__device__ __forceinline__ uint2 ld_relaxed2(const void* p) {
    uint2 v;
    asm volatile("{.reg .b64 t; ld.relaxed.gpu.global.b64 t, [%2]; mov.b64 {%0,%1}, t;}" : "=r"(v.x), "=r"(v.y) : "l"(p) : "memory");
    return v;
}
__device__ __forceinline__ void st_stamp_if(unsigned int* p, uint32_t v, bool pred) {
    asm volatile("{.reg .pred p; .reg .b32 t; .reg .b64 w; setp.ne.b32 p, %2, 0; mov.u32 t, %%globaltimer_lo; mov.b64 w, {%1, t};"
                 " @p st.relaxed.gpu.global.b64 [%0], w;}" ::"l"(p), "r"(v), "r"((int)pred) : "memory");
}
__device__ __forceinline__ void sched_cut() {
    asm volatile("{.reg .pred p; .reg .u64 t; .reg .u32 a, b;\nC%=: mov.u64 t, %%clock64; mov.b64 {a, b}, t; setp.eq.u32 p, a, %0; @p bra C%=;}" ::"n"(0) : "memory");
}
__device__ __forceinline__ uint32_t pin(uint32_t v) { return __shfl_xor_sync(0xffffffffu, v, 0); }
template <class T>
__device__ __forceinline__ T* pin(T* p) { return (T*)__shfl_xor_sync(0xffffffffu, (unsigned long long)p, 0); }
template <class T>
__device__ __forceinline__ T* pin_uniform(T* p) { return (T*)__shfl_sync(0xffffffffu, (unsigned long long)p, 0); }
__device__ __forceinline__ uint32_t stale_tags(uint32_t a, uint32_t par) {
    uint32_t r;
    asm volatile("{.reg .b32 v<16>;\n"
                 "ld.shared.u32 v0, [%1]; ld.shared.u32 v1, [%1+256]; ld.shared.u32 v2, [%1+512]; ld.shared.u32 v3, [%1+768];\n"
                 "ld.shared.u32 v4, [%1+4096]; ld.shared.u32 v5, [%1+4352]; ld.shared.u32 v6, [%1+4608]; ld.shared.u32 v7, [%1+4864];\n"
                 "ld.shared.u32 v8, [%1+8192]; ld.shared.u32 v9, [%1+8448]; ld.shared.u32 v10, [%1+8704]; ld.shared.u32 v11, [%1+8960];\n"
                 "ld.shared.u32 v12, [%1+12288]; ld.shared.u32 v13, [%1+12544]; ld.shared.u32 v14, [%1+12800]; ld.shared.u32 v15, [%1+13056];\n"
                 "lop3.b32 v0, v0, v1, %2, 0x7e; lop3.b32 v2, v2, v3, %2, 0x7e; lop3.b32 v4, v4, v5, %2, 0x7e; lop3.b32 v6, v6, v7, %2, 0x7e;\n"
                 "lop3.b32 v8, v8, v9, %2, 0x7e; lop3.b32 v10, v10, v11, %2, 0x7e; lop3.b32 v12, v12, v13, %2, 0x7e; lop3.b32 v14, v14, v15, %2, 0x7e;\n"
                 "lop3.b32 v0, v0, v2, v4, 0xfe; lop3.b32 v6, v6, v8, v10, 0xfe; lop3.b32 v0, v0, v6, v12, 0xfe; or.b32 %0, v0, v14;}"
                 : "=r"(r) : "r"(a), "r"(par) : "memory");
    return r;
}

__device__ __forceinline__ void wgmma128_rs(float (&d)[64], const uint32_t* a, uint64_t db, int scaleD) {
    asm volatile(
        "{ .reg .pred p; setp.ne.b32 p, %69, 0;\n"
        "wgmma.mma_async.sync.aligned.m64n128k16.f32.bf16.bf16 "
        "{%0,%1,%2,%3,%4,%5,%6,%7,%8,%9,%10,%11,%12,%13,%14,%15,%16,%17,%18,%19,%20,%21,%22,%23,%24,%25,%26,%27,%28,%29,%30,%31,"
        "%32,%33,%34,%35,%36,%37,%38,%39,%40,%41,%42,%43,%44,%45,%46,%47,%48,%49,%50,%51,%52,%53,%54,%55,%56,%57,%58,%59,%60,%61,%62,%63}, "
        "{%64,%65,%66,%67}, %68, p, 1, 1, 0;\n}"
        : "+f"(d[0]), "+f"(d[1]), "+f"(d[2]), "+f"(d[3]), "+f"(d[4]), "+f"(d[5]), "+f"(d[6]), "+f"(d[7]),
          "+f"(d[8]), "+f"(d[9]), "+f"(d[10]), "+f"(d[11]), "+f"(d[12]), "+f"(d[13]), "+f"(d[14]), "+f"(d[15]),
          "+f"(d[16]), "+f"(d[17]), "+f"(d[18]), "+f"(d[19]), "+f"(d[20]), "+f"(d[21]), "+f"(d[22]), "+f"(d[23]),
          "+f"(d[24]), "+f"(d[25]), "+f"(d[26]), "+f"(d[27]), "+f"(d[28]), "+f"(d[29]), "+f"(d[30]), "+f"(d[31]),
          "+f"(d[32]), "+f"(d[33]), "+f"(d[34]), "+f"(d[35]), "+f"(d[36]), "+f"(d[37]), "+f"(d[38]), "+f"(d[39]),
          "+f"(d[40]), "+f"(d[41]), "+f"(d[42]), "+f"(d[43]), "+f"(d[44]), "+f"(d[45]), "+f"(d[46]), "+f"(d[47]),
          "+f"(d[48]), "+f"(d[49]), "+f"(d[50]), "+f"(d[51]), "+f"(d[52]), "+f"(d[53]), "+f"(d[54]), "+f"(d[55]),
          "+f"(d[56]), "+f"(d[57]), "+f"(d[58]), "+f"(d[59]), "+f"(d[60]), "+f"(d[61]), "+f"(d[62]), "+f"(d[63])
        : "r"(a[0]), "r"(a[1]), "r"(a[2]), "r"(a[3]), "l"(db), "r"(scaleD));
}
__device__ __forceinline__ void ldsm4(uint32_t* r, uint32_t a) {
    asm volatile("ldmatrix.sync.aligned.m8n8.x4.shared.b16 {%0,%1,%2,%3}, [%4];" : "=r"(r[0]), "=r"(r[1]), "=r"(r[2]), "=r"(r[3]) : "r"(a) : "memory");
}

__device__ __forceinline__ void load_b(uint32_t dst, const CUtensorMap* m, int row, uint32_t bar) {
    tma2d_pair_elect(dst, m, 0, row, bar);
}
__device__ __forceinline__ int tile_of_step(int step, int own, int kh) {
    const int u = step >= 17 ? step - 17 : step - 1 - (step > OLS);
    int e = (u + (u >= ((own - 8 * kh) & 14) ? 2 : 0) + 8 * kh) & 15;
    if (u == 14) e = own ^ 1;
    if (step == 0 || step == OLS) e = own;
    return e + (step >= 17 || step == OLS ? 16 : 0);
}
__device__ __forceinline__ uint32_t router_key(float score, int row) {
    const float r = score + 0.0f;
    uint32_t u = pack_bf16(r, 0.f) & 0xffffu;
    u = (u & 0x8000u) ? (~u & 0xffffu) : (u | 0x8000u);
    if (r != r) u = 0;
    return (u << 16) | (uint32_t)(0x7fff - row);
}

#define g_fb_h ((float*)g_s.part)
#define g_fb_upd (g_fb_h + 2048)
#define g_fb_gate (g_fb_h + 4096)
#define g_fb_keys (g_s.part + 8192)
__global__ void fb_hidden(const bf16* x, const bf16* dre, const bf16* dim, const bf16* gw, const bf16* wr) {
    __shared__ float xs[D_];
    const int s = blockIdx.x, t = threadIdx.x;
    xs[t] = __bfloat162float(x[s * D_ + t]);
    __syncthreads();
    float a = 0.f, b = 0.f;
    for (int d = 0; d < D_; d++) { a = fmaf(xs[d], __bfloat162float(dre[t * D_ + d]), a); b = fmaf(xs[d], __bfloat162float(dim[t * D_ + d]), b); }
    ((bf16*)g_s.ab)[s * 1024 + t] = __float2bfloat16(a);
    ((bf16*)g_s.ab)[s * 1024 + 512 + t] = __float2bfloat16(b);
    if (t == 0) {
        float u = 0.f, v = 0.f;
        for (int d = 0; d < D_; d++) { u = fmaf(xs[d], __bfloat162float(gw[d]), u); v = fmaf(xs[d], __bfloat162float(wr[d]), v); }
        g_fb_gate[s] = sigmoidf_(u);
        g_fb_keys[s] = router_key(v, s);
    }
}
__device__ uint32_t fb_best() {
    uint32_t k = 0;
    for (int i = 0; i < S_; i++) k = max(k, g_fb_keys[i]);
    return k;
}
__global__ void fb_ffn1(const bf16* x, const bf16* wg, const bf16* wu) {
    const int f = blockIdx.x * blockDim.x + threadIdx.x, idx = 0x7fff - (int)(fb_best() & 0x7fffu);
    float a = 0.f, b = 0.f;
    for (int d = 0; d < D_; d++) {
        const float xv = __bfloat162float(x[idx * D_ + d]);
        a = fmaf(xv, __bfloat162float(wg[d * F_ + f]), a); b = fmaf(xv, __bfloat162float(wu[d * F_ + f]), b);
    }
    g_fb_h[f] = a * sigmoidf_(a) * b;
}
__global__ void fb_ffn2(const bf16* wd) {
    const int e = blockIdx.x * blockDim.x + threadIdx.x;
    const uint32_t u = fb_best() >> 16, rb = (u & 0x8000u) ? (u & 0x7fffu) : (~u & 0xffffu);
    float a = 0.f;
    for (int f = 0; f < F_; f++) a = fmaf(g_fb_h[f], __bfloat162float(wd[f * D_ + e]), a);
    g_fb_upd[e] = a * sigmoidf_(__uint_as_float(rb << 16));
}
__global__ void fb_seq(const bf16* x, const bf16* cre, const bf16* cim, bf16* out) {
    __shared__ float c[2][S_];
    __shared__ int idx;
    const int t = blockIdx.x, e = threadIdx.x;
    for (int i = e; i < S_; i += D_) { c[0][i] = __bfloat162float(cre[t * S_ + i]); c[1][i] = __bfloat162float(cim[t * S_ + i]); }
    if (e == 0) idx = 0x7fff - (int)(fb_best() & 0x7fffu);
    __syncthreads();
    float y = 0.f;
    for (int s = 0; s < S_; s++)
        y += c[0][s] * __bfloat162float(((const bf16*)g_s.ab)[s * 1024 + e]) - c[1][s] * __bfloat162float(((const bf16*)g_s.ab)[s * 1024 + 512 + e]);
    const float g = g_fb_gate[t];
    out[t * D_ + e] = __float2bfloat16(g * y + (1.f - g) * (__bfloat162float(x[t * D_ + e]) + (t == idx ? g_fb_upd[e] : 0.f)));
}

__device__ __forceinline__ void spare_job(const Params& p, unsigned char* smem, int sp, uint32_t tstart) {
    const int tid = threadIdx.x, warp = tid >> 5, lane = tid & 31;
    const uint32_t e1 = *(volatile unsigned int*)&p.s->epoch[NCTA + sp] + 1u;
    const uint32_t par = e1 & 1u;
    uint32_t* red = (uint32_t*)smem;
    __syncthreads();
    if (tid == 0) *(volatile unsigned int*)&p.s->epoch[NCTA + sp] = e1;
#pragma unroll 1
    for (int k = 0; k < (PFD ? 0 : 6); k++) {
        const char* src = k < 2 ? (const char*)p.wd + (sp * 2 + k) * 229376
                                : (const char*)((sp & 1) ? p.wu : p.wg) + ((sp >> 1) * 4 + k - 2) * 229376;
        while ((uint32_t)clock64() - tstart < PF_T0 + k * PF_DT) __nanosleep(LOWP ? 200 : 20);
        if (tid >= 448) {
            if (tid < 455) asm volatile("cp.async.bulk.prefetch.L2.global [%0], 16384;" ::"l"(src + (tid - 448) * 16384) : "memory");
        } else {
            prefetch_l2(src + 114688 + tid * 128);
            prefetch_l2(src + 172032 + tid * 128);
        }
        __syncwarp();
    }
    if (tid == 0) PROF(1);
    if (PFD) while ((uint32_t)clock64() - tstart < 13000) __nanosleep(500);
    if (warp == 0) {
        const uint4 k4 = wait_tags(p.s->keys + lane * 4, 15, par);
        const uint32_t k = __reduce_max_sync(0xffffffffu, max(max(k4.x, k4.y), max(k4.z, k4.w)));
        const int idx = 0x7fff - (int)(k & 0x7fffu);
        const uint4 g4 = wait_tags(p.s->gate + (idx & ~3), 0, par);
        const uint32_t gw = (idx & 2) ? ((idx & 1) ? g4.w : g4.z) : ((idx & 1) ? g4.y : g4.x);
        const uint32_t u = k >> 16;
        const uint32_t rb = (u & 0x8000u) ? (u & 0x7fffu) : (~u & 0xffffu);
        if (lane == 0) {
            red[16] = idx;
            const float og = 1.f - __uint_as_float(gw & ~1u), rs = sigmoidf_(__uint_as_float(rb << 16));
            red[17] = pack_bf16(og, og);
            red[18] = pack_bf16(rs, rs);
        }
    }
    while ((uint32_t)clock64() - tstart < SUM_T0) __nanosleep(200);
    float4 s = make_float4(0.f, 0.f, 0.f, 0.f);
    if (warp < 14) {
        uint32_t n = 0;
        while ((int)(ld_relaxed(p.s->phint + (sp * 16 + warp) * 8) - e1 * 8u) < 0) {
            __nanosleep(40);
            if (++n > SPIN_LIMIT) __trap();
        }
        if (tid == 0) PROF(2);
        const unsigned int* src = p.s->part + warp * 4 * D_ + sp * 128 + lane * 4;
        uint4 v[4];
        while (true) {
            uint32_t bad = 0;
#pragma unroll
            for (int i = 0; i < 4; i++) v[i] = ld_relaxed4(src + i * D_);
#pragma unroll
            for (int i = 0; i < 4; i++) bad |= (v[i].x ^ par) | (v[i].y ^ par) | (v[i].z ^ par) | (v[i].w ^ par);
            if (!__any_sync(0xffffffffu, bad & 1u)) break;
            if (++n > SPIN_LIMIT) __trap();
        }
#pragma unroll
        for (int i = 0; i < 4; i++) {
            s.x += __uint_as_float(v[i].x); s.y += __uint_as_float(v[i].y);
            s.z += __uint_as_float(v[i].z); s.w += __uint_as_float(v[i].w);
        }
    } else if (warp == 14) {
        wait_counters<100>(p.s->ready + (lane & 7) * 32, e1 * 16u);
    }
    float* acc = (float*)(smem + 1024);
    *(float4*)&acc[warp * 128 + lane * 4] = s;
    __syncthreads();
    if (tid < 64) {
        float t0 = 0.f, t1 = 0.f;
#pragma unroll
        for (int i = 0; i < 14; i++) {
            const float2 z = *(const float2*)&acc[i * 128 + tid * 2];
            t0 += z.x; t1 += z.y;
        }
        asm volatile("red.relaxed.gpu.global.add.noftz.bf16x2 [%0], %1;"
                     ::"l"(p.out + red[16] * D_ + sp * 128 + tid * 2), "r"(hmul2_bf16(red[17], hmul2_bf16(red[18], pack_bf16(t0, t1)))) : "memory");
    }
}

__host__ __device__ constexpr int off_d(int c) { return (c < 2 ? 1 : c / 2 + 2) * REGION + (c & 1) * 16384; }
__host__ __device__ constexpr int off_xe(int c) { return (c < 2 ? 6 * REGION : c < 4 ? 16384 : c < 6 ? 0 : 6 * REGION + 16384) + (c & 1) * 8192; }
__host__ __device__ constexpr int off_xl(int c) { return c < 4 ? 2 * REGION + c * 8192 : off_xe(c - 4); }

__global__ void __cluster_dims__(2, 1, 1) __launch_bounds__(NTHREADS, 1)
fused_kernel(const __grid_constant__ Params p) {
    extern __shared__ __align__(1024) unsigned char smem[];
    const uint32_t tstart = (uint32_t)clock64();
    const uint32_t sb = smem_u32(smem);
    const int tid = threadIdx.x, lane = tid & 31;
    const int rank = blockIdx.x & 1;
#define GET_ROLE(smid, role) asm volatile("mov.u32 %0, %%smid;" : "=r"(smid));                                \
    asm("{.reg .pred p, q; .reg .u32 t, a, b; shr.u32 t, %1, 1; mad.lo.u32 a, t, 293, -928; shr.u32 a, a, 8; mad.lo.u32 b, t, 8, -464;" \
        " setp.lt.u32 p, t, 32; setp.lt.u32 q, t, 62; selp.u32 a, a, b, q; selp.u32 %0, t, a, p;}" : "=r"(role) : "r"(smid))
    uint32_t t1 = 0;
    if (__any_sync(0xffffffffu, tid == 0)) {
        uint32_t s0, r0;
        GET_ROLE(s0, r0);
        if (FAST0 == 2) {
            asm volatile("{.reg .pred p; elect.sync _|p, 0xffffffff; @p prefetch.tensormap [%0]; @p prefetch.tensormap [%1]; @p prefetch.tensormap [%2];}"
                         ::"l"(&p.mDre), "l"(&p.mDim), "l"(&p.mX1) : "memory");
        }
        mbar_init_elect(sb + B_F, 1);
        if (r0 < 64) {
#pragma unroll
            for (int c = 0; c < NC0; c++) {
                if (c) {
                    while ((uint32_t)clock64() - t1 < PTIME(c)) {}
                    mbar_init_elect(sb + B_F + 8 * c, 1);
                }
                tma3d_elect(sb + off_d(c), &p.mDre + ((r0 >> 2) & 1), (r0 & 24) * 16, c, sb + B_F + 8 * c);
                tma3d_elect(sb + off_xe(c), &p.mX1, (r0 & 3) * 256 + (r0 & 32) * 4 + rank * 64, c, sb + B_F + 8 * c);
                mbar_expect_tx_elect(sb + B_F + 8 * c, 24576);
                if (c == FILL - 1) {
                    mbar_init_elect(sb + B_FILL, 1);
                    tma3d_elect(sb + off_xl(0), &p.mX1, (r0 & 3) * 256 + (r0 & 32) * 4 + rank * 64 + 1024, 0, sb + B_FILL);
                    mbar_expect_tx_elect(sb + B_FILL, 8192);
                }
                if (!c) t1 = (uint32_t)clock64();
            }
        }
    }
    const int warp = __shfl_sync(0xffffffffu, tid >> 5, 0);
    uint32_t smid, role;
    GET_ROLE(smid, role);
    const int gpc = role & 7;
    const int tn = (role >> 3) & 3;
    const int kh = gpc >> 2;
    const int own = (gpc & 3) * 4 + ((role >> 5) & 1) * 2 + rank;
    const int blk = kh * 4 + tn;
#define TCOL(e) (kh * 1024 + ((e) >> 3) * 256 + ((e) & 3) * 64)
#define TMAT(e) (((e) >> 2) & 1)
#define KROT 0
    const int comp = kh;
    const int xrow = own * 64;
    constexpr int XLATE = 1024;
    const CUtensorMap* mD = &p.mDre + comp;
    const int rot = ROT == 1 ? gpc & 6 : ROT == 2 ? (gpc & 2) * 2 : ROT == 3 ? gpc & 2 : ROT == 4 ? kh * 4 : 0;
    const int cta = gpc * 16 + (role >> 3) * 2 + rank;
    const bool ffn = FSP ? role < 56 : cta < FFN_CTAS;
    const int fp = FSP == 2 ? gpc * 7 + (role >> 3) : FSP ? role : cta >> 1;
    uint32_t epoch = 0;
#define CHUNK_LOAD(c) tma3d_elect(sb + off_d(c), mD, tn * 128, (c) ^ rot, sb + B_F + 8 * (c));                 \
                      tma3d_elect(sb + off_xe(c), &p.mX1, xrow, (c) ^ rot, sb + B_F + 8 * (c));                \
                      mbar_expect_tx_elect(sb + B_F + 8 * (c), 24576)
#define PACE_WAIT(c) while ((uint32_t)clock64() - t1 < PTIME(c)) {}
    if (warp != 0 || role >= 64) {
        const uint32_t b1 = sb + B_F + 8 * warp;
        mbar_init_elect(warp < NC0 ? b1 + 360 : b1, 1);
        if (warp >= NC0 && warp < 5) mbar_init_elect(b1 + 360, 1);
        mbar_init_elect(b1 + 120, warp < 7 ? 5 : warp < 14 ? 4 : 6);
        mbar_init_elect(b1 + 240, 1);
        if (warp == 9 || warp == 15) mbar_expect_tx_elect(b1 + 240, warp == 9 ? 2048 : 4);
        asm volatile("fence.mbarrier_init.release.cluster;" ::: "memory");
        if (tid == 128 && role < 64) epoch = *(volatile unsigned int*)&p.s->epoch[cta];
    } else {
    }
    if (role >= 64) {
        spare_job(p, smem, smid & 3, tstart);
        return;
    }
    __syncthreads();
    asm volatile("barrier.cluster.arrive.relaxed.aligned;" ::: "memory");
    if (warp == 0) {
#pragma unroll
        for (int c = NC0; c < 8; c++) {
            PACE_WAIT(c);
            CHUNK_LOAD(c);
            if (c == XL_AT) {
                if (FILL) tma3d_elect(sb + off_xl(1), &p.mX1, xrow + XLATE, 1, sb + B_G0);
                else tma3d_elect(sb + off_xl(0), &p.mX2, xrow + XLATE, 0 ^ rot, sb + B_G0);
                mbar_expect_tx_elect(sb + B_G0, FILL ? 8192 : 16384);
            }
            if (c == 7) {
                PACE_WAIT(8);
                tma3d_elect(sb + off_xl(2), &p.mX2, xrow + XLATE, 2 ^ rot, sb + B_G2);
                mbar_expect_tx_elect(sb + B_G2, 16384);
            }
        }
        if (PFX && tn < 2 && (KC && !MAP4 ? blk < 4 : true)) {
            asm volatile("{.reg .pred p; elect.sync _|p, 0xffffffff; @p cp.async.bulk.prefetch.tensor.3d.L2.global [%0, {%1,%2,%3}];}"
                         ::"l"(&p.mX2), "r"(0), "r"(xrow + XLATE), "r"((4 + 2 * (blk & 1)) ^ rot) : "memory");
        }
    }

    if (warp < 4) {
        if (warp == 0) {
            PROF(2);
            mbar_spin(sb + B_XE, 0);
            tma3d_elect(sb + off_xl(4), &p.mX2, xrow + XLATE, 4 ^ rot, sb + B_G1);
            tma3d_elect(sb + off_xl(6), &p.mX2, xrow + XLATE, 6 ^ rot, sb + B_G1);
            mbar_expect_tx_elect(sb + B_G1, 32768);
            PROF(3);
            const int el = tile_of_step(lane, own, KROT);
            const int taba = el * 64;
#define AMAP(c) &p.mCre + comp, c
            const int tabb = (blk * 32 + el) * 128 + rank * 64;
            const uint32_t dst = sb + 16384 + rank * 8192;
#define ABAR B_FULL
#define LOAD_A() const int c = __shfl_sync(0xffffffffu, taba, step);                                            \
                 const uint32_t bar = sb + 8 * slot;                                                            \
                 mbar_spin(bar + B_EMPTY, ph);                                                                  \
                 if (TT && step == TT) { mbar_spin(sb + B_SEEN, 0); due = *(volatile uint32_t*)(smem + M_T0) + TT * 512; } \
                 if (TT && step >= TT) { while ((int)((uint32_t)clock64() - due) < 0) {} due += TPER; }         \
                 tma2d_elect(sb + slot * REGION, AMAP(c), own * 128, bar + ABAR);   \
                 mbar_expect_tx_elect(bar + ABAR, 16384)
            uint32_t slot = 0, ph = 0, due = 0;
            int step = 0;
#pragma unroll 1
            for (; step < NSTAGE; step++, slot++) {
                LOAD_A();
                PROFIF(step == 0 ? 4 : 5, step == 0 || step == 5);
                if (ADEL && (step == 2 || step == 3)) { const uint32_t t4 = (uint32_t)clock64(); while ((uint32_t)clock64() - t4 < ADEL) {} }
            }
            slot = 0; ph = 1;
#pragma unroll 1
            for (int h = PE; h < 2; h++) {
#pragma unroll 1
                for (; step < 16 + 15 * h; step++) {
                    const int row = __shfl_sync(0xffffffffu, tabb, step);
                    LOAD_A();
                    if (!NARROW && (step == 6 || step == 17)) mbar_spin(sb + B_SEEN + (step >> 4) * 8, 0);
                    load_b(dst + slot * REGION, &p.mAB, row, bar + B_BL);
                    mbar_expect_tx_elect(bar + B_BL, 16384);
                    PROF(160 + step);
                    if (++slot == NSTAGE) { slot = 0; ph ^= 1; }
                }
                const int row = __shfl_sync(0xffffffffu, tabb, step);
                LOAD_A();
                tma2d_elect(dst + slot * REGION, &p.mAB, 0, row, bar + B_BL);
                tma2d_elect((dst ^ 8192) + slot * REGION, &p.mAB, 0, row ^ 64, bar + B_BL);
                mbar_expect_tx_elect(bar + B_BL, 16384);
                PROF(160 + step);
                step++; slot++;
            }
        } else if (warp == 1) {
            if (lane < 4) asm volatile("prefetch.tensormap [%0];" ::"l"(&p.mCre + lane) : "memory");
            __syncwarp();
            asm volatile("barrier.cluster.wait.acquire.aligned;" ::: "memory");
            if (lane == 0)
                asm volatile("st.async.weak.shared::cluster.mbarrier::complete_tx::bytes.u32 [%0], %1, [%2];"
                             ::"r"(mapa(sb + M_ROLE, rank ^ 1)), "r"(role), "r"(mapa(sb + B_ROLE, rank ^ 1)) : "memory");
            mbar_wait_cluster(sb + B_ROLE, 0);
            if (*(volatile uint32_t*)(smem + M_ROLE) != role) __trap();
            mbar_wait(sb + B_EPOCH, 0);
            const uint32_t want = *(volatile uint32_t*)(smem + M_EPOCH) + 1u;
            const int el = tile_of_step(lane, own, KROT) & 15;
            const int tab = (blk * 32 + el) * 128 + rank * 64;
            const int li = (lane - 2) & 3;
            const int eh = NARROW ? __shfl_sync(0xffffffffu, el, li + 1 + (li + 1 >= OLS)) : el;
            const unsigned int* hp = p.s->hint + (blk * 8 + (eh >> 1)) * 32 + (eh & 1) * 2;
            uint2 st = ld_relaxed2(hp);
            if (TT) (void)ld_relaxed2(p.s->sync + gpc * 32 + (lane & 15) * 2);
            const uint32_t wante = HINTM ? want * 4u : want;
            uint32_t seen = __ballot_sync(0xffffffffu, st.x == wante);
#define POLL() { st = ld_relaxed2(hp); seen = __ballot_sync(0xffffffffu, st.x == wante); }
#define RS(i) ((i) + 1 + ((i) + 1 >= OLS))
            int rows[4];
#pragma unroll
            for (int i = 0; i < 4; i++) {
                rows[i] = __shfl_sync(0xffffffffu, tab, RS(i));
                mbar_expect_tx_elect(sb + B_BL + 8 * RS(i), 16384);
            }
            mbar_wait(sb + B_EMPTY + 8 * POLL_AT, 0);
            if (POLL_AT < 3) POLL();
            mbar_spin(sb + B_EMPTY + 8 * RS(0), 0);
            if (POLL_D) { const uint32_t t4 = (uint32_t)clock64(); while ((uint32_t)clock64() - t4 < POLL_D) {} }
            uint32_t t5 = 0;
#pragma unroll
            for (int i = 0; i < 4; i++) {
                while (!((seen >> (2 + i)) & 1u)) POLL();
                if (BGAP && i) while ((uint32_t)clock64() - t5 < BGAP) {}
                t5 = (uint32_t)clock64();
                if (i >= 1) mbar_spin(sb + B_EMPTY + 8 * RS(i), 0);
                load_b(sb + 16384 + rank * 8192 + RS(i) * REGION, &p.mAB, rows[i], sb + B_BL + 8 * RS(i));
                PROF(160 + RS(i));
            }
            mbar_wait(sb + B_FULL + 8 * OLS, 0);
            if (!TT) mbar_arrive_elect(sb + B_SEEN);
            PROF(7);
            unsigned char* gdst = p.s->ab + (blk * 32 + own + 16) * 16384;
            uint32_t t3 = (uint32_t)clock64() + OL_T0;
#pragma unroll 1
            for (int i = 0; i < 8; i++) {
                while ((int)((uint32_t)clock64() - t3) < 0) { if (LOWP) __nanosleep(64); }
                t3 += OL_DT;
                bulk_store_elect<2048>(gdst + i * 2048, sb + 6 * REGION + i * 2048);
                if (TT && i == 1) {
                    uint2 z;
                    do z = ld_relaxed2(p.s->sync + gpc * 32 + (lane & 15) * 2); while (__any_sync(0xffffffffu, z.x != want));
                    const uint32_t mine = __shfl_sync(0xffffffffu, z.y, cta & 15);
                    const uint32_t d = z.y - mine;
                    const uint32_t m = __reduce_max_sync(0xffffffffu, d < 1500u ? d : 0u);
                    if (lane == 0) *(volatile uint32_t*)(smem + M_T0) = mine + m - TOFF;
                    __syncwarp();
                    mbar_arrive_elect(sb + B_SEEN);
                }
            }
            bulk_wait_read();
            if (LATEH) st_relaxed_if(p.s->hint + (blk * 8 + (own >> 1)) * 32 + 4 + rank, want, lane == 0);
            mbar_arrive_n_elect<4>(sb + B_FREE + 8);
            PROF(8);
            if (LATEH) {
                if (LATEH > 1) __nanosleep(LATEH);
                wait_counters<100>(hp + 4 - (el & 1), want);
            }
            mbar_arrive_elect(sb + B_SEEN + 8);
            PROF(9);
            mbar_wait(sb + B_PUBI, 0);
            PROF(29);
            if (lane == 0) {
                if (TRED) fence_proxy_async_gmem();
                red_release_add(p.s->ready + blk * 32, 1);
            }
            __syncwarp();
            PROF(30);
            if (INITH) __nanosleep(INITH);
            wait_counters<INITS>(p.s->ready + (lane & 7) * 32, want * 16u);
            mbar_arrive_elect(sb + B_INIT);
            PROF(10);
        } else {
            mbar_arrive_elect(sb + B_BL + 8 * OLS * (warp & 1));
            if (PE && warp == 2) {
                mbar_arrive_elect(sb + B_BL + 8);
                mbar_expect_tx_elect(sb + B_FULL + 8, 16384);
                mbar_arrive_n_elect<3>(sb + B_FULL + 8);
            }
            if (PFA_T && warp == 3) {
                const int e = tile_of_step(PFA_S + tn, own, KROT);
                while ((uint32_t)clock64() - tstart < PFA_T) __nanosleep(20);
                if (lane == 0) tma2d_prefetch(&p.mCre + comp, e * 64, own * 128);
                __syncwarp();
            }
            uint32_t k = 12;
            if (PFD && warp == 3) k = 0;
#define PREFETCH_W() {                                                                                        \
                const char* src = (k >= 8 ? (const char*)p.wd + ((cta >> 5) * 2 + (k >> 1) - 4) * 229376       \
                                          : (const char*)((cta & 32) ? p.wu : p.wg) + ((cta >> 6) * 4 + (k >> 1)) * 229376) + ((cta & 31) * 2 + (k & 1)) * 3584; \
                asm volatile("{.reg .pred p; elect.sync _|p, 0xffffffff; @p cp.async.bulk.prefetch.L2.global [%0], 3584;}" ::"l"(src) : "memory"); \
                k++; }
#pragma unroll 1
            while (k < PF_N0) {
                while ((uint32_t)clock64() - tstart < PF_T0 + k * (PF_DT / 2)) __nanosleep(50);
                __syncwarp();
                PREFETCH_W();
            }
            mbar_wait(sb + B_EPOCH, 0);
            const uint32_t par = (*(volatile uint32_t*)(smem + M_EPOCH) + 1u) & 1u;
            const uint32_t a0 = sb + 16384 + (lane >> 3) * 1028 + ((lane >> 2) & 1) * 144 + (lane & 3) * 32;
            const int tab = (blk * 32 + tile_of_step(lane, own, KROT)) * 128;
            const uint32_t retry = sb + B_RETRY + (warp & 1) * 240;
            uint32_t slot = PE ? 6 - warp : OLS == 1 ? warp : OLS == 2 ? 10 - 3 * warp : 4 - warp, ph = 0, rph = 0;
            uint32_t j = ffn ? warp & 1 : 12;
#pragma unroll 1
            for (int step = slot; step < 32 || j < 12; step += 2) {
                if (step < 32 && (OLS < 3 || step != OLS)) {
                    const uint32_t a = a0 + slot * REGION, bar = sb + 8 * slot;
                    mbar_wait(bar + B_BL, ph);
                    PROF(192 + step);
#pragma unroll 1
                    while (__any_sync(0xffffffffu, stale_tags(a, par) & 1u)) {
                        const int row = __shfl_sync(0xffffffffu, tab, step);
                        mbar_expect_tx_elect(retry, 16384);
                        tma2d_elect(sb + slot * REGION + 16384, &p.mAB, 0, row, retry);
                        tma2d_elect(sb + slot * REGION + 24576, &p.mAB, 0, row + 64, retry);
                        mbar_spin(retry, rph);
                        rph ^= 1u;
                    }
                    mbar_arrive_n_elect<4>(bar + B_FULL);
                    PROF(128 + step);
                }
                if (j < 12 && step >= FFN_S0 + j * FW0 / 4 && __any_sync(0xffffffffu, mbar_test(sb + B_FREE + 2 * (j & 12), 0))) {
                    const uint32_t fb = sb + B_FFN + 4 * (j & 6);
                    if (!(j & 1)) mbar_expect_tx_elect(fb, 8192);
                    tma2d_elect(sb + 6 * REGION + ((j + 4) & 7) * 4096, j < 8 ? &p.mWg + (j & 1) : &p.mWd, j < 8 ? fp * 32 : rank * 256,
                                j < 8 ? rank * 256 + (j >> 1) * 64 : fp * 32 + j * 8 - 64, fb);
                    j += 2;
                }
                if (k < 12) PREFETCH_W();
                if (PFL && step == PFL) {
                    const int e = tile_of_step(28 + tn, own, KROT);
                    if (lane == 0) tma2d_prefetch(&p.mCre + comp, e * 64, own * 128);
                    __syncwarp();
                }
                slot += 2;
                if (slot >= NSTAGE) { slot -= NSTAGE; ph ^= 1; }
            }
        }
    } else if (warp < 8) {
        const int t = tid - 128, w = warp - 4;
        if (t == 0) {
            *(volatile uint32_t*)(smem + M_EPOCH) = epoch;
            *(volatile unsigned int*)&p.s->epoch[cta] = epoch + 1;
            mbar_arrive(sb + B_EPOCH);
        }
        const uint4 gw0 = ldg_nc_off<0>(p.gate_w + lane * 8), gw1 = ldg_nc_off<512>(p.gate_w + lane * 8);
        const uint4 rw0 = ldg_nc_off<0>(p.w_r + lane * 8), rw1 = ldg_nc_off<512>(p.w_r + lane * 8);
        mbar_wait(sb + B_EPOCH, 0);
        const uint32_t par = (*(volatile uint32_t*)(smem + M_EPOCH) + 1u) & 1u;
        mbar_wait(sb + B_F + 8 * ROUTER_C, 0);
        const int row0 = cta * 16 + w * 4;
        uint4 xr[8];
        {
            const char* xp = (const char*)p.x + (uint32_t)row0 * (D_ * 2) + lane * 16;
            const uint32_t t6 = (uint32_t)clock64();
#define RWAIT(n) if (RDT) while ((uint32_t)clock64() - t6 < (n) * RDT) __nanosleep(40)
            xr[0] = ldg_nc_off<0>(xp);    xr[1] = ldg_nc_off<512>(xp);  RWAIT(1); xr[2] = ldg_nc_off<1024>(xp); xr[3] = ldg_nc_off<1536>(xp); RWAIT(2);
            xr[4] = ldg_nc_off<2048>(xp); xr[5] = ldg_nc_off<2560>(xp); RWAIT(3); xr[6] = ldg_nc_off<3072>(xp); xr[7] = ldg_nc_off<3584>(xp);
            float a[8];
#pragma unroll
            for (int i = 0; i < 4; i++) {
                const uint32_t xv[8] = {xr[2 * i].x, xr[2 * i].y, xr[2 * i].z, xr[2 * i].w, xr[2 * i + 1].x, xr[2 * i + 1].y, xr[2 * i + 1].z, xr[2 * i + 1].w};
                const uint32_t gv[8] = {gw0.x, gw0.y, gw0.z, gw0.w, gw1.x, gw1.y, gw1.z, gw1.w};
                const uint32_t rv[8] = {rw0.x, rw0.y, rw0.z, rw0.w, rw1.x, rw1.y, rw1.z, rw1.w};
                float u = 0.f, v = 0.f;
#pragma unroll
                for (int j = 0; j < 8; j++) {
                    const uint32_t pr = hmul2_bf16(xv[j], gv[j]);
                    u += bflo(pr); u += bfhi(pr);
                    v = fmaf(bflo(xv[j]), bflo(rv[j]), v); v = fmaf(bfhi(xv[j]), bfhi(rv[j]), v);
                }
                a[i] = u; a[4 + i] = v;
            }
            if (RSPLIT && ROUTER_C < 16) mbar_wait(sb + B_FULL + 8 * (RSPLIT - 1), 0);
            halve<4, 16>(a); halve<2, 8>(a); halve<1, 4>(a);
            a[0] += __shfl_xor_sync(0xffffffffu, a[0], 1);
            a[0] += __shfl_xor_sync(0xffffffffu, a[0], 2);
            const int row = row0 + ((lane >> 2) & 3);
            const float gate = rbf(sigmoidf_(rbf(a[0])));
            if (lane < 16 && (lane & 3) == 0) st_relaxed(&p.s->gate[row], tagf(gate, par));
            const uint32_t best = __reduce_max_sync(0xffffffffu, lane >= 16 ? router_key(a[0], row) : 0u);
            if (lane == 0) *(volatile uint32_t*)(smem + M_RED + w * 4) = best;
            named_bar(1, 128);
            if (t < 8) {
                const uint4 k = *(const uint4*)(smem + M_RED);
                st_key(&p.s->keys[t * NCTA + cta], max(max(k.x, k.y), max(k.z, k.w)) | (par << 15));
            }
            PROFIF(11, t == 0);
            const uint32_t og = pack_bf16(1.f - gate, 1.f - gate);
#pragma unroll
            for (int i = 0; i < 8; i++) {
                const uint32_t o = __shfl_sync(0xffffffffu, og, 4 * (i >> 1));
                xr[i] = make_uint4(hmul2_bf16(o, xr[i].x), hmul2_bf16(o, xr[i].y), hmul2_bf16(o, xr[i].z), hmul2_bf16(o, xr[i].w));
            }
        }
        if (ROUTER_C < 16) mbar_wait(sb + B_FULL + 8 * OLS, 0);
        else __nanosleep(KEYS_NS);
        if (w == 0) {
            const uint4 k4 = wait_tags(p.s->keys + gpc * NCTA + lane * 4, 15, par);
            const uint32_t k = __reduce_max_sync(0xffffffffu, max(max(k4.x, k4.y), max(k4.z, k4.w)));
            sts128(sb + M_UPD + lane * 16, ldg_nc_off<0>(p.x + (0x7fff - (k & 0x7fffu)) * D_ + rank * 256 + lane * 8));
        } else if (w == 1) {
            const uint4 g4 = wait_tags(p.s->gate + own * 128 + lane * 4, 0, par);
            *(uint4*)(smem + M_G + lane * 16) = make_uint4(g4.x & ~1u, g4.y & ~1u, g4.z & ~1u, g4.w & ~1u);
            mbar_arrive_warp(sb + B_GATE);
        }
        named_bar(1, 128);
        PROFIF(13, t == 0);
        char* op = (char*)p.out + (uint32_t)row0 * (D_ * 2) + lane * 16;
        float a[16];
#pragma unroll
        for (int i = 0; i < 16; i++) a[i] = 0.f;
#pragma unroll 1
        for (int i = 0; i < 4; i++) {
            if (i >= 2) {
                mbar_wait(sb + B_FREE + 8, 0);
                const uint32_t t2 = (uint32_t)clock64();
#pragma unroll
                for (int j = 0; j < 4; j++) {
                    while ((uint32_t)clock64() - t2 < j * INIT_DT) __nanosleep(50);
                    *(uint4*)(op + j * 512) = xr[j];
                    xr[j] = xr[j + 4];
                }
                op += 2048;
                if (i == 3) mbar_arrive_warp(sb + B_PUBI);
            }
            if (ffn) {
                const float xs0 = __bfloat162float(((const bf16*)(smem + M_UPD))[64 * i + (t >> 2)]);
                const float xs1 = __bfloat162float(((const bf16*)(smem + M_UPD))[64 * i + 32 + (t >> 2)]);
                const uint32_t wa = sb + 6 * REGION + (i ^ 2) * 8192 + t * 16;
                mbar_wait(sb + B_FFN + 8 * i, 0);
                const uint4 v0 = lds128(wa), v1 = lds128(wa + 4096), v2 = lds128(wa + 2048), v3 = lds128(wa + 6144);
                const uint32_t w0[8] = {v0.x, v0.y, v0.z, v0.w, v1.x, v1.y, v1.z, v1.w};
                const uint32_t w1[8] = {v2.x, v2.y, v2.z, v2.w, v3.x, v3.y, v3.z, v3.w};
#pragma unroll
                for (int k = 0; k < 8; k++) {
                    a[2 * k] = fmaf(xs1, bflo(w1[k]), fmaf(xs0, bflo(w0[k]), a[2 * k]));
                    a[2 * k + 1] = fmaf(xs1, bfhi(w1[k]), fmaf(xs0, bfhi(w0[k]), a[2 * k + 1]));
                }
                if (i == 1) {
                    named_bar(1, 128);
                    mbar_arrive_if(sb + B_VD, t == 0);
                }
            }
        }
        if (!ffn) return;
        PROFIF(14, t == 0);
        {
            halve<8, 16>(a); halve<4, 8>(a); halve<2, 4>(a);
            const uint32_t ho = (lane >> 4) * 128 + (lane & 3) * 32 + ((lane >> 2) & 3) * 8;
            asm volatile("barrier.cluster.wait.acquire.aligned;" ::: "memory");
#pragma unroll
            for (int k = 0; k < 2; k++)
                asm volatile("st.async.weak.shared::cluster.mbarrier::complete_tx::bytes.v2.f32 [%0], {%1,%2}, [%3];"
                             ::"r"(mapa(sb + (k ? 6 * REGION + w * 512 : M_HX + w * 256) + ho, rank ^ k ^ 1)), "f"(a[0]), "f"(a[1]),
                               "r"(mapa(sb + B_HX, rank ^ k ^ 1)) : "memory");
            mbar_wait_cluster(sb + B_HX, 0);
            const float *hx = (const float*)(smem + M_HX) + lane, *hy = (const float*)(smem + 6 * REGION) + lane;
            const float gs = rbf(((hx[0] + hy[0]) + (hx[64] + hy[128])) + ((hx[128] + hy[256]) + (hx[192] + hy[384])));
            const float us = rbf(((hx[32] + hy[32]) + (hx[96] + hy[160])) + ((hx[160] + hy[288]) + (hx[224] + hy[416])));
            float* hrow = (float*)(smem + 6 * REGION + 256) + w * 128;
            hrow[lane] = rbf(rbf(gs * sigmoidf_(gs)) * us);
            __syncwarp();
            PROFIF(12, t == 0);
            float o0 = 0.f, o1 = 0.f;
#pragma unroll 1
            for (int i = 0; i < 2; i++) {
                float4 hv[4];
                uint32_t vd[16];
#pragma unroll
                for (int k = 0; k < 4; k++) hv[k] = *(const float4*)&hrow[i * 16 + k * 4];
                mbar_wait(sb + B_FFN + 8 * i, 1);
#pragma unroll
                for (int k = 0; k < 16; k++) vd[k] = *(const volatile uint32_t*)(smem + 6 * REGION + 16384 + i * 8192 + k * 512 + t * 4);
#pragma unroll
                for (int k = 0; k < 4; k++) {
                    o0 = fmaf(hv[k].x, bflo(vd[4 * k]), o0);     o1 = fmaf(hv[k].x, bfhi(vd[4 * k]), o1);
                    o0 = fmaf(hv[k].y, bflo(vd[4 * k + 1]), o0); o1 = fmaf(hv[k].y, bfhi(vd[4 * k + 1]), o1);
                    o0 = fmaf(hv[k].z, bflo(vd[4 * k + 2]), o0); o1 = fmaf(hv[k].z, bfhi(vd[4 * k + 2]), o1);
                    o0 = fmaf(hv[k].w, bflo(vd[4 * k + 3]), o0); o1 = fmaf(hv[k].w, bfhi(vd[4 * k + 3]), o1);
                }
            }
            asm volatile("st.relaxed.gpu.global.v2.u32 [%0], {%1,%2};" ::"l"(&p.s->part[fp * D_ + rank * 256 + t * 2]),
                         "r"(tagf(o0, par)), "r"(tagf(o1, par)) : "memory");
            if (lane == 0) asm volatile("red.relaxed.gpu.global.add.u32 [%0], 1;" ::"l"(p.s->phint + ((rank * 2 + (w >> 1)) * 16 + (fp >> 2)) * 8) : "memory");
            PROFIF(15, t == 0);
        }
    } else {
        const int wg = (warp >> 2) - 2, wq = warp & 3;
        const uint32_t sbd = (sb & 0x3FFFF) >> 4;
        const bool lead = (tid & 127) == 0;
        const bool lead0 = lead && !wg, lead1 = lead && wg;
        const int q = lane & 3;
        float acc[64];
        const uint32_t rE = mapa(sb + B_EMPTY, rank ^ 1);
#define RELEASE(n, slot, pred) release_pair<n>(sb + B_EMPTY + 8 * (slot), rE + 8 * (slot), pred)
        const uint32_t img = sb + 6 * REGION + (wg ? 0 : 16384) + wq * 4096;
        const uint32_t sdst = pin(img + (lane >> 2) * 64 + ((q ^ (lane >> 3)) << 4));
        unsigned char* gdst = pin_uniform(p.s->ab + ((blk * 32 + own) * 4 + wq) * 4096);
        unsigned char* gd2 = pin(gdst + (sdst - img));
        unsigned int* hint = pin(p.s->hint + (blk * 8 + (own >> 1)) * 32 + rank * 2 + lane);
#define HINT(pred) red_inc_if(hint, (pred) && (!NARROW || (ORD ? !(own & 2) : own < 6)) && lane == 0)
        uint32_t e1 = 0;
        asm volatile("barrier.cluster.wait.acquire.aligned;" ::: "memory");
        if (wg) {
            if (NOFW) {
                mbar_spin(sb + B_EPOCH, 0);
                e1 = *(volatile uint32_t*)(smem + M_EPOCH) + 1u;
            }
            if (FILL) { mbar_spin(sb + B_F, 0); mbar_spin(sb + B_FILL, 0); }
            else mbar_spin(sb + B_G0, 0);
            PROFIF(20, lead);
            if (!FILL) mbar_spin(sb + B_GO1, 0);
        }
#pragma unroll
        for (int c = RS1 ? 2 : 0; c < 8; c++) {
            if (!NOFW || !wg || c == 2 || c == 4) mbar_spin(sb + (c == 4 && wg ? B_G1 : c == 2 && wg ? B_G2 : PAUSE && c == 1 && wg ? B_XE : B_F + 8 * c), PAUSE && c == 1 && wg);
            if (FILL && c == 1 && wg) { mbar_spin(sb + B_G0, 0); mbar_spin(sb + B_GO1, 0); PROFL(0); }
            if (c == 0) { PROFIF(16 + 5 * wg, lead); PROFL(0); }
            wg_fence();
#pragma unroll
            for (int kk = 0; kk < 4; kk++) {
                wgmma128<0>(acc, desc_lo(sbd + 0x10000 + (wg ? off_xl(c) : off_xe(c)) / 16 + 2 * kk), desc_lo(sbd + 0x10000 + off_d(c) / 16 + 2 * kk), (c | kk) != 0);
                if (c == 7 && kk == GOK - 1) wg_commit();
            }
            wg_commit();
            if (c == 3 && (!NOFW || !wg)) {
                mbar_spin(sb + B_EPOCH, 0);
                e1 = *(volatile uint32_t*)(smem + M_EPOCH) + 1u;
            }
            if (c == 7 && wg) mbar_spin(sb + B_FULL, 0);
            if (c == 7 && GO0) { wg_wait<2>(); mbar_arrive_if(sb + B_GO1, lead0); }
            if (c >= 2 && c != 3 && c != 5) wg_wait<1>();
            if (c == 2) RELEASE(2, 1, lead1);
            if (c == 4) { mbar_arrive_if(sb + B_XE, lead0); RELEASE(2, 2, lead1); RELEASE(2, 3, lead1); }
            if (c == 6 && !HINTM) st_stamp_if(hint, e1, lead0 && (ORD ? !(own & 2) : own < 6));
            if (c == 6) RELEASE(2, 4 * wg, lead);
            if (c == 7) mbar_arrive_if(sb + B_GO1 + 8 * wg, GO0 ? lead1 : lead);
        }
        const uint32_t neg = comp && !KC ? 0x80008000u : 0u, negp = neg | (e1 & 1u);
        const int rh = RSW ? wg ^ kh : wg;
        const uint32_t da0 = sbd + 0x10000 + rh * 512, db0 = sbd + 0x400000 + 1024;
#define STEP(da, db, first) wg_fence();                                                                     \
        _Pragma("unroll") for (int kk = 0; kk < 4; kk++)                                                    \
            wgmma128(acc, desc_lo((da) + kk * 2), desc64_lo((db) + kk * 256), !((first) && kk == 0));       \
        wg_commit()
#define PROFSTEP(s) PROFIF(64 + wg * 32 + (s), lead)
        const uint32_t dbe = db0 + 6 * (REGION / 16), dbl = dbe - 1024;
#define PW(i, j) pack_bf16(acc[16 * ((i) >> 1) + 2 * ((i) & 1) + 4 * (j)], acc[16 * ((i) >> 1) + 2 * ((i) & 1) + 4 * (j) + 1])
#define PT(i, j) ((j) == ((i) >> 1) ? (PW(i, j) & ~1u) ^ negp : PW(i, j) ^ neg)
#define CUT(n) if ((ECUT >> (n)) & 1) sched_cut()
#define PIECE(i) make_uint4(PT(i, 0), PT(i, 1), PT(i, 2), PT(i, 3))
        if (wg) {
            wg_wait<0>();
            fence_regs<0, 64>(acc);
            PROFIF(22, lead); PROFL(1);
            const uint32_t tl = TT ? (uint32_t)clock64() : 0;
#define STS1(i) sts128_off<(i) * 512>(sdst, PIECE(i))
            STS1(0); CUT(1); STS1(1); CUT(2); STS1(2); CUT(3); STS1(3); CUT(4); STS1(4); CUT(5); STS1(5); CUT(6); STS1(6); CUT(7); STS1(7);
            if (W1FIRST == 1) { PROFL(3); STEP(da0, dbe, true); }
            fence_proxy_async_smem();
            __syncwarp();
            mbar_arrive_if(sb + B_FULL + 8 * OLS, lane == 0);
            PROFL(2);
            if (!W1FIRST) { PROFL(3); STEP(da0, dbe, true); }
            PROFIF(23, lead);
            RELEASE(1, 5, lead);
            if (TT && lead) asm volatile("st.relaxed.gpu.global.v2.u32 [%0], {%1,%2};" ::"l"(p.s->sync + cta * 2), "r"(e1), "r"(tl) : "memory");
        } else {
            wg_wait<0>();
            fence_regs<0, 64>(acc);
            PROFIF(17, lead); PROFL(1);
            uint4 v[8];
#define STG0(i) v[i] = PIECE(i); stg_off<(i) * 512>(gd2, v[i]); if (HINTM == (i) + 1) HINT(true); if (PAUSE == (i) + 1) mbar_arrive_if(sb + B_XE, lead)
            STG0(0); CUT(1); STG0(1); CUT(2); STG0(2); CUT(3); STG0(3); CUT(4); STG0(4); CUT(5); STG0(5); CUT(6); STG0(6); CUT(7); STG0(7);
            PROFIF(48 + wq, lane == 0);
#define STS0(i) if (THR && (i) % THR == 0) mbar_spin(sb + B_EPOCH, 0); sts128_off<(i) * 512>(sdst, v[i])
            STS0(0); STS0(1); STS0(2); STS0(3); STS0(4); STS0(5); STS0(6); STS0(7);
            if (PE) mbar_spin(sb + B_EMPTY + 8, 0);
            fence_proxy_async_smem();
            __syncwarp();
            if (PE)
                asm volatile("{.reg .pred p; elect.sync _|p, 0xffffffff;"
                             " @p cp.async.bulk.shared::cluster.shared::cta.mbarrier::complete_tx::bytes [%0], [%1], 4096, [%2];}"
                             ::"r"(rE - B_EMPTY + REGION + 16384 + wq * 4096), "r"(img), "r"(rE - B_EMPTY + B_FULL + 8) : "memory");
            mbar_arrive_if(sb + B_FULL, lane == 0);
            PROFIF(19, lead); PROFL(2);
            RELEASE(1, 5, lead);
            mbar_arrive_if(sb + B_FREE, lane == 0);
            mbar_spin(sb + B_FULL, 0);
            mbar_spin(sb + B_SKEW0, 0);
            PROFSTEP(0); PROFL(3);
            STEP(da0, dbe, true);
        }
        constexpr int NU = OLS + 2;
#pragma unroll
        for (int step = 1; step < NU; step++) {
            mbar_spin(sb + B_FULL + 8 * step, 0);
            PROFSTEP(step);
            if (step < 4) PROFL(3 + step);
            STEP(da0 + step * (REGION / 16), step == OLS ? dbl : db0 + step * (REGION / 16), false);
            wg_wait<1>();
            RELEASE(1, step - 1, lead);
            if (step == 1) mbar_arrive_if(sb + B_FREE, lead);
            if (step == OLS + 1) mbar_arrive_if(sb + B_FREE + 8, lead);
            if (step == 4) PROFL(7);
        }
        int slot = NU % NSTAGE, ph = NU / NSTAGE, pslot = NU - 1;
#pragma unroll 1
        for (int step = NU; step < 26; step++) {
            mbar_wait(sb + B_FULL + 8 * slot, ph);
            PROFSTEP(step);
            STEP(da0 + slot * (REGION / 16), db0 + slot * (REGION / 16), false);
            wg_wait<1>();
            RELEASE(1, pslot, lead);
            pslot = slot;
            if (++slot == NSTAGE) { slot = 0; ph ^= 1; }
        }
        PROFL(8);
        float g0 = 0.f, g1 = 0.f;
        char* op = nullptr;
        const int r0 = rh * 64 + wq * 16 + (lane >> 2);
        const bool odd = lane & 4;
#define OUT_SETUP() mbar_wait(sb + B_GATE, 0);                                                              \
        g0 = ((const volatile float*)(smem + M_G))[r0];                                                     \
        g1 = ((const volatile float*)(smem + M_G))[r0 + 8];                                                 \
        if (KC && comp) { g0 = -g0; g1 = -g1; }                                                             \
        op = pin((char*)p.out + (uint32_t)((own * 128 + (SHUF ? r0 & ~1 : r0)) * D_ + tn * 128 + (lane & (SHUF ? 7 : 3)) * 8) * 2u)
        if (SK == 6 && wg) {
            wg_wait<0>();
        } else {
            mbar_wait(sb + B_FULL + 8 * 2, 0);
            STEP(da0 + 2 * (REGION / 16), db0 + 2 * (REGION / 16), false);
            wg_wait<1>();
            slot = 3;
        }
        RELEASE(1, 1, lead);
#pragma unroll 1
        for (int step = 24 + slot; step < 32; step++) {
            if (step == (wg ? 32 - SK : 30)) {
                OUT_SETUP();
                mbar_wait(sb + (wg ? B_TAIL : B_INIT), 0);
            }
            if (!wg || step < 32 - SK) mbar_wait(sb + B_FULL + 8 * slot, ph);
            STEP(da0 + slot * (REGION / 16), db0 + slot * (REGION / 16), false);
            if (++slot == NSTAGE) { slot = 0; ph ^= 1; }
        }
        if (!wg) {
            wg_wait<1>();
            mbar_arrive_if(sb + B_TAIL, lead);
        }
        if (!wg || TRED == 2) {
            const int sr = ((lane >> 2) & 1) * 4 + (lane >> 3);
            const uint32_t st0 = sb + rh * 8192 + wq * 2048, sa = pin(st0 + sr * 128 + ((q ^ sr) << 4));
            if (TORD) sched_cut();
            wg_wait<0>();
            fence_regs<0, 64>(acc);
            PROFIF(24 + 2 * wg, lead); PROFL(9);
#define OW(i, j) pack_bf16((((i) & 1) ? g1 : g0) * acc[16 * ((i) >> 1) + 2 * ((i) & 1) + 4 * (j)], (((i) & 1) ? g1 : g0) * acc[16 * ((i) >> 1) + 2 * ((i) & 1) + 4 * (j) + 1])
#define OSTS(i) sts128_off<((i) >> 2) * REGION + ((i) & 1) * 1024>(((i) & 2) ? sa ^ 64 : sa, make_uint4(OW(i, 0), OW(i, 1), OW(i, 2), OW(i, 3)))
#define ORED(h) fence_proxy_async_smem(); __syncwarp();                                                     \
            asm volatile("{.reg .pred p; elect.sync _|p, 0xffffffff;"                                       \
                         " @p cp.reduce.async.bulk.tensor.4d.global.shared::cta.add.tile.bulk_group [%0, {%2,%3,%3,%4}], [%1];}" \
                         ::"l"(&p.mOut), "r"(st0 + (h) * REGION), "r"(tn * 128 + (h) * 64), "r"(0), "r"(own * 16 + rh * 8 + wq * 2) : "memory")
            OSTS(0); OSTS(1); OSTS(2); OSTS(3);
            ORED(0);
            if (TORD) sched_cut();
            OSTS(4); OSTS(5); OSTS(6); OSTS(7);
            ORED(1);
            bulk_wait_read();
        } else {
        char* opb = pin(op + (odd ? 1024 - 64 : 1024 + 64));
        if (TORD) sched_cut();
        wg_wait<0>();
        fence_regs<0, 64>(acc);
        PROFIF(24 + 2 * wg, lead); PROFL(9);
        uint32_t k[4][4], r[4][4];
#define PACKLINE(i) _Pragma("unroll") for (int j = 0; j < 4; j++) {                                         \
            const int o = 32 * ((i) >> 1) + 2 * ((i) & 1) + 4 * j;                                          \
            const float g = ((i) & 1) ? g1 : g0;                                                            \
            r[i][j] = __shfl_xor_sync(0xffffffffu, pack_bf16(g * acc[o + 16], g * acc[o + 17]), 4);         \
            k[i][j] = pack_bf16(g * acc[o], g * acc[o + 1]); }
#define REDLINE(i)                                                                                          \
        red_bf16x8<((i) & 1) * 8192 + ((i) >> 1) * 128>(op, odd ? r[i][0] : k[i][0], odd ? r[i][1] : k[i][1], odd ? r[i][2] : k[i][2], odd ? r[i][3] : k[i][3]); \
        red_bf16x8<((i) & 1) * 8192 + ((i) >> 1) * 128>(opb, odd ? k[i][0] : r[i][0], odd ? k[i][1] : r[i][1], odd ? k[i][2] : r[i][2], odd ? k[i][3] : r[i][3])
        PACKLINE(0) REDLINE(0);
        if (TORD) sched_cut();
        PACKLINE(1) REDLINE(1);
        if (TORD > 1) sched_cut();
        PACKLINE(2) REDLINE(2);
        if (TORD > 2) sched_cut();
        PACKLINE(3) REDLINE(3);
        }
    }
}

typedef CUresult (*EncodeTiledFn)(CUtensorMap*, CUtensorMapDataType, cuuint32_t, void*, const cuuint64_t*, const cuuint64_t*,
                                  const cuuint32_t*, const cuuint32_t*, CUtensorMapInterleave, CUtensorMapSwizzle,
                                  CUtensorMapL2promotion, CUtensorMapFloatOOBfill);

static void make_map(EncodeTiledFn enc, CUtensorMap* m, const void* base, uint64_t cols, uint64_t rows, uint32_t box_rows,
                     CUtensorMapSwizzle sw = CU_TENSOR_MAP_SWIZZLE_128B, uint32_t box_cols = 64,
                     CUtensorMapL2promotion promo = CU_TENSOR_MAP_L2_PROMOTION_L2_128B) {
    cuuint64_t dims[2] = {cols, rows};
    cuuint64_t str[1] = {cols * 2};
    cuuint32_t box[2] = {box_cols, box_rows};
    cuuint32_t es[2] = {1, 1};
    enc(m, CU_TENSOR_MAP_DATA_TYPE_BFLOAT16, 2, (void*)base, dims, str, box, es, CU_TENSOR_MAP_INTERLEAVE_NONE,
        sw, promo, CU_TENSOR_MAP_FLOAT_OOB_FILL_NONE);
}

static void make_map_chunks(EncodeTiledFn enc, CUtensorMap* m, const void* base, uint64_t rows, uint32_t box_rows, uint32_t n = 1) {
    cuuint64_t dims[3] = {64, rows, 8};
    cuuint64_t str[2] = {D_ * 2, 128};
    cuuint32_t box[3] = {64, box_rows, n};
    cuuint32_t es[3] = {1, 1, 1};
    enc(m, CU_TENSOR_MAP_DATA_TYPE_BFLOAT16, 3, (void*)base, dims, str, box, es, CU_TENSOR_MAP_INTERLEAVE_NONE,
        CU_TENSOR_MAP_SWIZZLE_128B, CU_TENSOR_MAP_L2_PROMOTION_L2_128B, CU_TENSOR_MAP_FLOAT_OOB_FILL_NONE);
}

static void make_map_out(EncodeTiledFn enc, CUtensorMap* m, const void* base) {
    cuuint64_t dims[4] = {D_, 4, 2, S_ / 8};
    cuuint64_t str[3] = {2 * D_ * 2, D_ * 2, 8 * D_ * 2};
    cuuint32_t box[4] = {64, 4, 2, 2};
    cuuint32_t es[4] = {1, 1, 1, 1};
    enc(m, CU_TENSOR_MAP_DATA_TYPE_BFLOAT16, 4, (void*)base, dims, str, box, es, CU_TENSOR_MAP_INTERLEAVE_NONE,
        CU_TENSOR_MAP_SWIZZLE_128B, CU_TENSOR_MAP_L2_PROMOTION_NONE, CU_TENSOR_MAP_FLOAT_OOB_FILL_NONE);
}

extern "C" void kernel_launch(void* const* d_in, const int* in_sizes, int n_in, void* d_out, int out_size) {
    (void)in_sizes; (void)n_in; (void)out_size;
    static EncodeTiledFn enc = nullptr;
    static bool fused_ok = false;
    static void* ab_ptr = nullptr;
    if (!enc) {
        void* fn = nullptr;
        cudaDriverEntryPointQueryResult q;
        cudaGetDriverEntryPoint("cuTensorMapEncodeTiled", &fn, cudaEnableDefault, &q);
        enc = (EncodeTiledFn)fn;
        cudaGetSymbolAddress(&ab_ptr, g_s);
        cudaFuncSetAttribute(fused_kernel, cudaFuncAttributeMaxDynamicSharedMemorySize, SMEM_BYTES);
        int dev = 0, nsm = 0, ncl = 0;
        cudaGetDevice(&dev);
        cudaDeviceGetAttribute(&nsm, cudaDevAttrMultiProcessorCount, dev);
        cudaLaunchConfig_t cfg = {};
        cfg.gridDim = dim3(132); cfg.blockDim = dim3(NTHREADS); cfg.dynamicSmemBytes = SMEM_BYTES;
        cudaLaunchAttribute at;
        at.id = cudaLaunchAttributeClusterDimension;
        at.val.clusterDim.x = 2; at.val.clusterDim.y = 1; at.val.clusterDim.z = 1;
        cfg.attrs = &at; cfg.numAttrs = 1;
        fused_ok = cudaOccupancyMaxActiveClusters(&ncl, fused_kernel, &cfg) == cudaSuccess && nsm == 132 && ncl == 66;
        (void)cudaGetLastError();
    }
    if (!fused_ok) {
        const bf16* const* in = (const bf16* const*)d_in;
        fb_hidden<<<S_, D_, 0, cudaStreamPerThread>>>(in[0], in[3], in[4], in[10], in[6]);
        fb_ffn1<<<F_ / 128, 128, 0, cudaStreamPerThread>>>(in[0], in[7], in[8]);
        fb_ffn2<<<D_ / 64, 64, 0, cudaStreamPerThread>>>(in[9]);
        fb_seq<<<S_, D_, 0, cudaStreamPerThread>>>(in[0], in[1], in[2], (bf16*)d_out);
        return;
    }
    Params p;
    p.s = (Scratch*)ab_ptr;
    p.x = (const bf16*)d_in[0];
    p.w_r = (const bf16*)d_in[6];
    p.wg = (const bf16*)d_in[7];
    p.wu = (const bf16*)d_in[8];
    p.wd = (const bf16*)d_in[9];
    p.gate_w = (const bf16*)d_in[10];
    p.out = (bf16*)d_out;
    make_map_chunks(enc, &p.mX1, d_in[0], S_, 64);
    make_map_chunks(enc, &p.mX2, d_in[0], S_, 64, 2);
    make_map(enc, &p.mCre, d_in[1], S_, S_, 128);
    make_map(enc, &p.mCim, d_in[2], S_, S_, 128);
    make_map_chunks(enc, &p.mDre, d_in[3], D_, 128);
    make_map_chunks(enc, &p.mDim, d_in[4], D_, 128);
    make_map(enc, &p.mAB, ab_ptr, 64, 8 * 32 * 128, 64, CU_TENSOR_MAP_SWIZZLE_NONE);
    make_map_out(enc, &p.mOut, d_out);
    make_map(enc, &p.mWg, d_in[7], F_, D_, 64, CU_TENSOR_MAP_SWIZZLE_NONE, 32, WPROMO);
    make_map(enc, &p.mWu, d_in[8], F_, D_, 64, CU_TENSOR_MAP_SWIZZLE_NONE, 32, WPROMO);
    make_map(enc, &p.mWd, d_in[9], D_, F_, 8, CU_TENSOR_MAP_SWIZZLE_NONE, 256);
    fused_kernel<<<132, NTHREADS, SMEM_BYTES, cudaStreamPerThread>>>(p);
}
```

```cpp
#include <cuda_runtime.h>
#include <cuda.h>
#include <cuda_bf16.h>
#include <stdint.h>

typedef __nv_bfloat16 bf16;

constexpr int S_ = 2048, D_ = 512, F_ = 1792;
constexpr int NCTA = 128;
constexpr int NTHREADS = 512;
constexpr int NSTAGE = 6;
constexpr int REGION = 32768;
constexpr int FFN_CTAS = F_ / 16;
constexpr uint32_t SPIN_LIMIT = 1u << 22;
constexpr int PACE = 250;
constexpr int A_GAP = 300;
constexpr int B_GAP = 350;
constexpr int LATE_GAP = 240;
constexpr int INIT_GAP = 400;
constexpr int PF_T0 = 3000;
constexpr int PF_GAP = 850;
constexpr int PF_N0 = 4;
constexpr int FFN_S0 = 4;
constexpr int FFN_W = 7;
constexpr int ROUTER_C = 4;
constexpr int HINT_AT = 5;
constexpr int SUM_T0 = 15000;
constexpr int SK = 5;

constexpr int OFF_MISC = 7 * REGION;
constexpr int B_F = OFF_MISC;
constexpr int B_G0 = B_F + 64;
constexpr int B_G4 = B_G0 + 8;
constexpr int B_XE = B_G4 + 8;
constexpr int B_GO1 = B_XE + 8;
constexpr int B_GO0 = B_GO1 + 8;
constexpr int B_EPOCH = B_GO0 + 8;
constexpr int B_RETRY = B_EPOCH + 8;
constexpr int B_INIT = B_RETRY + 8;
constexpr int B_FULL = B_INIT + 8;
constexpr int B_EMPTY = B_FULL + 48;
constexpr int B_PUB = B_EMPTY + 48;
constexpr int B_FREE = B_PUB + 8;
constexpr int B_BL = B_FREE + 24;
constexpr int B_TAIL = B_BL + 48;
constexpr int B_HX = B_TAIL + 8;
constexpr int B_FFN = B_HX + 8;
constexpr int B_ROLE = B_FFN + 40;
constexpr int B_EARLY = B_ROLE + 8;
constexpr int B_GATE = B_EARLY + 8;
constexpr int B_G2 = B_GATE + 8;
constexpr int M_EPOCH = B_G2 + 8;
constexpr int M_ROLE = M_EPOCH + 4;
constexpr int M_KEY = OFF_MISC + 416;
constexpr int M_HX = OFF_MISC + 512;
constexpr int M_G = M_HX + 1024;
constexpr int M_XS = M_G + 512;
constexpr int SMEM_BYTES = 232448;
static_assert(M_ROLE + 4 <= M_KEY && M_XS + 512 <= SMEM_BYTES, "smem");

struct Scratch {
    unsigned char ab[8 * 32 * 16384];
    unsigned int hint[8 * 4 * 32];
    unsigned int ready[8 * 32];
    unsigned int gate[S_];
    unsigned int part[FFN_CTAS / 2 * D_];
    unsigned int phint[4 * 16 * 8];
    unsigned int keys[8 * NCTA];
    unsigned int epoch[NCTA + 4];
};
__device__ __align__(1024) Scratch g_s;

struct Params {
    Scratch* s;
    bf16* out;
    const bf16 *x, *gate_w, *w_r, *wg, *wu, *wd;
    CUtensorMap mDre, mDim, mX1, mX2, mCre, mCim, mAB, mOut, mWg, mWu, mWd;
};

#define ELECT "{.reg .pred p; elect.sync _|p, 0xffffffff; @p "
__device__ __forceinline__ uint32_t smem_u32(const void* p) { return (uint32_t)__cvta_generic_to_shared(p); }
__device__ __forceinline__ uint32_t clk() { return (uint32_t)clock64(); }
__device__ __forceinline__ void spin_until(uint32_t t) { while ((int)(clk() - t) < 0) {} }
template <int NS>
__device__ __forceinline__ void sleep_until(uint32_t t) { while ((int)(clk() - t) < 0) __nanosleep(NS); }
__device__ __forceinline__ void mbar_init_elect(uint32_t bar, uint32_t cnt) {
    asm volatile(ELECT "mbarrier.init.shared::cta.b64 [%0], %1;}" ::"r"(bar), "r"(cnt) : "memory");
}
__device__ __forceinline__ void mbar_expect_tx_elect(uint32_t bar, uint32_t bytes) {
    asm volatile(ELECT "mbarrier.arrive.expect_tx.shared::cta.b64 _, [%0], %1;}" ::"r"(bar), "r"(bytes) : "memory");
}
template <int N = 1>
__device__ __forceinline__ void mbar_arrive_elect(uint32_t bar) {
    asm volatile(ELECT "mbarrier.arrive.shared::cta.b64 _, [%0], %1;}" ::"r"(bar), "n"(N) : "memory");
}
__device__ __forceinline__ void mbar_arrive_if(uint32_t bar, bool pred) {
    asm volatile("{.reg .pred p; setp.ne.b32 p, %1, 0; @p mbarrier.arrive.shared::cta.b64 _, [%0];}" ::"r"(bar), "r"((int)pred) : "memory");
}
__device__ __forceinline__ void mbar_arrive_warp(uint32_t bar) {
    __syncwarp();
    mbar_arrive_if(bar, (threadIdx.x & 31) == 0);
}
template <int N>
__device__ __forceinline__ void release_pair(uint32_t bar, uint32_t rbar, bool pred) {
    asm volatile("{.reg .pred p; setp.ne.b32 p, %2, 0; @p mbarrier.arrive.shared::cta.b64 _, [%0], %3;"
                 " @p mbarrier.arrive.shared::cluster.b64 _, [%1], %3;}" ::"r"(bar), "r"(rbar), "r"((int)pred), "n"(N) : "memory");
}
__device__ __forceinline__ uint32_t mapa(uint32_t a, uint32_t cta) {
    uint32_t r;
    asm volatile("mapa.shared::cluster.u32 %0, %1, %2;" : "=r"(r) : "r"(a), "r"(cta));
    return r;
}
__device__ __forceinline__ bool mbar_test(uint32_t bar, uint32_t parity) {
    uint32_t ok;
    asm volatile("{.reg .pred p; mbarrier.test_wait.parity.shared::cta.b64 p, [%1], %2; selp.u32 %0,1,0,p;}"
                 : "=r"(ok) : "r"(bar), "r"(parity) : "memory");
    return ok;
}
__device__ __forceinline__ void mbar_wait(uint32_t bar, uint32_t parity) {
    asm volatile("{.reg .pred p, q; .reg .u32 n; mov.u32 n, 0;\n"
                 "W%=: mbarrier.try_wait.parity.shared::cta.b64 p, [%0], %1;\n"
                 "add.u32 n, n, 1; setp.lt.and.u32 q, n, %2, !p; @q bra W%=; @!p trap;}" ::"r"(bar), "r"(parity), "n"(SPIN_LIMIT) : "memory");
}
__device__ __forceinline__ void mbar_wait_cluster(uint32_t bar, uint32_t parity) {
    asm volatile("{.reg .pred p, q; .reg .u32 n; mov.u32 n, 0;\n"
                 "W%=: mbarrier.try_wait.parity.acquire.cluster.shared::cta.b64 p, [%0], %1;\n"
                 "add.u32 n, n, 1; setp.lt.and.u32 q, n, %2, !p; @q bra W%=; @!p trap;}" ::"r"(bar), "r"(parity), "n"(SPIN_LIMIT) : "memory");
}
__device__ __forceinline__ void mbar_spin(uint32_t bar, uint32_t parity) {
    asm volatile("{.reg .pred p;\nW%=: mbarrier.try_wait.parity.shared::cta.b64 p, [%0], %1; @!p bra W%=;}" ::"r"(bar), "r"(parity) : "memory");
}
__device__ __forceinline__ void cluster_arrive() { asm volatile("barrier.cluster.arrive.relaxed.aligned;" ::: "memory"); }
__device__ __forceinline__ void cluster_wait() { asm volatile("barrier.cluster.wait.acquire.aligned;" ::: "memory"); }
__device__ __forceinline__ void side_bar() { asm volatile("bar.sync 1, 128;" ::: "memory"); }
__device__ __forceinline__ void tma2d_elect(uint32_t dst, const CUtensorMap* m, int c0, int c1, uint32_t bar) {
    asm volatile(ELECT "cp.async.bulk.tensor.2d.shared::cluster.global.mbarrier::complete_tx::bytes [%0], [%1, {%3,%4}], [%2];}"
                 ::"r"(dst), "l"(m), "r"(bar), "r"(c0), "r"(c1) : "memory");
}
__device__ __forceinline__ void tma2d_pair_elect(uint32_t dst, const CUtensorMap* m, int c0, int c1, uint32_t bar) {
    asm volatile(ELECT "cp.async.bulk.tensor.2d.shared::cluster.global.mbarrier::complete_tx::bytes.multicast::cluster"
                 " [%0], [%1, {%3,%4}], [%2], %5;}" ::"r"(dst), "l"(m), "r"(bar), "r"(c0), "r"(c1), "h"((uint16_t)3) : "memory");
}
__device__ __forceinline__ void tma3d_elect(uint32_t dst, const CUtensorMap* m, int row, int chunk, uint32_t bar) {
    asm volatile(ELECT "cp.async.bulk.tensor.3d.shared::cluster.global.mbarrier::complete_tx::bytes [%0], [%1, {%3,%4,%5}], [%2];}"
                 ::"r"(dst), "l"(m), "r"(bar), "r"(0), "r"(row), "r"(chunk) : "memory");
}
__device__ __forceinline__ void bulk_wait_read() {
    asm volatile("cp.async.bulk.commit_group; cp.async.bulk.wait_group.read 0;" ::: "memory");
    __syncwarp();
}
__device__ __forceinline__ void fence_proxy_async_smem() { asm volatile("fence.proxy.async.shared::cta;" ::: "memory"); }
__device__ __forceinline__ uint32_t ld_relaxed(const void* p) {
    uint32_t v;
    asm volatile("ld.relaxed.gpu.global.u32 %0, [%1];" : "=r"(v) : "l"(p) : "memory");
    return v;
}
__device__ __forceinline__ uint4 ld_relaxed4(const void* p) {
    uint4 v;
    asm volatile("ld.relaxed.gpu.global.v4.u32 {%0,%1,%2,%3}, [%4];" : "=r"(v.x), "=r"(v.y), "=r"(v.z), "=r"(v.w) : "l"(p) : "memory");
    return v;
}
__device__ __forceinline__ void red_inc_if(unsigned int* p, bool pred) {
    asm volatile("{.reg .pred p; setp.ne.b32 p, %1, 0; @p red.relaxed.gpu.global.add.u32 [%0], 1;}" ::"l"(p), "r"((int)pred) : "memory");
}
__device__ __forceinline__ uint32_t tagf(float v, uint32_t par) { return (__float_as_uint(v) & ~1u) | par; }
__device__ __forceinline__ uint4 wait_tags(const unsigned int* p, int bit, uint32_t par) {
    uint32_t n = 0;
    while (true) {
        const uint4 v = ld_relaxed4(p);
        const uint32_t m = par ? (v.x & v.y & v.z & v.w) : ~(v.x | v.y | v.z | v.w);
        if (__all_sync(0xffffffffu, (m >> bit) & 1u)) return v;
        __nanosleep(100);
        if (++n > SPIN_LIMIT) __trap();
    }
}
__device__ __forceinline__ void wait_counters(const unsigned int* p, uint32_t want) {
    uint32_t n = 0;
    while (!__all_sync(0xffffffffu, (int)(ld_relaxed(p) - want) >= 0)) {
        __nanosleep(200);
        if (++n > SPIN_LIMIT) __trap();
    }
    asm volatile("fence.acquire.gpu;" ::: "memory");
}
__device__ __forceinline__ uint32_t stale_tags(uint32_t a, uint32_t par) {
    uint32_t r;
    asm volatile("{.reg .b32 v<16>;\n"
                 "ld.shared.u32 v0, [%1]; ld.shared.u32 v1, [%1+256]; ld.shared.u32 v2, [%1+512]; ld.shared.u32 v3, [%1+768];\n"
                 "ld.shared.u32 v4, [%1+4096]; ld.shared.u32 v5, [%1+4352]; ld.shared.u32 v6, [%1+4608]; ld.shared.u32 v7, [%1+4864];\n"
                 "ld.shared.u32 v8, [%1+8192]; ld.shared.u32 v9, [%1+8448]; ld.shared.u32 v10, [%1+8704]; ld.shared.u32 v11, [%1+8960];\n"
                 "ld.shared.u32 v12, [%1+12288]; ld.shared.u32 v13, [%1+12544]; ld.shared.u32 v14, [%1+12800]; ld.shared.u32 v15, [%1+13056];\n"
                 "lop3.b32 v0, v0, v1, %2, 0x7e; lop3.b32 v2, v2, v3, %2, 0x7e; lop3.b32 v4, v4, v5, %2, 0x7e; lop3.b32 v6, v6, v7, %2, 0x7e;\n"
                 "lop3.b32 v8, v8, v9, %2, 0x7e; lop3.b32 v10, v10, v11, %2, 0x7e; lop3.b32 v12, v12, v13, %2, 0x7e; lop3.b32 v14, v14, v15, %2, 0x7e;\n"
                 "lop3.b32 v0, v0, v2, v4, 0xfe; lop3.b32 v6, v6, v8, v10, 0xfe; lop3.b32 v0, v0, v6, v12, 0xfe; or.b32 %0, v0, v14;}"
                 : "=r"(r) : "r"(a), "r"(par) : "memory");
    return r;
}
template <int OFF>
__device__ __forceinline__ uint4 ldg_nc(const void* p) {
    uint4 v;
    asm volatile("ld.global.nc.v4.u32 {%0,%1,%2,%3}, [%4+%5];" : "=r"(v.x), "=r"(v.y), "=r"(v.z), "=r"(v.w) : "l"(p), "n"(OFF));
    return v;
}
template <int OFF>
__device__ __forceinline__ void stg128(void* p, const uint4& v) {
    asm volatile("st.global.v4.u32 [%0+%5], {%1,%2,%3,%4};" ::"l"(p), "r"(v.x), "r"(v.y), "r"(v.z), "r"(v.w), "n"(OFF) : "memory");
}
template <int OFF>
__device__ __forceinline__ void sts128(uint32_t a, const uint4& v) {
    asm volatile("st.shared.v4.u32 [%0+%5], {%1,%2,%3,%4};" ::"r"(a), "r"(v.x), "r"(v.y), "r"(v.z), "r"(v.w), "n"(OFF) : "memory");
}
__device__ __forceinline__ uint4 lds128(uint32_t a) {
    uint4 v;
    asm volatile("ld.shared.v4.u32 {%0,%1,%2,%3}, [%4];" : "=r"(v.x), "=r"(v.y), "=r"(v.z), "=r"(v.w) : "r"(a) : "memory");
    return v;
}
template <int OFF>
__device__ __forceinline__ void red_bf16x8(void* p, uint32_t x, uint32_t y, uint32_t z, uint32_t w) {
    asm volatile("red.relaxed.gpu.global.add.noftz.v4.bf16x2 [%0+%5], {%1,%2,%3,%4};"
                 ::"l"(p), "r"(x), "r"(y), "r"(z), "r"(w), "n"(OFF) : "memory");
}
__device__ __forceinline__ void sched_cut() {
    asm volatile("{.reg .pred p; .reg .u64 t; .reg .u32 a, b;\n"
                 "C%=: mov.u64 t, %%clock64; mov.b64 {a, b}, t; setp.eq.u32 p, a, %0; @p bra C%=;}" ::"n"(0) : "memory");
}
__device__ __forceinline__ uint32_t pin(uint32_t v) { return __shfl_xor_sync(0xffffffffu, v, 0); }
template <class T>
__device__ __forceinline__ T* pin(T* p) { return (T*)__shfl_xor_sync(0xffffffffu, (unsigned long long)p, 0); }
__device__ __forceinline__ float selpf(float a, float b, bool p) {
    float r;
    asm("{.reg .pred q; setp.ne.b32 q, %3, 0; selp.f32 %0, %1, %2, q;}" : "=f"(r) : "f"(a), "f"(b), "r"((int)p));
    return r;
}
template <int N, int MASK, int SZ>
__device__ __forceinline__ void halve(float (&a)[SZ]) {
    const bool up = threadIdx.x & MASK;
#pragma unroll
    for (int j = 0; j < N; j++) a[j] = selpf(a[N + j], a[j], up) + __shfl_xor_sync(0xffffffffu, selpf(a[j], a[N + j], up), MASK);
}
__device__ __forceinline__ float bflo(uint32_t u) { return __uint_as_float(u << 16); }
__device__ __forceinline__ float bfhi(uint32_t u) { return __uint_as_float(u & 0xffff0000u); }
__device__ __forceinline__ uint32_t pack_bf16(float lo, float hi) {
    uint32_t r;
    asm("cvt.rn.bf16x2.f32 %0, %1, %2;" : "=r"(r) : "f"(hi), "f"(lo));
    return r;
}
__device__ __forceinline__ uint32_t hmul2_bf16(uint32_t a, uint32_t b) {
    uint32_t r;
    asm("mul.rn.bf16x2 %0, %1, %2;" : "=r"(r) : "r"(a), "r"(b));
    return r;
}
__device__ __forceinline__ float rbf(float v) { return bflo(pack_bf16(v, 0.f)); }
__device__ __forceinline__ float sigmoidf_(float v) { return __frcp_rn(1.0f + __expf(-v)); }

__device__ __forceinline__ void wg_fence() { asm volatile("wgmma.fence.sync.aligned;" ::: "memory"); }
__device__ __forceinline__ void wg_commit() { asm volatile("wgmma.commit_group.sync.aligned;" ::: "memory"); }
template <int N> __device__ __forceinline__ void wg_wait() { asm volatile("wgmma.wait_group.sync.aligned %0;" ::"n"(N) : "memory"); }
__device__ __forceinline__ uint64_t desc128(uint32_t lo) { return (uint64_t)lo | (0x40000040ull << 32); }
__device__ __forceinline__ uint64_t desc64(uint32_t lo) { return (uint64_t)lo | (0x80000020ull << 32); }
__device__ __forceinline__ void fence_regs(float (&d)[64]) {
#pragma unroll
    for (int i = 0; i < 64; i++) asm volatile("" : "+f"(d[i])::"memory");
}
template <int TB>
__device__ __forceinline__ void wgmma128(float (&d)[64], uint64_t da, uint64_t db, int scaleD) {
    asm volatile(
        "{ .reg .pred p; setp.ne.b32 p, %66, 0;\n"
        "wgmma.mma_async.sync.aligned.m64n128k16.f32.bf16.bf16 "
        "{%0,%1,%2,%3,%4,%5,%6,%7,%8,%9,%10,%11,%12,%13,%14,%15,%16,%17,%18,%19,%20,%21,%22,%23,%24,%25,%26,%27,%28,%29,%30,%31,"
        "%32,%33,%34,%35,%36,%37,%38,%39,%40,%41,%42,%43,%44,%45,%46,%47,%48,%49,%50,%51,%52,%53,%54,%55,%56,%57,%58,%59,%60,%61,%62,%63}, "
        "%64, %65, p, 1, 1, 0, %67;\n}"
        : "+f"(d[0]), "+f"(d[1]), "+f"(d[2]), "+f"(d[3]), "+f"(d[4]), "+f"(d[5]), "+f"(d[6]), "+f"(d[7]),
          "+f"(d[8]), "+f"(d[9]), "+f"(d[10]), "+f"(d[11]), "+f"(d[12]), "+f"(d[13]), "+f"(d[14]), "+f"(d[15]),
          "+f"(d[16]), "+f"(d[17]), "+f"(d[18]), "+f"(d[19]), "+f"(d[20]), "+f"(d[21]), "+f"(d[22]), "+f"(d[23]),
          "+f"(d[24]), "+f"(d[25]), "+f"(d[26]), "+f"(d[27]), "+f"(d[28]), "+f"(d[29]), "+f"(d[30]), "+f"(d[31]),
          "+f"(d[32]), "+f"(d[33]), "+f"(d[34]), "+f"(d[35]), "+f"(d[36]), "+f"(d[37]), "+f"(d[38]), "+f"(d[39]),
          "+f"(d[40]), "+f"(d[41]), "+f"(d[42]), "+f"(d[43]), "+f"(d[44]), "+f"(d[45]), "+f"(d[46]), "+f"(d[47]),
          "+f"(d[48]), "+f"(d[49]), "+f"(d[50]), "+f"(d[51]), "+f"(d[52]), "+f"(d[53]), "+f"(d[54]), "+f"(d[55]),
          "+f"(d[56]), "+f"(d[57]), "+f"(d[58]), "+f"(d[59]), "+f"(d[60]), "+f"(d[61]), "+f"(d[62]), "+f"(d[63])
        : "l"(da), "l"(db), "r"(scaleD), "n"(TB));
}

__device__ __forceinline__ uint32_t get_role(uint32_t& smid) {
    uint32_t role;
    asm volatile("mov.u32 %0, %%smid;" : "=r"(smid));
    asm("{.reg .pred p, q; .reg .u32 t, a, b; shr.u32 t, %1, 1; mad.lo.u32 a, t, 293, -928; shr.u32 a, a, 8; mad.lo.u32 b, t, 8, -464;"
        " setp.lt.u32 p, t, 32; setp.lt.u32 q, t, 62; selp.u32 a, a, b, q; selp.u32 %0, t, a, p;}" : "=r"(role) : "r"(smid));
    return role;
}
__device__ __forceinline__ int tile_of_step(int step, int own) {
    const int u = step >= 17 ? step - 17 : step - 2;
    int e = u + (u >= (own & 14) ? 2 : 0);
    if (u == 14) e = own ^ 1;
    if (step < 2) e = own;
    return e + (step >= 17 || step == 1 ? 16 : 0);
}
__device__ __forceinline__ uint32_t router_key(float score, int row) {
    const float r = score + 0.0f;
    uint32_t u = pack_bf16(r, 0.f) & 0xffffu;
    u = (u & 0x8000u) ? (~u & 0xffffu) : (u | 0x8000u);
    if (r != r) u = 0;
    return (u << 16) | (uint32_t)(0x7fff - row);
}

#define g_fb_h ((float*)g_s.part)
#define g_fb_upd (g_fb_h + 2048)
#define g_fb_gate (g_fb_h + 4096)
#define g_fb_keys (g_s.part + 8192)
__global__ void fb_hidden(const bf16* x, const bf16* dre, const bf16* dim, const bf16* gw, const bf16* wr) {
    __shared__ float xs[D_];
    const int s = blockIdx.x, t = threadIdx.x;
    xs[t] = __bfloat162float(x[s * D_ + t]);
    __syncthreads();
    float a = 0.f, b = 0.f;
    for (int d = 0; d < D_; d++) { a = fmaf(xs[d], __bfloat162float(dre[t * D_ + d]), a); b = fmaf(xs[d], __bfloat162float(dim[t * D_ + d]), b); }
    ((bf16*)g_s.ab)[s * 1024 + t] = __float2bfloat16(a);
    ((bf16*)g_s.ab)[s * 1024 + 512 + t] = __float2bfloat16(b);
    if (t == 0) {
        float u = 0.f, v = 0.f;
        for (int d = 0; d < D_; d++) { u = fmaf(xs[d], __bfloat162float(gw[d]), u); v = fmaf(xs[d], __bfloat162float(wr[d]), v); }
        g_fb_gate[s] = sigmoidf_(u);
        g_fb_keys[s] = router_key(v, s);
    }
}
__device__ uint32_t fb_best() {
    uint32_t k = 0;
    for (int i = 0; i < S_; i++) k = max(k, g_fb_keys[i]);
    return k;
}
__global__ void fb_ffn1(const bf16* x, const bf16* wg, const bf16* wu) {
    const int f = blockIdx.x * blockDim.x + threadIdx.x, idx = 0x7fff - (int)(fb_best() & 0x7fffu);
    float a = 0.f, b = 0.f;
    for (int d = 0; d < D_; d++) {
        const float xv = __bfloat162float(x[idx * D_ + d]);
        a = fmaf(xv, __bfloat162float(wg[d * F_ + f]), a); b = fmaf(xv, __bfloat162float(wu[d * F_ + f]), b);
    }
    g_fb_h[f] = a * sigmoidf_(a) * b;
}
__global__ void fb_ffn2(const bf16* wd) {
    const int e = blockIdx.x * blockDim.x + threadIdx.x;
    const uint32_t u = fb_best() >> 16, rb = (u & 0x8000u) ? (u & 0x7fffu) : (~u & 0xffffu);
    float a = 0.f;
    for (int f = 0; f < F_; f++) a = fmaf(g_fb_h[f], __bfloat162float(wd[f * D_ + e]), a);
    g_fb_upd[e] = a * sigmoidf_(__uint_as_float(rb << 16));
}
__global__ void fb_seq(const bf16* x, const bf16* cre, const bf16* cim, bf16* out) {
    __shared__ float c[2][S_];
    __shared__ int idx;
    const int t = blockIdx.x, e = threadIdx.x;
    for (int i = e; i < S_; i += D_) { c[0][i] = __bfloat162float(cre[t * S_ + i]); c[1][i] = __bfloat162float(cim[t * S_ + i]); }
    if (e == 0) idx = 0x7fff - (int)(fb_best() & 0x7fffu);
    __syncthreads();
    float y = 0.f;
    for (int s = 0; s < S_; s++)
        y += c[0][s] * __bfloat162float(((const bf16*)g_s.ab)[s * 1024 + e]) - c[1][s] * __bfloat162float(((const bf16*)g_s.ab)[s * 1024 + 512 + e]);
    const float g = g_fb_gate[t];
    out[t * D_ + e] = __float2bfloat16(g * y + (1.f - g) * (__bfloat162float(x[t * D_ + e]) + (t == idx ? g_fb_upd[e] : 0.f)));
}

__device__ __forceinline__ void spare_job(const Params& p, unsigned char* smem, int sp, uint32_t tstart) {
    const int tid = threadIdx.x, warp = tid >> 5, lane = tid & 31;
    const uint32_t e1 = *(volatile unsigned int*)&p.s->epoch[NCTA + sp] + 1u;
    const uint32_t par = e1 & 1u;
    uint32_t* sel = (uint32_t*)smem;
    float* acc = (float*)(smem + 1024);
    __syncthreads();
    if (tid == 0) *(volatile unsigned int*)&p.s->epoch[NCTA + sp] = e1;
    sleep_until<500>(tstart + SUM_T0);
    if (warp < 14) {
        uint32_t n = 0;
        while ((int)(ld_relaxed(p.s->phint + (sp * 16 + warp) * 8) - e1 * 8u) < 0) {
            __nanosleep(100);
            if (++n > SPIN_LIMIT) __trap();
        }
        const unsigned int* src = p.s->part + warp * 4 * D_ + sp * 128 + lane * 4;
        uint4 v[4];
        while (true) {
            uint32_t bad = 0;
#pragma unroll
            for (int i = 0; i < 4; i++) v[i] = ld_relaxed4(src + i * D_);
#pragma unroll
            for (int i = 0; i < 4; i++) bad |= (v[i].x ^ par) | (v[i].y ^ par) | (v[i].z ^ par) | (v[i].w ^ par);
            if (!__any_sync(0xffffffffu, bad & 1u)) break;
            if (++n > SPIN_LIMIT) __trap();
        }
        float4 s = make_float4(0.f, 0.f, 0.f, 0.f);
#pragma unroll
        for (int i = 0; i < 4; i++) {
            s.x += __uint_as_float(v[i].x); s.y += __uint_as_float(v[i].y);
            s.z += __uint_as_float(v[i].z); s.w += __uint_as_float(v[i].w);
        }
        *(float4*)&acc[warp * 128 + lane * 4] = s;
    } else if (warp == 14) {
        const uint4 k4 = wait_tags(p.s->keys + lane * 4, 15, par);
        const uint32_t k = __reduce_max_sync(0xffffffffu, max(max(k4.x, k4.y), max(k4.z, k4.w)));
        const int idx = 0x7fff - (int)(k & 0x7fffu);
        const uint4 g4 = wait_tags(p.s->gate + (idx & ~3), 0, par);
        const uint32_t gw = (idx & 2) ? ((idx & 1) ? g4.w : g4.z) : ((idx & 1) ? g4.y : g4.x);
        const uint32_t u = k >> 16;
        const uint32_t rb = (u & 0x8000u) ? (u & 0x7fffu) : (~u & 0xffffu);
        const float og = 1.f - __uint_as_float(gw & ~1u), rs = sigmoidf_(__uint_as_float(rb << 16));
        if (lane == 0) { sel[0] = idx; sel[1] = pack_bf16(og, og); sel[2] = pack_bf16(rs, rs); }
        sleep_until<500>(tstart + SUM_T0 + 4000);
        wait_counters(p.s->ready + (lane & 7) * 32, e1 * 16u);
    }
    __syncthreads();
    if (tid < 64) {
        float t0 = 0.f, t1 = 0.f;
#pragma unroll
        for (int i = 0; i < 14; i++) {
            const float2 z = *(const float2*)&acc[i * 128 + tid * 2];
            t0 += z.x; t1 += z.y;
        }
        asm volatile("red.relaxed.gpu.global.add.noftz.bf16x2 [%0], %1;" ::"l"(p.out + sel[0] * D_ + sp * 128 + tid * 2),
                     "r"(hmul2_bf16(sel[1], hmul2_bf16(sel[2], pack_bf16(t0, t1)))) : "memory");
    }
}

__host__ __device__ constexpr int off_d(int c) { return (c < 2 ? 1 : c / 2 + 2) * REGION + (c & 1) * 16384; }
__host__ __device__ constexpr int off_xe(int c) { return (c < 2 ? 6 * REGION : c < 4 ? 16384 : c < 6 ? 0 : 6 * REGION + 16384) + (c & 1) * 8192; }
__host__ __device__ constexpr int off_xl(int c) { return c < 4 ? 2 * REGION + c * 8192 : off_xe(c - 4); }

__global__ void __cluster_dims__(2, 1, 1) __launch_bounds__(NTHREADS, 1)
fused_kernel(const __grid_constant__ Params p) {
    extern __shared__ __align__(1024) unsigned char smem[];
    const uint32_t tstart = clk();
    const uint32_t sb = smem_u32(smem);
    const int tid = threadIdx.x, lane = tid & 31;
    const int rank = blockIdx.x & 1;
    uint32_t t1 = 0;
    if (__any_sync(0xffffffffu, tid == 0)) {
        uint32_t s0;
        const uint32_t r0 = get_role(s0);
        mbar_init_elect(sb + B_F, 1);
        if (r0 < 64) {
#pragma unroll
            for (int c = 0; c < 2; c++) {
                if (c) {
                    spin_until(t1 + PACE);
                    mbar_init_elect(sb + B_F + 8, 1);
                }
                tma3d_elect(sb + off_d(c), &p.mDre + ((r0 >> 2) & 1), (r0 & 24) * 16, c, sb + B_F + 8 * c);
                tma3d_elect(sb + off_xe(c), &p.mX1, (r0 & 3) * 256 + (r0 & 32) * 4 + rank * 64, c, sb + B_F + 8 * c);
                mbar_expect_tx_elect(sb + B_F + 8 * c, 24576);
                if (!c) t1 = clk();
            }
        }
    }
    const int warp = __shfl_sync(0xffffffffu, tid >> 5, 0);
    uint32_t smid;
    const uint32_t role = get_role(smid);
    const int gpc = role & 7;
    const int tn = (role >> 3) & 3;
    const int comp = gpc >> 2;
    const int own = (gpc & 3) * 4 + ((role >> 5) & 1) * 2 + rank;
    const int blk = comp * 4 + tn;
    const int cta = gpc * 16 + (role >> 3) * 2 + rank;
    const bool ffn = cta < FFN_CTAS;
    uint32_t epoch = 0;
    if (warp != 0) {
        const uint32_t b1 = sb + B_F + 8 * warp;
        mbar_init_elect(warp < 2 ? b1 + 360 : b1, 1);
        if (warp == 2 || warp == 3) mbar_init_elect(b1 + 360, 1);
        mbar_init_elect(b1 + 120, warp < 7 ? 5 : warp < 14 ? 4 : warp - 12);
        mbar_init_elect(b1 + 240, 1);
        if (warp == 9 || warp == 15) mbar_expect_tx_elect(b1 + 240, warp == 9 ? 2048 : 4);
        asm volatile("fence.mbarrier_init.release.cluster;" ::: "memory");
        if (tid == 128 && role < 64) epoch = *(volatile unsigned int*)&p.s->epoch[cta];
    }
    if (role >= 64) {
        spare_job(p, smem, smid & 3, tstart);
        return;
    }
    __syncthreads();
    cluster_arrive();
    if (warp == 0) {
#pragma unroll
        for (int c = 2; c < 8; c++) {
            spin_until(t1 + c * PACE);
            tma3d_elect(sb + off_d(c), &p.mDre + comp, tn * 128, c, sb + B_F + 8 * c);
            tma3d_elect(sb + off_xe(c), &p.mX1, own * 64, c, sb + B_F + 8 * c);
            mbar_expect_tx_elect(sb + B_F + 8 * c, 24576);
        }
        tma3d_elect(sb + off_xl(0), &p.mX2, own * 64 + 1024, 0, sb + B_G0);
        mbar_expect_tx_elect(sb + B_G0, 16384);
        spin_until(t1 + 8 * PACE);
        tma3d_elect(sb + off_xl(2), &p.mX2, own * 64 + 1024, 2, sb + B_G2);
        mbar_expect_tx_elect(sb + B_G2, 16384);
        if (tn < 2)
            asm volatile(ELECT "cp.async.bulk.prefetch.tensor.3d.L2.global [%0, {%1,%2,%3}];}"
                         ::"l"(&p.mX2), "r"(0), "r"(own * 64 + 1024), "r"(4 + 2 * tn) : "memory");
    }

    if (warp < 4) {
        const int tab = tile_of_step(lane, own);
        const uint32_t bdst = sb + 16384 + rank * 8192;
        const int brow = blk * 4096 + rank * 64;
        if (warp == 0) {
            mbar_spin(sb + B_XE, 0);
            tma3d_elect(sb + off_xl(4), &p.mX2, own * 64 + 1024, 4, sb + B_G4);
            tma3d_elect(sb + off_xl(6), &p.mX2, own * 64 + 1024, 6, sb + B_G4);
            mbar_expect_tx_elect(sb + B_G4, 32768);
#define LOAD_A() const int e = __shfl_sync(0xffffffffu, tab, step);                                             \
                 const uint32_t bar = sb + 8 * slot;                                                            \
                 mbar_spin(bar + B_EMPTY, ph);                                                                  \
                 tma2d_elect(sb + slot * REGION, &p.mCre + comp, e * 64, own * 128, bar + B_FULL);              \
                 mbar_expect_tx_elect(bar + B_FULL, 16384)
            uint32_t slot = 0, ph = 0;
            int step = 0;
#pragma unroll 1
            for (; step < NSTAGE; step++, slot++) {
                LOAD_A();
                if (step == 2 || step == 3) spin_until(clk() + A_GAP);
            }
            slot = 0; ph = 1;
#pragma unroll 1
            for (int last = 16; last < 32; last += 15) {
#pragma unroll 1
                for (; step < last; step++) {
                    LOAD_A();
                    tma2d_pair_elect(bdst + slot * REGION, &p.mAB, 0, brow + e * 128, bar + B_BL);
                    mbar_expect_tx_elect(bar + B_BL, 16384);
                    if (++slot == NSTAGE) { slot = 0; ph ^= 1; }
                }
                LOAD_A();
                tma2d_elect(bdst + slot * REGION, &p.mAB, 0, brow + e * 128, bar + B_BL);
                tma2d_elect((bdst ^ 8192) + slot * REGION, &p.mAB, 0, (brow ^ 64) + e * 128, bar + B_BL);
                mbar_expect_tx_elect(bar + B_BL, 16384);
                step++; slot++;
            }
        } else if (warp == 1) {
            if (lane < 4) asm volatile("prefetch.tensormap [%0];" ::"l"(&p.mCre + lane) : "memory");
            __syncwarp();
            cluster_wait();
            if (lane == 0)
                asm volatile("st.async.weak.shared::cluster.mbarrier::complete_tx::bytes.u32 [%0], %1, [%2];"
                             ::"r"(mapa(sb + M_ROLE, rank ^ 1)), "r"(role), "r"(mapa(sb + B_ROLE, rank ^ 1)) : "memory");
            mbar_wait_cluster(sb + B_ROLE, 0);
            if (*(volatile uint32_t*)(smem + M_ROLE) != role) __trap();
            mbar_wait(sb + B_EPOCH, 0);
            const uint32_t want = (*(volatile uint32_t*)(smem + M_EPOCH) + 1u) * 4u;
            const int eh = __shfl_sync(0xffffffffu, tab, 2 + (lane & 3));
            const unsigned int* hp = p.s->hint + (blk * 4 + (eh >> 1)) * 32 + (eh & 1);
            uint32_t seen = __ballot_sync(0xffffffffu, ld_relaxed(hp) == want);
            int rows[4];
#pragma unroll
            for (int i = 0; i < 4; i++) {
                rows[i] = brow + __shfl_sync(0xffffffffu, tab, 2 + i) * 128;
                mbar_expect_tx_elect(sb + B_BL + 8 * (2 + i), 16384);
            }
            mbar_wait(sb + B_EMPTY + 8 * 3, 0);
            mbar_spin(sb + B_EMPTY + 8 * 2, 0);
            uint32_t t3 = 0;
#pragma unroll
            for (int i = 0; i < 4; i++) {
                while (!((seen >> i) & 1u)) seen = __ballot_sync(0xffffffffu, ld_relaxed(hp) == want);
                if (i) spin_until(t3 + B_GAP);
                t3 = clk();
                if (i >= 2) mbar_spin(sb + B_EMPTY + 8 * (2 + i), 0);
                tma2d_pair_elect(bdst + (2 + i) * REGION, &p.mAB, 0, rows[i], sb + B_BL + 8 * (2 + i));
            }
            mbar_wait(sb + B_FREE, 0);
            unsigned char* gdst = p.s->ab + (blk * 32 + own + 16) * 16384;
            t3 = clk();
#pragma unroll 1
            for (int i = 0; i < 16; i++) {
                sleep_until<20>(t3);
                t3 += LATE_GAP;
                asm volatile(ELECT "cp.async.bulk.global.shared::cta.bulk_group [%0], [%1], 1024;}"
                             ::"l"(gdst + i * 1024), "r"(sb + 6 * REGION + i * 1024) : "memory");
            }
            bulk_wait_read();
            mbar_arrive_elect(sb + B_FREE + 8);
            mbar_wait(sb + B_PUB, 0);
            if (lane == 0) {
                asm volatile("fence.proxy.async.global;" ::: "memory");
                asm volatile("red.release.gpu.global.add.u32 [%0], 1;" ::"l"(p.s->ready + blk * 32) : "memory");
            }
            __syncwarp();
            __nanosleep(500);
            wait_counters(p.s->ready + (lane & 7) * 32, want * 4u);
            mbar_arrive_elect(sb + B_INIT);
        } else {
            mbar_arrive_elect(sb + B_BL + 8 * (warp & 1));
            uint32_t k = warp == 3 ? 0 : 12;
#define PREFETCH_W() {                                                                                          \
                const char* src = (k >= 8 ? (const char*)p.wd + ((cta >> 5) * 2 + (k >> 1) - 4) * 229376        \
                                          : (const char*)((cta & 32) ? p.wu : p.wg) + ((cta >> 6) * 4 + (k >> 1)) * 229376) \
                                  + ((cta & 31) * 2 + (k & 1)) * 3584;                                          \
                asm volatile(ELECT "cp.async.bulk.prefetch.L2.global [%0], 3584;}" ::"l"(src) : "memory");      \
                k++; }
#pragma unroll 1
            while (k < PF_N0) {
                sleep_until<50>(tstart + PF_T0 + k * PF_GAP);
                __syncwarp();
                PREFETCH_W();
            }
            mbar_wait(sb + B_EPOCH, 0);
            const uint32_t par = (*(volatile uint32_t*)(smem + M_EPOCH) + 1u) & 1u;
            const uint32_t a0 = sb + 16384 + (lane >> 3) * 1028 + ((lane >> 2) & 1) * 144 + (lane & 3) * 32;
            const uint32_t retry = sb + B_RETRY + (warp & 1) * 240;
            uint32_t slot = warp, ph = 0, rph = 0;
            uint32_t j = ffn ? warp & 1 : 12;
#pragma unroll 1
            for (int step = warp; step < 32 || j < 12; step += 2) {
                if (step < 32) {
                    const uint32_t bar = sb + 8 * slot;
                    mbar_wait(bar + B_BL, ph);
#pragma unroll 1
                    while (__any_sync(0xffffffffu, stale_tags(a0 + slot * REGION, par) & 1u)) {
                        const int row = blk * 4096 + __shfl_sync(0xffffffffu, tab, step) * 128;
                        mbar_expect_tx_elect(retry, 16384);
                        tma2d_elect(sb + slot * REGION + 16384, &p.mAB, 0, row, retry);
                        tma2d_elect(sb + slot * REGION + 24576, &p.mAB, 0, row + 64, retry);
                        mbar_spin(retry, rph);
                        rph ^= 1u;
                    }
                    mbar_arrive_elect<4>(bar + B_FULL);
                }
                if (j < 12 && step >= FFN_S0 + j * FFN_W / 4 && __any_sync(0xffffffffu, mbar_test(sb + B_FREE + 2 * (j & 12), 0))) {
                    const uint32_t fb = sb + B_FFN + 4 * (j & 6);
                    if (!(j & 1)) mbar_expect_tx_elect(fb, 8192);
                    tma2d_elect(sb + 6 * REGION + ((j + 4) & 7) * 4096, j < 8 ? &p.mWg + (j & 1) : &p.mWd,
                                j < 8 ? (cta >> 1) * 32 : rank * 256, j < 8 ? rank * 256 + (j >> 1) * 64 : (cta >> 1) * 32 + j * 8 - 64, fb);
                    j += 2;
                }
                if (k < 12) PREFETCH_W();
                slot += 2;
                if (slot >= NSTAGE) { slot -= NSTAGE; ph ^= 1; }
            }
        }
    } else if (warp < 8) {
        const int t = tid - 128, w = warp - 4;
        if (t == 0) {
            *(volatile uint32_t*)(smem + M_EPOCH) = epoch;
            *(volatile unsigned int*)&p.s->epoch[cta] = epoch + 1;
        }
        mbar_arrive_if(sb + B_EPOCH, t == 0);
        const uint4 gw0 = ldg_nc<0>(p.gate_w + lane * 8), gw1 = ldg_nc<512>(p.gate_w + lane * 8);
        const uint4 rw0 = ldg_nc<0>(p.w_r + lane * 8), rw1 = ldg_nc<512>(p.w_r + lane * 8);
        mbar_wait(sb + B_EPOCH, 0);
        const uint32_t par = (*(volatile uint32_t*)(smem + M_EPOCH) + 1u) & 1u;
        mbar_wait(sb + B_F + 8 * ROUTER_C, 0);
        const int row0 = cta * 16 + w * 4;
        uint4 xr[8];
        {
            const char* xp = (const char*)p.x + (uint32_t)row0 * (D_ * 2) + lane * 16;
            xr[0] = ldg_nc<0>(xp);    xr[1] = ldg_nc<512>(xp);  xr[2] = ldg_nc<1024>(xp); xr[3] = ldg_nc<1536>(xp);
            xr[4] = ldg_nc<2048>(xp); xr[5] = ldg_nc<2560>(xp); xr[6] = ldg_nc<3072>(xp); xr[7] = ldg_nc<3584>(xp);
            float a[8];
#pragma unroll
            for (int i = 0; i < 4; i++) {
                const uint32_t xv[8] = {xr[2 * i].x, xr[2 * i].y, xr[2 * i].z, xr[2 * i].w,
                                        xr[2 * i + 1].x, xr[2 * i + 1].y, xr[2 * i + 1].z, xr[2 * i + 1].w};
                const uint32_t gv[8] = {gw0.x, gw0.y, gw0.z, gw0.w, gw1.x, gw1.y, gw1.z, gw1.w};
                const uint32_t rv[8] = {rw0.x, rw0.y, rw0.z, rw0.w, rw1.x, rw1.y, rw1.z, rw1.w};
                float u = 0.f, v = 0.f;
#pragma unroll
                for (int j = 0; j < 8; j++) {
                    const uint32_t pr = hmul2_bf16(xv[j], gv[j]);
                    u += bflo(pr); u += bfhi(pr);
                    v = fmaf(bflo(xv[j]), bflo(rv[j]), v); v = fmaf(bfhi(xv[j]), bfhi(rv[j]), v);
                }
                a[i] = u; a[4 + i] = v;
            }
            mbar_wait(sb + B_EARLY, 0);
            halve<4, 16>(a); halve<2, 8>(a); halve<1, 4>(a);
            a[0] += __shfl_xor_sync(0xffffffffu, a[0], 1);
            a[0] += __shfl_xor_sync(0xffffffffu, a[0], 2);
            const int row = row0 + ((lane >> 2) & 3);
            const float gate = rbf(sigmoidf_(rbf(a[0])));
            if (lane < 16 && (lane & 3) == 0)
                asm volatile("st.relaxed.gpu.global.u32 [%0], %1;" ::"l"(&p.s->gate[row]), "r"(tagf(gate, par)) : "memory");
            const uint32_t best = __reduce_max_sync(0xffffffffu, lane >= 16 ? router_key(a[0], row) : 0u);
            if (lane == 0) *(volatile uint32_t*)(smem + M_KEY + w * 4) = best;
            side_bar();
            if (t < 8) {
                const uint4 k = *(const uint4*)(smem + M_KEY);
                asm volatile("{.reg .b32 old; atom.relaxed.gpu.global.exch.b32 old, [%0], %1;}" ::"l"(&p.s->keys[t * NCTA + cta]),
                             "r"(max(max(k.x, k.y), max(k.z, k.w)) | (par << 15)) : "memory");
            }
            const uint32_t og = pack_bf16(1.f - gate, 1.f - gate);
#pragma unroll
            for (int i = 0; i < 8; i++) {
                const uint32_t o = __shfl_sync(0xffffffffu, og, 4 * (i >> 1));
                xr[i] = make_uint4(hmul2_bf16(o, xr[i].x), hmul2_bf16(o, xr[i].y), hmul2_bf16(o, xr[i].z), hmul2_bf16(o, xr[i].w));
            }
        }
        mbar_wait(sb + B_FREE, 0);
        if (w == 0) {
            const uint4 k4 = wait_tags(p.s->keys + gpc * NCTA + lane * 4, 15, par);
            const uint32_t k = __reduce_max_sync(0xffffffffu, max(max(k4.x, k4.y), max(k4.z, k4.w)));
            sts128<M_XS>(sb + lane * 16, ldg_nc<0>(p.x + (0x7fff - (k & 0x7fffu)) * D_ + rank * 256 + lane * 8));
        } else if (w == 1) {
            const uint4 g4 = wait_tags(p.s->gate + own * 128 + lane * 4, 0, par);
            const uint32_t sg = comp ? 0x80000000u : 0u;
            sts128<M_G>(sb + lane * 16, make_uint4((g4.x & ~1u) ^ sg, (g4.y & ~1u) ^ sg, (g4.z & ~1u) ^ sg, (g4.w & ~1u) ^ sg));
            mbar_arrive_warp(sb + B_GATE);
        }
        side_bar();
        char* op = (char*)p.out + (uint32_t)row0 * (D_ * 2) + lane * 16;
        float a[16];
#pragma unroll
        for (int i = 0; i < 16; i++) a[i] = 0.f;
#pragma unroll 1
        for (int i = 0; i < 4; i++) {
            if (i >= 2) {
                mbar_wait(sb + B_FREE + 8, 0);
                const uint32_t t2 = clk() + w * (INIT_GAP / 4);
#pragma unroll
                for (int j = 0; j < 4; j++) {
                    sleep_until<20>(t2 + j * INIT_GAP);
                    *(uint4*)(op + j * 512) = xr[j];
                    xr[j] = xr[j + 4];
                }
                op += 2048;
                if (i == 3) mbar_arrive_warp(sb + B_PUB);
            }
            if (ffn) {
                const float xs0 = __bfloat162float(((const bf16*)(smem + M_XS))[64 * i + (t >> 2)]);
                const float xs1 = __bfloat162float(((const bf16*)(smem + M_XS))[64 * i + 32 + (t >> 2)]);
                const uint32_t wa = sb + 6 * REGION + (i ^ 2) * 8192 + t * 16;
                mbar_wait(sb + B_FFN + 8 * i, 0);
                const uint4 v0 = lds128(wa), v1 = lds128(wa + 4096), v2 = lds128(wa + 2048), v3 = lds128(wa + 6144);
                const uint32_t w0[8] = {v0.x, v0.y, v0.z, v0.w, v1.x, v1.y, v1.z, v1.w};
                const uint32_t w1[8] = {v2.x, v2.y, v2.z, v2.w, v3.x, v3.y, v3.z, v3.w};
#pragma unroll
                for (int k = 0; k < 8; k++) {
                    a[2 * k] = fmaf(xs1, bflo(w1[k]), fmaf(xs0, bflo(w0[k]), a[2 * k]));
                    a[2 * k + 1] = fmaf(xs1, bfhi(w1[k]), fmaf(xs0, bfhi(w0[k]), a[2 * k + 1]));
                }
                if (i == 1) {
                    side_bar();
                    mbar_arrive_if(sb + B_FREE + 16, t == 0);
                }
            }
        }
        if (!ffn) return;
        halve<8, 16>(a); halve<4, 8>(a); halve<2, 4>(a);
        const uint32_t ho = (lane >> 4) * 128 + (lane & 3) * 32 + ((lane >> 2) & 3) * 8;
        cluster_wait();
#pragma unroll
        for (int k = 0; k < 2; k++)
            asm volatile("st.async.weak.shared::cluster.mbarrier::complete_tx::bytes.v2.f32 [%0], {%1,%2}, [%3];"
                         ::"r"(mapa(sb + (k ? 6 * REGION + w * 512 : M_HX + w * 256) + ho, rank ^ k ^ 1)), "f"(a[0]), "f"(a[1]),
                           "r"(mapa(sb + B_HX, rank ^ k ^ 1)) : "memory");
        mbar_wait_cluster(sb + B_HX, 0);
        const float *hx = (const float*)(smem + M_HX) + lane, *hy = (const float*)(smem + 6 * REGION) + lane;
        const float gs = rbf(((hx[0] + hy[0]) + (hx[64] + hy[128])) + ((hx[128] + hy[256]) + (hx[192] + hy[384])));
        const float us = rbf(((hx[32] + hy[32]) + (hx[96] + hy[160])) + ((hx[160] + hy[288]) + (hx[224] + hy[416])));
        float* hrow = (float*)(smem + M_XS) + w * 32;
        hrow[lane] = rbf(rbf(gs * sigmoidf_(gs)) * us);
        __syncwarp();
        float o0 = 0.f, o1 = 0.f;
#pragma unroll 1
        for (int i = 0; i < 2; i++) {
            float4 hv[4];
            uint32_t vd[16];
#pragma unroll
            for (int k = 0; k < 4; k++) hv[k] = *(const float4*)&hrow[i * 16 + k * 4];
            mbar_wait(sb + B_FFN + 8 * i, 1);
#pragma unroll
            for (int k = 0; k < 16; k++) vd[k] = *(const volatile uint32_t*)(smem + 6 * REGION + 16384 + i * 8192 + k * 512 + t * 4);
#pragma unroll
            for (int k = 0; k < 4; k++) {
                o0 = fmaf(hv[k].x, bflo(vd[4 * k]), o0);     o1 = fmaf(hv[k].x, bfhi(vd[4 * k]), o1);
                o0 = fmaf(hv[k].y, bflo(vd[4 * k + 1]), o0); o1 = fmaf(hv[k].y, bfhi(vd[4 * k + 1]), o1);
                o0 = fmaf(hv[k].z, bflo(vd[4 * k + 2]), o0); o1 = fmaf(hv[k].z, bfhi(vd[4 * k + 2]), o1);
                o0 = fmaf(hv[k].w, bflo(vd[4 * k + 3]), o0); o1 = fmaf(hv[k].w, bfhi(vd[4 * k + 3]), o1);
            }
        }
        asm volatile("st.relaxed.gpu.global.v2.u32 [%0], {%1,%2};" ::"l"(&p.s->part[(cta >> 1) * D_ + rank * 256 + t * 2]),
                     "r"(tagf(o0, par)), "r"(tagf(o1, par)) : "memory");
        red_inc_if(p.s->phint + ((rank * 2 + (w >> 1)) * 16 + (cta >> 3)) * 8 + lane, lane == 0);
    } else {
        const int wg = (warp >> 2) - 2, wq = warp & 3;
        const uint32_t sbd = ((sb & 0x3FFFF) >> 4) + 0x10000;
        const bool lead = (tid & 127) == 0;
        const bool lead0 = lead && !wg, lead1 = lead && wg;
        const int q = lane & 3;
        float acc[64];
        const uint32_t rE = mapa(sb + B_EMPTY, rank ^ 1);
#define RELEASE(n, slot, pred) release_pair<n>(sb + B_EMPTY + 8 * (slot), rE + 8 * (slot), pred)
        const uint32_t ioff = wq * 4096 + (lane >> 2) * 64 + ((q ^ (lane >> 3)) << 4);
        const uint32_t sdst = pin(sb + 6 * REGION + (wg ? 0 : 16384) + ioff);
        unsigned char* gdst = pin(p.s->ab + (blk * 32 + own) * 16384 + ioff);
        unsigned int* hint = pin(p.s->hint + (blk * 4 + ((own >> 1) & 3)) * 32 + rank + lane);
        uint32_t par = 0;
#define GET_PAR() mbar_spin(sb + B_EPOCH, 0); par = (*(volatile uint32_t*)(smem + M_EPOCH) + 1u) & 1u
        cluster_wait();
        if (wg) {
            GET_PAR();
            mbar_spin(sb + B_G0, 0);
            mbar_spin(sb + B_GO1, 0);
        }
#pragma unroll
        for (int c = 0; c < 8; c++) {
            if (!wg || c == 2 || c == 4) mbar_spin(sb + (!wg ? B_F + 8 * c : c == 2 ? B_G2 : B_G4), 0);
            wg_fence();
#pragma unroll
            for (int kk = 0; kk < 4; kk++) {
                wgmma128<0>(acc, desc128(sbd + (wg ? off_xl(c) : off_xe(c)) / 16 + 2 * kk), desc128(sbd + off_d(c) / 16 + 2 * kk), (c | kk) != 0);
                if (c == 7 && kk == 0) wg_commit();
            }
            wg_commit();
            if (c == 3 && !wg) { GET_PAR(); }
            if (c == 7) {
                if (wg) mbar_spin(sb + B_FULL, 0);
                wg_wait<2>();
                mbar_arrive_if(sb + B_GO1, lead0);
            }
            if (c == 2 || c == 4 || c >= 6) wg_wait<1>();
            if (c == 2) RELEASE(2, 1, lead1);
            if (c == 4) { mbar_arrive_if(sb + B_XE, lead0); RELEASE(2, 2, lead1); RELEASE(2, 3, lead1); }
            if (c == 6) RELEASE(2, 4 * wg, lead);
            if (c == 7) mbar_arrive_if(sb + B_GO0, lead1);
        }
        const int rh = wg ^ comp;
        const uint32_t da0 = sbd + rh * 512, db0 = sbd - 0x10000 + 0x400000 + 1024;
        const uint32_t dbe = db0 + 6 * (REGION / 16), dbl = dbe - 1024;
#define STEP(da, db, first) wg_fence();                                                                     \
        _Pragma("unroll") for (int kk = 0; kk < 4; kk++)                                                    \
            wgmma128<1>(acc, desc128((da) + kk * 2), desc64((db) + kk * 256), !((first) && kk == 0));       \
        wg_commit()
#define ACC(i, j) (16 * ((i) >> 1) + 2 * ((i) & 1) + 4 * (j))
#define PW(i, j) pack_bf16(acc[ACC(i, j)], acc[ACC(i, j) + 1])
#define PT(i, j) ((j) == ((i) >> 1) ? (PW(i, j) & ~1u) | par : PW(i, j))
#define PIECE(i) make_uint4(PT(i, 0), PT(i, 1), PT(i, 2), PT(i, 3))
#define PIECES(F) F(0); F(1); sched_cut(); F(2); F(3); sched_cut(); F(4); F(5); sched_cut(); F(6); F(7)
        if (wg) {
            wg_wait<0>();
            fence_regs(acc);
#define STS1(i) sts128<(i) * 512>(sdst, PIECE(i))
            PIECES(STS1);
            STEP(da0, dbe, true);
            fence_proxy_async_smem();
            mbar_arrive_warp(sb + B_FULL + 8);
            RELEASE(1, 5, lead);
        } else {
            wg_wait<0>();
            fence_regs(acc);
            uint4 v[8];
#define STG0(i) v[i] = PIECE(i); stg128<(i) * 512>(gdst, v[i]); if (HINT_AT == (i) + 1) red_inc_if(hint, own < 6 && lane == 0)
            PIECES(STG0);
#define STS0(i) mbar_spin(sb + B_EPOCH, 0); sts128<(i) * 512>(sdst, v[i])
            STS0(0); STS0(1); STS0(2); STS0(3); STS0(4); STS0(5); STS0(6); STS0(7);
            fence_proxy_async_smem();
            mbar_arrive_warp(sb + B_FULL);
            RELEASE(1, 5, lead);
            mbar_arrive_if(sb + B_EARLY, lead);
            mbar_spin(sb + B_FULL, 0);
            mbar_spin(sb + B_GO0, 0);
            STEP(da0, dbe, true);
        }
#pragma unroll
        for (int step = 1; step < 3; step++) {
            mbar_spin(sb + B_FULL + 8 * step, 0);
            STEP(da0 + step * (REGION / 16), step == 1 ? dbl : db0 + step * (REGION / 16), false);
            wg_wait<1>();
            RELEASE(1, step - 1, lead);
            mbar_arrive_if(sb + B_FREE + 8 * (step - 1), lead);
        }
        int slot = 3, ph = 0, pslot = 2;
#pragma unroll 1
        for (int step = 3; step <= 32 - NSTAGE; step++) {
            mbar_wait(sb + B_FULL + 8 * slot, ph);
            STEP(da0 + slot * (REGION / 16), db0 + slot * (REGION / 16), false);
            wg_wait<1>();
            RELEASE(1, pslot, lead);
            pslot = slot;
            if (++slot == NSTAGE) { slot = 0; ph ^= 1; }
        }
        float g0 = 0.f, g1 = 0.f;
        char* op = nullptr;
#pragma unroll 1
        for (int step = 33 - NSTAGE; step < 32; step++) {
            if (step == (wg ? 32 - SK : 30)) {
                const int r0 = rh * 64 + wq * 16 + (lane >> 2);
                mbar_wait(sb + B_GATE, 0);
                g0 = ((const volatile float*)(smem + M_G))[r0];
                g1 = ((const volatile float*)(smem + M_G))[r0 + 8];
                op = pin((char*)p.out + (uint32_t)((own * 128 + (r0 & ~1)) * D_ + tn * 128 + (lane & 7) * 8) * 2u);
                mbar_wait(sb + (wg ? B_TAIL : B_INIT), 0);
            }
            if (!wg || step < 32 - SK) mbar_wait(sb + B_FULL + 8 * slot, ph);
            STEP(da0 + slot * (REGION / 16), db0 + slot * (REGION / 16), false);
            if (++slot == NSTAGE) { slot = 0; ph ^= 1; }
        }
#define OW(i, j) pack_bf16((((i) & 1) ? g1 : g0) * acc[ACC(i, j)], (((i) & 1) ? g1 : g0) * acc[ACC(i, j) + 1])
        if (!wg) {
            wg_wait<1>();
            mbar_arrive_if(sb + B_TAIL, lead);
            const int sr = ((lane >> 2) & 1) * 4 + (lane >> 3);
            const uint32_t st0 = sb + rh * 8192 + wq * 2048, sa = pin(st0 + sr * 128 + ((q ^ sr) << 4));
            sched_cut();
            wg_wait<0>();
            fence_regs(acc);
#define OSTS(i) sts128<((i) >> 2) * REGION + ((i) & 1) * 1024>(((i) & 2) ? sa ^ 64 : sa, make_uint4(OW(i, 0), OW(i, 1), OW(i, 2), OW(i, 3)))
#define ORED(h) fence_proxy_async_smem(); __syncwarp();                                                     \
            asm volatile(ELECT "cp.reduce.async.bulk.tensor.4d.global.shared::cta.add.tile.bulk_group [%0, {%2,%3,%3,%4}], [%1];}" \
                         ::"l"(&p.mOut), "r"(st0 + (h) * REGION), "r"(tn * 128 + (h) * 64), "r"(0), "r"(own * 16 + rh * 8 + wq * 2) : "memory")
            OSTS(0); OSTS(1); OSTS(2); OSTS(3);
            ORED(0);
            sched_cut();
            OSTS(4); OSTS(5); OSTS(6); OSTS(7);
            ORED(1);
            bulk_wait_read();
        } else {
            const bool odd = lane & 4;
            char* opb = pin(op + (odd ? 1024 - 64 : 1024 + 64));
            sched_cut();
            wg_wait<0>();
            fence_regs(acc);
#define REDLINE(i) {                                                                                        \
                uint32_t k[4], r[4];                                                                        \
                _Pragma("unroll") for (int j = 0; j < 4; j++) {                                             \
                    r[j] = __shfl_xor_sync(0xffffffffu, OW((i) + 2, j), 4);                                 \
                    k[j] = OW(i, j);                                                                        \
                }                                                                                           \
                red_bf16x8<((i) & 1) * 8192 + ((i) >> 2) * 128>(op, odd ? r[0] : k[0], odd ? r[1] : k[1], odd ? r[2] : k[2], odd ? r[3] : k[3]);  \
                red_bf16x8<((i) & 1) * 8192 + ((i) >> 2) * 128>(opb, odd ? k[0] : r[0], odd ? k[1] : r[1], odd ? k[2] : r[2], odd ? k[3] : r[3]); }
            REDLINE(0)
            sched_cut();
            REDLINE(1) REDLINE(4) REDLINE(5)
        }
    }
}

typedef CUresult (*EncodeTiledFn)(CUtensorMap*, CUtensorMapDataType, cuuint32_t, void*, const cuuint64_t*, const cuuint64_t*,
                                  const cuuint32_t*, const cuuint32_t*, CUtensorMapInterleave, CUtensorMapSwizzle,
                                  CUtensorMapL2promotion, CUtensorMapFloatOOBfill);

static void make_map(EncodeTiledFn enc, CUtensorMap* m, const void* base, uint64_t cols, uint64_t rows, uint32_t box_rows,
                     CUtensorMapSwizzle sw = CU_TENSOR_MAP_SWIZZLE_128B, uint32_t box_cols = 64) {
    cuuint64_t dims[2] = {cols, rows};
    cuuint64_t str[1] = {cols * 2};
    cuuint32_t box[2] = {box_cols, box_rows};
    cuuint32_t es[2] = {1, 1};
    enc(m, CU_TENSOR_MAP_DATA_TYPE_BFLOAT16, 2, (void*)base, dims, str, box, es, CU_TENSOR_MAP_INTERLEAVE_NONE,
        sw, CU_TENSOR_MAP_L2_PROMOTION_L2_128B, CU_TENSOR_MAP_FLOAT_OOB_FILL_NONE);
}

static void make_map_chunks(EncodeTiledFn enc, CUtensorMap* m, const void* base, uint64_t rows, uint32_t box_rows, uint32_t n = 1) {
    cuuint64_t dims[3] = {64, rows, 8};
    cuuint64_t str[2] = {D_ * 2, 128};
    cuuint32_t box[3] = {64, box_rows, n};
    cuuint32_t es[3] = {1, 1, 1};
    enc(m, CU_TENSOR_MAP_DATA_TYPE_BFLOAT16, 3, (void*)base, dims, str, box, es, CU_TENSOR_MAP_INTERLEAVE_NONE,
        CU_TENSOR_MAP_SWIZZLE_128B, CU_TENSOR_MAP_L2_PROMOTION_L2_128B, CU_TENSOR_MAP_FLOAT_OOB_FILL_NONE);
}

static void make_map_out(EncodeTiledFn enc, CUtensorMap* m, const void* base) {
    cuuint64_t dims[4] = {D_, 4, 2, S_ / 8};
    cuuint64_t str[3] = {2 * D_ * 2, D_ * 2, 8 * D_ * 2};
    cuuint32_t box[4] = {64, 4, 2, 2};
    cuuint32_t es[4] = {1, 1, 1, 1};
    enc(m, CU_TENSOR_MAP_DATA_TYPE_BFLOAT16, 4, (void*)base, dims, str, box, es, CU_TENSOR_MAP_INTERLEAVE_NONE,
        CU_TENSOR_MAP_SWIZZLE_128B, CU_TENSOR_MAP_L2_PROMOTION_NONE, CU_TENSOR_MAP_FLOAT_OOB_FILL_NONE);
}

extern "C" void kernel_launch(void* const* d_in, const int* in_sizes, int n_in, void* d_out, int out_size) {
    (void)in_sizes; (void)n_in; (void)out_size;
    static EncodeTiledFn enc = nullptr;
    static bool fused_ok = false;
    static void* scratch = nullptr;
    if (!enc) {
        void* fn = nullptr;
        cudaDriverEntryPointQueryResult q;
        cudaGetDriverEntryPoint("cuTensorMapEncodeTiled", &fn, cudaEnableDefault, &q);
        enc = (EncodeTiledFn)fn;
        cudaGetSymbolAddress(&scratch, g_s);
        cudaFuncSetAttribute(fused_kernel, cudaFuncAttributeMaxDynamicSharedMemorySize, SMEM_BYTES);
        int dev = 0, nsm = 0, ncl = 0;
        cudaGetDevice(&dev);
        cudaDeviceGetAttribute(&nsm, cudaDevAttrMultiProcessorCount, dev);
        cudaLaunchConfig_t cfg = {};
        cfg.gridDim = dim3(132); cfg.blockDim = dim3(NTHREADS); cfg.dynamicSmemBytes = SMEM_BYTES;
        cudaLaunchAttribute at;
        at.id = cudaLaunchAttributeClusterDimension;
        at.val.clusterDim.x = 2; at.val.clusterDim.y = 1; at.val.clusterDim.z = 1;
        cfg.attrs = &at; cfg.numAttrs = 1;
        fused_ok = cudaOccupancyMaxActiveClusters(&ncl, fused_kernel, &cfg) == cudaSuccess && nsm == 132 && ncl == 66;
        (void)cudaGetLastError();
    }
    if (!fused_ok) {
        const bf16* const* in = (const bf16* const*)d_in;
        fb_hidden<<<S_, D_, 0, cudaStreamPerThread>>>(in[0], in[3], in[4], in[10], in[6]);
        fb_ffn1<<<F_ / 128, 128, 0, cudaStreamPerThread>>>(in[0], in[7], in[8]);
        fb_ffn2<<<D_ / 64, 64, 0, cudaStreamPerThread>>>(in[9]);
        fb_seq<<<S_, D_, 0, cudaStreamPerThread>>>(in[0], in[1], in[2], (bf16*)d_out);
        return;
    }
    Params p;
    p.s = (Scratch*)scratch;
    p.x = (const bf16*)d_in[0];
    p.w_r = (const bf16*)d_in[6];
    p.wg = (const bf16*)d_in[7];
    p.wu = (const bf16*)d_in[8];
    p.wd = (const bf16*)d_in[9];
    p.gate_w = (const bf16*)d_in[10];
    p.out = (bf16*)d_out;
    make_map_chunks(enc, &p.mX1, d_in[0], S_, 64);
    make_map_chunks(enc, &p.mX2, d_in[0], S_, 64, 2);
    make_map(enc, &p.mCre, d_in[1], S_, S_, 128);
    make_map(enc, &p.mCim, d_in[2], S_, S_, 128);
    make_map_chunks(enc, &p.mDre, d_in[3], D_, 128);
    make_map_chunks(enc, &p.mDim, d_in[4], D_, 128);
    make_map(enc, &p.mAB, scratch, 64, 8 * 32 * 128, 64, CU_TENSOR_MAP_SWIZZLE_NONE);
    make_map_out(enc, &p.mOut, d_out);
    make_map(enc, &p.mWg, d_in[7], F_, D_, 64, CU_TENSOR_MAP_SWIZZLE_NONE, 32);
    make_map(enc, &p.mWu, d_in[8], F_, D_, 64, CU_TENSOR_MAP_SWIZZLE_NONE, 32);
    make_map(enc, &p.mWd, d_in[9], D_, F_, 8, CU_TENSOR_MAP_SWIZZLE_NONE, 256);
    fused_kernel<<<132, NTHREADS, SMEM_BYTES, cudaStreamPerThread>>>(p);
}
```

```cpp
#include <cuda_runtime.h>
#include <cuda.h>
#include <cuda_bf16.h>
#include <stdint.h>

typedef __nv_bfloat16 bf16;

constexpr int S_ = 2048, D_ = 512, F_ = 1792;
constexpr int NCTA = 128;
constexpr int NTHREADS = 512;
constexpr int NSTAGE = 6;
constexpr int REGION = 32768;
constexpr int FFN_CTAS = F_ / 16;
constexpr uint32_t SPIN_LIMIT = 1u << 22;
constexpr int PACE = 260;
constexpr int A_GAP = 300;
constexpr int B_GAP = 350;
constexpr int LATE_GAP = 240;
constexpr int INIT_GAP = 360;
constexpr int INIT_NS = 300;
constexpr int PF_T0 = 3000;
constexpr int PF_GAP = 850;
constexpr int PF_N0 = 4;
constexpr int FFN_S0 = 4;
constexpr int FFN_W = 7;
constexpr int ROUTER_C = 4;
constexpr int HINT_AT = 5;
constexpr int SUM_T0 = 15000;
constexpr int PS1 = 24;
constexpr int NA = 3;
constexpr int KEY_NS = 300;
constexpr int SK = 6;

constexpr int OFF_MISC = 7 * REGION;
constexpr int B_F = OFF_MISC;
constexpr int B_G0 = B_F + 64;
constexpr int B_G4 = B_G0 + 8;
constexpr int B_XE = B_G4 + 8;
constexpr int B_GO1 = B_XE + 8;
constexpr int B_GO0 = B_GO1 + 8;
constexpr int B_EPOCH = B_GO0 + 8;
constexpr int B_RETRY = B_EPOCH + 8;
constexpr int B_INIT = B_RETRY + 8;
constexpr int B_FULL = B_INIT + 8;
constexpr int B_EMPTY = B_FULL + 48;
constexpr int B_PUB = B_EMPTY + 48;
constexpr int B_FREE = B_PUB + 8;
constexpr int B_BL = B_FREE + 24;
constexpr int B_TAIL = B_BL + 48;
constexpr int B_HX = B_TAIL + 8;
constexpr int B_FFN = B_HX + 8;
constexpr int B_ROLE = B_FFN + 40;
constexpr int B_EARLY = B_ROLE + 8;
constexpr int B_GATE = B_EARLY + 8;
constexpr int B_G2 = B_GATE + 8;
constexpr int B_LOW = B_G2 + 8;
constexpr int M_EPOCH = B_LOW + 8;
constexpr int M_ROLE = M_EPOCH + 4;
constexpr int M_KEY = OFF_MISC + 416;
constexpr int M_HX = OFF_MISC + 512;
constexpr int M_G = M_HX + 1024;
constexpr int M_XS = M_G + 512;
constexpr int SMEM_BYTES = 232448;
static_assert(M_ROLE + 4 <= M_KEY && M_XS + 512 <= SMEM_BYTES, "smem");

struct Scratch {
    unsigned char ab[8 * 32 * 16384];
    unsigned int hint[8 * 4 * 32];
    unsigned int ready[16 * 32];
    unsigned int gate[S_];
    unsigned int part[FFN_CTAS / 2 * D_];
    unsigned int phint[4 * 16 * 8];
    unsigned int keys[8 * NCTA];
    unsigned int epoch[NCTA + 4];
};
__device__ __align__(1024) Scratch g_s;

struct Params {
    Scratch* s;
    bf16* out;
    const bf16 *x, *gate_w, *w_r, *wg, *wu, *wd;
    CUtensorMap mDre, mDim, mX1, mX2, mCre, mCim, mAB, mOut, mWg, mWu, mWd;
};

#define ELECT "{.reg .pred p; elect.sync _|p, 0xffffffff; @p "
__device__ __forceinline__ uint32_t smem_u32(const void* p) { return (uint32_t)__cvta_generic_to_shared(p); }
__device__ __forceinline__ uint32_t clk() { return (uint32_t)clock64(); }
__device__ __forceinline__ void spin_until(uint32_t t) { while ((int)(clk() - t) < 0) {} }
template <int NS>
__device__ __forceinline__ void sleep_until(uint32_t t) { while ((int)(clk() - t) < 0) __nanosleep(NS); }
__device__ __forceinline__ void mbar_init_elect(uint32_t bar, uint32_t cnt) {
    asm volatile(ELECT "mbarrier.init.shared::cta.b64 [%0], %1;}" ::"r"(bar), "r"(cnt) : "memory");
}
__device__ __forceinline__ void mbar_expect_tx_elect(uint32_t bar, uint32_t bytes) {
    asm volatile(ELECT "mbarrier.arrive.expect_tx.shared::cta.b64 _, [%0], %1;}" ::"r"(bar), "r"(bytes) : "memory");
}
template <int N = 1>
__device__ __forceinline__ void mbar_arrive_elect(uint32_t bar) {
    asm volatile(ELECT "mbarrier.arrive.shared::cta.b64 _, [%0], %1;}" ::"r"(bar), "n"(N) : "memory");
}
__device__ __forceinline__ void mbar_arrive_if(uint32_t bar, bool pred) {
    asm volatile("{.reg .pred p; setp.ne.b32 p, %1, 0; @p mbarrier.arrive.shared::cta.b64 _, [%0];}" ::"r"(bar), "r"((int)pred) : "memory");
}
__device__ __forceinline__ void mbar_arrive_warp(uint32_t bar) {
    __syncwarp();
    mbar_arrive_if(bar, (threadIdx.x & 31) == 0);
}
template <int N>
__device__ __forceinline__ void release_pair(uint32_t bar, uint32_t rbar, bool pred) {
    asm volatile("{.reg .pred p; setp.ne.b32 p, %2, 0; @p mbarrier.arrive.shared::cta.b64 _, [%0], %3;"
                 " @p mbarrier.arrive.shared::cluster.b64 _, [%1], %3;}" ::"r"(bar), "r"(rbar), "r"((int)pred), "n"(N) : "memory");
}
__device__ __forceinline__ uint32_t mapa(uint32_t a, uint32_t cta) {
    uint32_t r;
    asm volatile("mapa.shared::cluster.u32 %0, %1, %2;" : "=r"(r) : "r"(a), "r"(cta));
    return r;
}
__device__ __forceinline__ bool mbar_test(uint32_t bar, uint32_t parity) {
    uint32_t ok;
    asm volatile("{.reg .pred p; mbarrier.test_wait.parity.shared::cta.b64 p, [%1], %2; selp.u32 %0,1,0,p;}"
                 : "=r"(ok) : "r"(bar), "r"(parity) : "memory");
    return ok;
}
__device__ __forceinline__ void mbar_wait(uint32_t bar, uint32_t parity) {
    asm volatile("{.reg .pred p, q; .reg .u32 n; mov.u32 n, 0;\n"
                 "W%=: mbarrier.try_wait.parity.shared::cta.b64 p, [%0], %1;\n"
                 "add.u32 n, n, 1; setp.lt.and.u32 q, n, %2, !p; @q bra W%=; @!p trap;}" ::"r"(bar), "r"(parity), "n"(SPIN_LIMIT) : "memory");
}
__device__ __forceinline__ void mbar_wait_cluster(uint32_t bar, uint32_t parity) {
    asm volatile("{.reg .pred p, q; .reg .u32 n; mov.u32 n, 0;\n"
                 "W%=: mbarrier.try_wait.parity.acquire.cluster.shared::cta.b64 p, [%0], %1;\n"
                 "add.u32 n, n, 1; setp.lt.and.u32 q, n, %2, !p; @q bra W%=; @!p trap;}" ::"r"(bar), "r"(parity), "n"(SPIN_LIMIT) : "memory");
}
__device__ __forceinline__ void mbar_spin(uint32_t bar, uint32_t parity) {
    asm volatile("{.reg .pred p;\nW%=: mbarrier.try_wait.parity.shared::cta.b64 p, [%0], %1; @!p bra W%=;}" ::"r"(bar), "r"(parity) : "memory");
}
__device__ __forceinline__ void cluster_arrive() { asm volatile("barrier.cluster.arrive.relaxed.aligned;" ::: "memory"); }
__device__ __forceinline__ void cluster_wait() { asm volatile("barrier.cluster.wait.acquire.aligned;" ::: "memory"); }
__device__ __forceinline__ void side_bar() { asm volatile("bar.sync 1, 128;" ::: "memory"); }
__device__ __forceinline__ void tma2d_elect(uint32_t dst, const CUtensorMap* m, int c0, int c1, uint32_t bar) {
    asm volatile(ELECT "cp.async.bulk.tensor.2d.shared::cluster.global.mbarrier::complete_tx::bytes [%0], [%1, {%3,%4}], [%2];}"
                 ::"r"(dst), "l"(m), "r"(bar), "r"(c0), "r"(c1) : "memory");
}
__device__ __forceinline__ void tma2d_pair_elect(uint32_t dst, const CUtensorMap* m, int c0, int c1, uint32_t bar) {
    asm volatile(ELECT "cp.async.bulk.tensor.2d.shared::cluster.global.mbarrier::complete_tx::bytes.multicast::cluster"
                 " [%0], [%1, {%3,%4}], [%2], %5;}" ::"r"(dst), "l"(m), "r"(bar), "r"(c0), "r"(c1), "h"((uint16_t)3) : "memory");
}
__device__ __forceinline__ void tma3d_elect(uint32_t dst, const CUtensorMap* m, int row, int chunk, uint32_t bar) {
    asm volatile(ELECT "cp.async.bulk.tensor.3d.shared::cluster.global.mbarrier::complete_tx::bytes [%0], [%1, {%3,%4,%5}], [%2];}"
                 ::"r"(dst), "l"(m), "r"(bar), "r"(0), "r"(row), "r"(chunk) : "memory");
}
__device__ __forceinline__ void bulk_wait_read() {
    asm volatile("cp.async.bulk.commit_group; cp.async.bulk.wait_group.read 0;" ::: "memory");
    __syncwarp();
}
__device__ __forceinline__ void fence_proxy_async_smem() { asm volatile("fence.proxy.async.shared::cta;" ::: "memory"); }
__device__ __forceinline__ uint32_t ld_relaxed(const void* p) {
    uint32_t v;
    asm volatile("ld.relaxed.gpu.global.u32 %0, [%1];" : "=r"(v) : "l"(p) : "memory");
    return v;
}
__device__ __forceinline__ uint4 ld_relaxed4(const void* p) {
    uint4 v;
    asm volatile("ld.relaxed.gpu.global.v4.u32 {%0,%1,%2,%3}, [%4];" : "=r"(v.x), "=r"(v.y), "=r"(v.z), "=r"(v.w) : "l"(p) : "memory");
    return v;
}
__device__ __forceinline__ void red_inc_if(unsigned int* p, bool pred) {
    asm volatile("{.reg .pred p; setp.ne.b32 p, %1, 0; @p red.relaxed.gpu.global.add.u32 [%0], 1;}" ::"l"(p), "r"((int)pred) : "memory");
}
__device__ __forceinline__ uint32_t tagf(float v, uint32_t par) { return (__float_as_uint(v) & ~1u) | par; }
__device__ __forceinline__ uint4 wait_tags(const unsigned int* p, int bit, uint32_t par) {
    uint32_t n = 0;
    while (true) {
        const uint4 v = ld_relaxed4(p);
        const uint32_t m = par ? (v.x & v.y & v.z & v.w) : ~(v.x | v.y | v.z | v.w);
        if (__all_sync(0xffffffffu, (m >> bit) & 1u)) return v;
        __nanosleep(100);
        if (++n > SPIN_LIMIT) __trap();
    }
}
__device__ __forceinline__ void wait_counter(const unsigned int* p, uint32_t want) {
    uint32_t n = 0;
    while (!__all_sync(0xffffffffu, (int)(ld_relaxed(p) - want) >= 0)) {
        __nanosleep(200);
        if (++n > SPIN_LIMIT) __trap();
    }
    asm volatile("fence.acquire.gpu;" ::: "memory");
}
__device__ __forceinline__ uint32_t stale_tags(uint32_t a, uint32_t par) {
    uint32_t r;
    asm volatile("{.reg .b32 v<16>;\n"
                 "ld.shared.u32 v0, [%1]; ld.shared.u32 v1, [%1+256]; ld.shared.u32 v2, [%1+512]; ld.shared.u32 v3, [%1+768];\n"
                 "ld.shared.u32 v4, [%1+4096]; ld.shared.u32 v5, [%1+4352]; ld.shared.u32 v6, [%1+4608]; ld.shared.u32 v7, [%1+4864];\n"
                 "ld.shared.u32 v8, [%1+8192]; ld.shared.u32 v9, [%1+8448]; ld.shared.u32 v10, [%1+8704]; ld.shared.u32 v11, [%1+8960];\n"
                 "ld.shared.u32 v12, [%1+12288]; ld.shared.u32 v13, [%1+12544]; ld.shared.u32 v14, [%1+12800]; ld.shared.u32 v15, [%1+13056];\n"
                 "lop3.b32 v0, v0, v1, %2, 0x7e; lop3.b32 v2, v2, v3, %2, 0x7e; lop3.b32 v4, v4, v5, %2, 0x7e; lop3.b32 v6, v6, v7, %2, 0x7e;\n"
                 "lop3.b32 v8, v8, v9, %2, 0x7e; lop3.b32 v10, v10, v11, %2, 0x7e; lop3.b32 v12, v12, v13, %2, 0x7e; lop3.b32 v14, v14, v15, %2, 0x7e;\n"
                 "lop3.b32 v0, v0, v2, v4, 0xfe; lop3.b32 v6, v6, v8, v10, 0xfe; lop3.b32 v0, v0, v6, v12, 0xfe; or.b32 %0, v0, v14;}"
                 : "=r"(r) : "r"(a), "r"(par) : "memory");
    return r;
}
template <int OFF>
__device__ __forceinline__ uint4 ldg_nc(const void* p) {
    uint4 v;
    asm volatile("ld.global.nc.v4.u32 {%0,%1,%2,%3}, [%4+%5];" : "=r"(v.x), "=r"(v.y), "=r"(v.z), "=r"(v.w) : "l"(p), "n"(OFF));
    return v;
}
template <int OFF>
__device__ __forceinline__ void stg128(void* p, const uint4& v) {
    asm volatile("st.global.v4.u32 [%0+%5], {%1,%2,%3,%4};" ::"l"(p), "r"(v.x), "r"(v.y), "r"(v.z), "r"(v.w), "n"(OFF) : "memory");
}
template <int OFF>
__device__ __forceinline__ void sts128(uint32_t a, const uint4& v) {
    asm volatile("st.shared.v4.u32 [%0+%5], {%1,%2,%3,%4};" ::"r"(a), "r"(v.x), "r"(v.y), "r"(v.z), "r"(v.w), "n"(OFF) : "memory");
}
__device__ __forceinline__ uint4 lds128(uint32_t a) {
    uint4 v;
    asm volatile("ld.shared.v4.u32 {%0,%1,%2,%3}, [%4];" : "=r"(v.x), "=r"(v.y), "=r"(v.z), "=r"(v.w) : "r"(a) : "memory");
    return v;
}
template <int OFF>
__device__ __forceinline__ void red_bf16x8(void* p, uint32_t x, uint32_t y, uint32_t z, uint32_t w) {
    asm volatile("red.relaxed.gpu.global.add.noftz.v4.bf16x2 [%0+%5], {%1,%2,%3,%4};"
                 ::"l"(p), "r"(x), "r"(y), "r"(z), "r"(w), "n"(OFF) : "memory");
}
__device__ __forceinline__ void sched_cut() {
    asm volatile("{.reg .pred p; .reg .u64 t; .reg .u32 a, b;\n"
                 "C%=: mov.u64 t, %%clock64; mov.b64 {a, b}, t; setp.eq.u32 p, a, %0; @p bra C%=;}" ::"n"(0) : "memory");
}
__device__ __forceinline__ uint32_t pin(uint32_t v) { return __shfl_xor_sync(0xffffffffu, v, 0); }
template <class T>
__device__ __forceinline__ T* pin(T* p) { return (T*)__shfl_xor_sync(0xffffffffu, (unsigned long long)p, 0); }
__device__ __forceinline__ float selpf(float a, float b, bool p) {
    float r;
    asm("{.reg .pred q; setp.ne.b32 q, %3, 0; selp.f32 %0, %1, %2, q;}" : "=f"(r) : "f"(a), "f"(b), "r"((int)p));
    return r;
}
template <int N, int MASK, int SZ>
__device__ __forceinline__ void halve(float (&a)[SZ]) {
    const bool up = threadIdx.x & MASK;
#pragma unroll
    for (int j = 0; j < N; j++) a[j] = selpf(a[N + j], a[j], up) + __shfl_xor_sync(0xffffffffu, selpf(a[j], a[N + j], up), MASK);
}
__device__ __forceinline__ float bflo(uint32_t u) { return __uint_as_float(u << 16); }
__device__ __forceinline__ float bfhi(uint32_t u) { return __uint_as_float(u & 0xffff0000u); }
__device__ __forceinline__ uint32_t pack_bf16(float lo, float hi) {
    uint32_t r;
    asm("cvt.rn.bf16x2.f32 %0, %1, %2;" : "=r"(r) : "f"(hi), "f"(lo));
    return r;
}
__device__ __forceinline__ uint32_t hmul2_bf16(uint32_t a, uint32_t b) {
    uint32_t r;
    asm("mul.rn.bf16x2 %0, %1, %2;" : "=r"(r) : "r"(a), "r"(b));
    return r;
}
__device__ __forceinline__ float rbf(float v) { return bflo(pack_bf16(v, 0.f)); }
__device__ __forceinline__ float sigmoidf_(float v) { return __frcp_rn(1.0f + __expf(-v)); }

__device__ __forceinline__ void wg_fence() { asm volatile("wgmma.fence.sync.aligned;" ::: "memory"); }
__device__ __forceinline__ void wg_commit() { asm volatile("wgmma.commit_group.sync.aligned;" ::: "memory"); }
template <int N> __device__ __forceinline__ void wg_wait() { asm volatile("wgmma.wait_group.sync.aligned %0;" ::"n"(N) : "memory"); }
__device__ __forceinline__ uint64_t desc128(uint32_t lo) { return (uint64_t)lo | (0x40000040ull << 32); }
__device__ __forceinline__ uint64_t desc64(uint32_t lo) { return (uint64_t)lo | (0x80000020ull << 32); }
__device__ __forceinline__ void fence_regs(float (&d)[64]) {
#pragma unroll
    for (int i = 0; i < 64; i++) asm volatile("" : "+f"(d[i])::"memory");
}
template <int TB>
__device__ __forceinline__ void wgmma128(float (&d)[64], uint64_t da, uint64_t db, int scaleD) {
    asm volatile(
        "{ .reg .pred p; setp.ne.b32 p, %66, 0;\n"
        "wgmma.mma_async.sync.aligned.m64n128k16.f32.bf16.bf16 "
        "{%0,%1,%2,%3,%4,%5,%6,%7,%8,%9,%10,%11,%12,%13,%14,%15,%16,%17,%18,%19,%20,%21,%22,%23,%24,%25,%26,%27,%28,%29,%30,%31,"
        "%32,%33,%34,%35,%36,%37,%38,%39,%40,%41,%42,%43,%44,%45,%46,%47,%48,%49,%50,%51,%52,%53,%54,%55,%56,%57,%58,%59,%60,%61,%62,%63}, "
        "%64, %65, p, 1, 1, 0, %67;\n}"
        : "+f"(d[0]), "+f"(d[1]), "+f"(d[2]), "+f"(d[3]), "+f"(d[4]), "+f"(d[5]), "+f"(d[6]), "+f"(d[7]),
          "+f"(d[8]), "+f"(d[9]), "+f"(d[10]), "+f"(d[11]), "+f"(d[12]), "+f"(d[13]), "+f"(d[14]), "+f"(d[15]),
          "+f"(d[16]), "+f"(d[17]), "+f"(d[18]), "+f"(d[19]), "+f"(d[20]), "+f"(d[21]), "+f"(d[22]), "+f"(d[23]),
          "+f"(d[24]), "+f"(d[25]), "+f"(d[26]), "+f"(d[27]), "+f"(d[28]), "+f"(d[29]), "+f"(d[30]), "+f"(d[31]),
          "+f"(d[32]), "+f"(d[33]), "+f"(d[34]), "+f"(d[35]), "+f"(d[36]), "+f"(d[37]), "+f"(d[38]), "+f"(d[39]),
          "+f"(d[40]), "+f"(d[41]), "+f"(d[42]), "+f"(d[43]), "+f"(d[44]), "+f"(d[45]), "+f"(d[46]), "+f"(d[47]),
          "+f"(d[48]), "+f"(d[49]), "+f"(d[50]), "+f"(d[51]), "+f"(d[52]), "+f"(d[53]), "+f"(d[54]), "+f"(d[55]),
          "+f"(d[56]), "+f"(d[57]), "+f"(d[58]), "+f"(d[59]), "+f"(d[60]), "+f"(d[61]), "+f"(d[62]), "+f"(d[63])
        : "l"(da), "l"(db), "r"(scaleD), "n"(TB));
}

__device__ __forceinline__ uint32_t get_role(uint32_t& smid) {
    uint32_t role;
    asm volatile("mov.u32 %0, %%smid;" : "=r"(smid));
    asm("{.reg .pred p, q; .reg .u32 t, a, b; shr.u32 t, %1, 1; mad.lo.u32 a, t, 293, -928; shr.u32 a, a, 8; mad.lo.u32 b, t, 8, -464;"
        " setp.lt.u32 p, t, 32; setp.lt.u32 q, t, 62; selp.u32 a, a, b, q; selp.u32 %0, t, a, p;}" : "=r"(role) : "r"(smid));
    return role;
}
__device__ __forceinline__ int tile_of_step(int step, int own) {
    const int u = step >= 17 ? step - 17 - (step > PS1) : step - 2;
    int e = u + (u >= (own & 14) ? 2 : 0);
    if (step == 16 || step == PS1) e = own ^ 1;
    if (step < 2) e = own;
    return e + (step >= 17 || step == 1 ? 16 : 0);
}
__device__ __forceinline__ uint32_t router_key(float score, int row) {
    const float r = score + 0.0f;
    uint32_t u = pack_bf16(r, 0.f) & 0xffffu;
    u = (u & 0x8000u) ? (~u & 0xffffu) : (u | 0x8000u);
    if (r != r) u = 0;
    return (u << 16) | (uint32_t)(0x7fff - row);
}

#define g_fb_h ((float*)g_s.part)
#define g_fb_upd (g_fb_h + 2048)
#define g_fb_gate (g_fb_h + 4096)
#define g_fb_keys (g_s.part + 8192)
__global__ void fb_hidden(const bf16* x, const bf16* dre, const bf16* dim, const bf16* gw, const bf16* wr) {
    __shared__ float xs[D_];
    const int s = blockIdx.x, t = threadIdx.x;
    xs[t] = __bfloat162float(x[s * D_ + t]);
    __syncthreads();
    float a = 0.f, b = 0.f;
    for (int d = 0; d < D_; d++) { a = fmaf(xs[d], __bfloat162float(dre[t * D_ + d]), a); b = fmaf(xs[d], __bfloat162float(dim[t * D_ + d]), b); }
    ((bf16*)g_s.ab)[s * 1024 + t] = __float2bfloat16(a);
    ((bf16*)g_s.ab)[s * 1024 + 512 + t] = __float2bfloat16(b);
    if (t == 0) {
        float u = 0.f, v = 0.f;
        for (int d = 0; d < D_; d++) { u = fmaf(xs[d], __bfloat162float(gw[d]), u); v = fmaf(xs[d], __bfloat162float(wr[d]), v); }
        g_fb_gate[s] = sigmoidf_(u);
        g_fb_keys[s] = router_key(v, s);
    }
}
__device__ uint32_t fb_best() {
    uint32_t k = 0;
    for (int i = 0; i < S_; i++) k = max(k, g_fb_keys[i]);
    return k;
}
__global__ void fb_ffn1(const bf16* x, const bf16* wg, const bf16* wu) {
    const int f = blockIdx.x * blockDim.x + threadIdx.x, idx = 0x7fff - (int)(fb_best() & 0x7fffu);
    float a = 0.f, b = 0.f;
    for (int d = 0; d < D_; d++) {
        const float xv = __bfloat162float(x[idx * D_ + d]);
        a = fmaf(xv, __bfloat162float(wg[d * F_ + f]), a); b = fmaf(xv, __bfloat162float(wu[d * F_ + f]), b);
    }
    g_fb_h[f] = a * sigmoidf_(a) * b;
}
__global__ void fb_ffn2(const bf16* wd) {
    const int e = blockIdx.x * blockDim.x + threadIdx.x;
    const uint32_t u = fb_best() >> 16, rb = (u & 0x8000u) ? (u & 0x7fffu) : (~u & 0xffffu);
    float a = 0.f;
    for (int f = 0; f < F_; f++) a = fmaf(g_fb_h[f], __bfloat162float(wd[f * D_ + e]), a);
    g_fb_upd[e] = a * sigmoidf_(__uint_as_float(rb << 16));
}
__global__ void fb_seq(const bf16* x, const bf16* cre, const bf16* cim, bf16* out) {
    __shared__ float c[2][S_];
    __shared__ int idx;
    const int t = blockIdx.x, e = threadIdx.x;
    for (int i = e; i < S_; i += D_) { c[0][i] = __bfloat162float(cre[t * S_ + i]); c[1][i] = __bfloat162float(cim[t * S_ + i]); }
    if (e == 0) idx = 0x7fff - (int)(fb_best() & 0x7fffu);
    __syncthreads();
    float y = 0.f;
    for (int s = 0; s < S_; s++)
        y += c[0][s] * __bfloat162float(((const bf16*)g_s.ab)[s * 1024 + e]) - c[1][s] * __bfloat162float(((const bf16*)g_s.ab)[s * 1024 + 512 + e]);
    const float g = g_fb_gate[t];
    out[t * D_ + e] = __float2bfloat16(g * y + (1.f - g) * (__bfloat162float(x[t * D_ + e]) + (t == idx ? g_fb_upd[e] : 0.f)));
}

__device__ __forceinline__ void spare_job(const Params& p, unsigned char* smem, int sp, uint32_t tstart) {
    const int tid = threadIdx.x, warp = tid >> 5, lane = tid & 31;
    const uint32_t e1 = *(volatile unsigned int*)&p.s->epoch[NCTA + sp] + 1u;
    const uint32_t par = e1 & 1u;
    uint32_t* sel = (uint32_t*)smem;
    float* acc = (float*)(smem + 1024);
    __syncthreads();
    if (tid == 0) *(volatile unsigned int*)&p.s->epoch[NCTA + sp] = e1;
    sleep_until<500>(tstart + SUM_T0);
    if (warp < 14) {
        uint32_t n = 0;
        while ((int)(ld_relaxed(p.s->phint + (sp * 16 + warp) * 8) - e1 * 8u) < 0) {
            __nanosleep(100);
            if (++n > SPIN_LIMIT) __trap();
        }
        const unsigned int* src = p.s->part + warp * 4 * D_ + sp * 128 + lane * 4;
        uint4 v[4];
        while (true) {
            uint32_t bad = 0;
#pragma unroll
            for (int i = 0; i < 4; i++) v[i] = ld_relaxed4(src + i * D_);
#pragma unroll
            for (int i = 0; i < 4; i++) bad |= (v[i].x ^ par) | (v[i].y ^ par) | (v[i].z ^ par) | (v[i].w ^ par);
            if (!__any_sync(0xffffffffu, bad & 1u)) break;
            if (++n > SPIN_LIMIT) __trap();
        }
        float4 s = make_float4(0.f, 0.f, 0.f, 0.f);
#pragma unroll
        for (int i = 0; i < 4; i++) {
            s.x += __uint_as_float(v[i].x); s.y += __uint_as_float(v[i].y);
            s.z += __uint_as_float(v[i].z); s.w += __uint_as_float(v[i].w);
        }
        *(float4*)&acc[warp * 128 + lane * 4] = s;
    } else if (warp == 14) {
        const uint4 k4 = wait_tags(p.s->keys + lane * 4, 15, par);
        const uint32_t k = __reduce_max_sync(0xffffffffu, max(max(k4.x, k4.y), max(k4.z, k4.w)));
        const int idx = 0x7fff - (int)(k & 0x7fffu);
        const uint4 g4 = wait_tags(p.s->gate + (idx & ~3), 0, par);
        const uint32_t gw = (idx & 2) ? ((idx & 1) ? g4.w : g4.z) : ((idx & 1) ? g4.y : g4.x);
        const uint32_t u = k >> 16;
        const uint32_t rb = (u & 0x8000u) ? (u & 0x7fffu) : (~u & 0xffffu);
        const float og = 1.f - __uint_as_float(gw & ~1u), rs = sigmoidf_(__uint_as_float(rb << 16));
        if (lane == 0) { sel[0] = idx; sel[1] = pack_bf16(og, og); sel[2] = pack_bf16(rs, rs); }
        sleep_until<500>(tstart + SUM_T0 + 3000);
        wait_counter(p.s->ready + (idx >> 7) * 32, e1 * 8u);
    }
    __syncthreads();
    if (tid < 64) {
        float t0 = 0.f, t1 = 0.f;
#pragma unroll
        for (int i = 0; i < 14; i++) {
            const float2 z = *(const float2*)&acc[i * 128 + tid * 2];
            t0 += z.x; t1 += z.y;
        }
        asm volatile("red.relaxed.gpu.global.add.noftz.bf16x2 [%0], %1;" ::"l"(p.out + sel[0] * D_ + sp * 128 + tid * 2),
                     "r"(hmul2_bf16(sel[1], hmul2_bf16(sel[2], pack_bf16(t0, t1)))) : "memory");
    }
}

__host__ __device__ constexpr int off_d(int c) { return (c < 2 ? 1 : c / 2 + 2) * REGION + (c & 1) * 16384; }
__host__ __device__ constexpr int off_xe(int c) { return (c < 2 ? 6 * REGION : c < 4 ? 16384 : c < 6 ? 0 : 6 * REGION + 16384) + (c & 1) * 8192; }
__host__ __device__ constexpr int off_xl(int c) { return c < 4 ? 2 * REGION + c * 8192 : off_xe(c - 4); }

__global__ void __cluster_dims__(2, 1, 1) __launch_bounds__(NTHREADS, 1)
fused_kernel(const __grid_constant__ Params p) {
    extern __shared__ __align__(1024) unsigned char smem[];
    const uint32_t tstart = clk();
    const uint32_t sb = smem_u32(smem);
    const int tid = threadIdx.x, lane = tid & 31;
    const int rank = blockIdx.x & 1;
    uint32_t t1 = 0;
    if (__any_sync(0xffffffffu, tid == 0)) {
        uint32_t s0;
        const uint32_t r0 = get_role(s0);
        mbar_init_elect(sb + B_F, 1);
        if (r0 < 64) {
#pragma unroll
            for (int c = 0; c < 2; c++) {
                if (c) {
                    spin_until(t1 + PACE);
                    mbar_init_elect(sb + B_F + 8, 1);
                }
                tma3d_elect(sb + off_d(c), &p.mDre + ((r0 >> 2) & 1), (r0 & 24) * 16, c, sb + B_F + 8 * c);
                tma3d_elect(sb + off_xe(c), &p.mX1, (r0 & 3) * 256 + (r0 & 32) * 4 + rank * 64, c, sb + B_F + 8 * c);
                mbar_expect_tx_elect(sb + B_F + 8 * c, 24576);
                if (!c) t1 = clk();
            }
        }
    }
    const int warp = __shfl_sync(0xffffffffu, tid >> 5, 0);
    uint32_t smid;
    const uint32_t role = get_role(smid);
    const int gpc = role & 7;
    const int tn = (role >> 3) & 3;
    const int comp = gpc >> 2;
    const int own = (gpc & 3) * 4 + ((role >> 5) & 1) * 2 + rank;
    const int blk = comp * 4 + tn;
    const int cta = gpc * 16 + (role >> 3) * 2 + rank;
    const bool ffn = cta < FFN_CTAS;
    uint32_t epoch = 0;
    if (warp != 0) {
        const uint32_t b1 = sb + B_F + 8 * warp;
        mbar_init_elect(warp < 2 ? b1 + 360 : b1, 1);
        if (warp >= 2 && warp < 5) mbar_init_elect(b1 + 360, warp < 4 ? 1 : 4);
        mbar_init_elect(b1 + 120, warp < 7 ? 5 : warp < 14 ? 4 : warp - 12);
        mbar_init_elect(b1 + 240, 1);
        if (warp == 9 || warp == 15) mbar_expect_tx_elect(b1 + 240, warp == 9 ? 2048 : 4);
        asm volatile("fence.mbarrier_init.release.cluster;" ::: "memory");
        if (tid == 128 && role < 64) epoch = *(volatile unsigned int*)&p.s->epoch[cta];
    }
    if (role >= 64) {
        spare_job(p, smem, smid & 3, tstart);
        return;
    }
    __syncthreads();
    cluster_arrive();
    if (warp == 0) {
#pragma unroll
        for (int c = 2; c < 8; c++) {
            spin_until(t1 + c * PACE);
            tma3d_elect(sb + off_d(c), &p.mDre + comp, tn * 128, c, sb + B_F + 8 * c);
            tma3d_elect(sb + off_xe(c), &p.mX1, own * 64, c, sb + B_F + 8 * c);
            mbar_expect_tx_elect(sb + B_F + 8 * c, 24576);
        }
        tma3d_elect(sb + off_xl(0), &p.mX2, own * 64 + 1024, 0, sb + B_G0);
        mbar_expect_tx_elect(sb + B_G0, 16384);
        spin_until(t1 + 8 * PACE);
        tma3d_elect(sb + off_xl(2), &p.mX2, own * 64 + 1024, 2, sb + B_G2);
        mbar_expect_tx_elect(sb + B_G2, 16384);
        if (tn < 2)
            asm volatile(ELECT "cp.async.bulk.prefetch.tensor.3d.L2.global [%0, {%1,%2,%3}];}"
                         ::"l"(&p.mX2), "r"(0), "r"(own * 64 + 1024), "r"(4 + 2 * tn) : "memory");
    }

    if (warp < 4) {
        const int tab = tile_of_step(lane, own);
        const uint32_t bdst = sb + 16384 + rank * 8192;
        const int brow = blk * 4096 + rank * 64;
        if (warp == 0) {
            mbar_spin(sb + B_XE, 0);
            tma3d_elect(sb + off_xl(4), &p.mX2, own * 64 + 1024, 4, sb + B_G4);
            tma3d_elect(sb + off_xl(6), &p.mX2, own * 64 + 1024, 6, sb + B_G4);
            mbar_expect_tx_elect(sb + B_G4, 32768);
#define LOAD_A() const int e = __shfl_sync(0xffffffffu, tab, step);                                             \
                 const uint32_t bar = sb + 8 * slot;                                                            \
                 mbar_spin(bar + B_EMPTY, ph);                                                                  \
                 tma2d_elect(sb + slot * REGION, &p.mCre + comp, e * 64, own * 128, bar + B_FULL);              \
                 mbar_expect_tx_elect(bar + B_FULL, 16384)
            uint32_t slot = 0, ph = 0;
            int step = 0;
#pragma unroll 1
            for (; step < NSTAGE; step++, slot++) {
                LOAD_A();
                if (step == 2 || step == 3) spin_until(clk() + A_GAP);
            }
            slot = 0; ph = 1;
#pragma unroll 1
            for (int h = 0; h < 3; h++) {
                const int last = h == 0 ? 16 : h == 1 ? PS1 : 32 - NA;
#pragma unroll 1
                for (; step < last; step++) {
                    LOAD_A();
                    tma2d_pair_elect(bdst + slot * REGION, &p.mAB, 0, brow + e * 128, bar + B_BL);
                    mbar_expect_tx_elect(bar + B_BL, 16384);
                    if (++slot == NSTAGE) { slot = 0; ph ^= 1; }
                }
                if (h == 2) break;
                LOAD_A();
                tma2d_elect(bdst + slot * REGION, &p.mAB, 0, brow + e * 128, bar + B_BL);
                tma2d_elect((bdst ^ 8192) + slot * REGION, &p.mAB, 0, (brow ^ 64) + e * 128, bar + B_BL);
                mbar_expect_tx_elect(bar + B_BL, 16384);
                step++;
                if (++slot == NSTAGE) { slot = 0; ph ^= 1; }
            }
            mbar_spin(sb + B_LOW, 0);
            uint32_t aslot = 6;
#pragma unroll 1
            for (; step < 32; step++) {
                const int e = __shfl_sync(0xffffffffu, tab, step);
                const uint32_t bar = sb + 8 * slot;
                tma2d_elect(sb + aslot * REGION, &p.mCre + comp, e * 64, own * 128, bar + B_FULL);
                mbar_expect_tx_elect(bar + B_FULL, 16384);
                mbar_expect_tx_elect(bar + B_BL, 16384);
                mbar_spin(bar + B_EMPTY, ph);
                tma2d_pair_elect(bdst + slot * REGION, &p.mAB, 0, brow + e * 128, bar + B_BL);
                aslot = slot;
                if (++slot == NSTAGE) { slot = 0; ph ^= 1; }
            }
        } else if (warp == 1) {
            if (lane < 4) asm volatile("prefetch.tensormap [%0];" ::"l"(&p.mCre + lane) : "memory");
            __syncwarp();
            cluster_wait();
            if (lane == 0)
                asm volatile("st.async.weak.shared::cluster.mbarrier::complete_tx::bytes.u32 [%0], %1, [%2];"
                             ::"r"(mapa(sb + M_ROLE, rank ^ 1)), "r"(role), "r"(mapa(sb + B_ROLE, rank ^ 1)) : "memory");
            mbar_wait_cluster(sb + B_ROLE, 0);
            if (*(volatile uint32_t*)(smem + M_ROLE) != role) __trap();
            mbar_wait(sb + B_EPOCH, 0);
            const uint32_t want = (*(volatile uint32_t*)(smem + M_EPOCH) + 1u) * 4u;
            const int eh = __shfl_sync(0xffffffffu, tab, 2 + (lane & 3));
            const unsigned int* hp = p.s->hint + (blk * 4 + (eh >> 1)) * 32 + (eh & 1);
            uint32_t seen = __ballot_sync(0xffffffffu, ld_relaxed(hp) == want);
            int rows[4];
#pragma unroll
            for (int i = 0; i < 4; i++) {
                rows[i] = brow + __shfl_sync(0xffffffffu, tab, 2 + i) * 128;
                mbar_expect_tx_elect(sb + B_BL + 8 * (2 + i), 16384);
            }
            mbar_wait(sb + B_EMPTY + 8 * 3, 0);
            mbar_spin(sb + B_EMPTY + 8 * 2, 0);
            uint32_t t3 = 0;
#pragma unroll
            for (int i = 0; i < 4; i++) {
                while (!((seen >> i) & 1u)) seen = __ballot_sync(0xffffffffu, ld_relaxed(hp) == want);
                if (i) spin_until(t3 + B_GAP);
                t3 = clk();
                if (i >= 2) mbar_spin(sb + B_EMPTY + 8 * (2 + i), 0);
                tma2d_pair_elect(bdst + (2 + i) * REGION, &p.mAB, 0, rows[i], sb + B_BL + 8 * (2 + i));
            }
            mbar_wait(sb + B_FREE, 0);
            unsigned char* gdst = p.s->ab + (blk * 32 + own + 16) * 16384;
            t3 = clk();
#pragma unroll 1
            for (int i = 0; i < 16; i++) {
                sleep_until<20>(t3);
                t3 += LATE_GAP;
                asm volatile(ELECT "cp.async.bulk.global.shared::cta.bulk_group [%0], [%1], 1024;}"
                             ::"l"(gdst + i * 1024), "r"(sb + 6 * REGION + i * 1024) : "memory");
            }
            bulk_wait_read();
            mbar_arrive_elect(sb + B_FREE + 8);
            mbar_wait(sb + B_PUB, 0);
            if (lane == 0) {
                asm volatile("fence.proxy.async.global;" ::: "memory");
                asm volatile("red.release.gpu.global.add.u32 [%0], 1;" ::"l"(p.s->ready + (cta >> 3) * 32) : "memory");
            }
            __syncwarp();
            __nanosleep(INIT_NS);
            wait_counter(p.s->ready + own * 32, want * 2u);
            mbar_arrive_elect(sb + B_INIT);
        } else {
            mbar_arrive_elect(sb + B_BL + 8 * (warp & 1));
            uint32_t k = warp == 3 ? 0 : 12;
#define PREFETCH_W() {                                                                                          \
                const char* src = (k >= 8 ? (const char*)p.wd + ((cta >> 5) * 2 + (k >> 1) - 4) * 229376        \
                                          : (const char*)((cta & 32) ? p.wu : p.wg) + ((cta >> 6) * 4 + (k >> 1)) * 229376) \
                                  + ((cta & 31) * 2 + (k & 1)) * 3584;                                          \
                asm volatile(ELECT "cp.async.bulk.prefetch.L2.global [%0], 3584;}" ::"l"(src) : "memory");      \
                k++; }
#pragma unroll 1
            while (k < PF_N0) {
                sleep_until<50>(tstart + PF_T0 + k * PF_GAP);
                __syncwarp();
                PREFETCH_W();
            }
            mbar_wait(sb + B_EPOCH, 0);
            const uint32_t par = (*(volatile uint32_t*)(smem + M_EPOCH) + 1u) & 1u;
            const uint32_t a0 = sb + 16384 + (lane >> 3) * 1028 + ((lane >> 2) & 1) * 144 + (lane & 3) * 32;
            const uint32_t retry = sb + B_RETRY + (warp & 1) * 240;
            uint32_t slot = warp, ph = 0, rph = 0;
            uint32_t j = ffn ? warp & 1 : 12;
#pragma unroll 1
            for (int step = warp; step < 32 || j < 12; step += 2) {
                if (step < 32) {
                    const uint32_t bar = sb + 8 * slot;
                    mbar_wait(bar + B_BL, ph);
#pragma unroll 1
                    while (__any_sync(0xffffffffu, stale_tags(a0 + slot * REGION, par) & 1u)) {
                        const int row = blk * 4096 + __shfl_sync(0xffffffffu, tab, step) * 128;
                        mbar_expect_tx_elect(retry, 16384);
                        tma2d_elect(sb + slot * REGION + 16384, &p.mAB, 0, row, retry);
                        tma2d_elect(sb + slot * REGION + 24576, &p.mAB, 0, row + 64, retry);
                        mbar_spin(retry, rph);
                        rph ^= 1u;
                    }
                    mbar_arrive_elect<4>(bar + B_FULL);
                }
                if (j < 12 && step >= FFN_S0 + j * FFN_W / 4 && __any_sync(0xffffffffu, mbar_test(sb + B_FREE + 2 * (j & 12), 0))) {
                    const uint32_t fb = sb + B_FFN + 4 * (j & 6);
                    if (!(j & 1)) mbar_expect_tx_elect(fb, 8192);
                    tma2d_elect(sb + 6 * REGION + ((j + 4) & 7) * 4096, j < 8 ? &p.mWg + (j & 1) : &p.mWd,
                                j < 8 ? (cta >> 1) * 32 : rank * 256, j < 8 ? rank * 256 + (j >> 1) * 64 : (cta >> 1) * 32 + j * 8 - 64, fb);
                    j += 2;
                }
                if (k < 12) PREFETCH_W();
                slot += 2;
                if (slot >= NSTAGE) { slot -= NSTAGE; ph ^= 1; }
            }
        }
    } else if (warp < 8) {
        const int t = tid - 128, w = warp - 4;
        if (t == 0) {
            *(volatile uint32_t*)(smem + M_EPOCH) = epoch;
            *(volatile unsigned int*)&p.s->epoch[cta] = epoch + 1;
        }
        mbar_arrive_if(sb + B_EPOCH, t == 0);
        const uint4 gw0 = ldg_nc<0>(p.gate_w + lane * 8), gw1 = ldg_nc<512>(p.gate_w + lane * 8);
        const uint4 rw0 = ldg_nc<0>(p.w_r + lane * 8), rw1 = ldg_nc<512>(p.w_r + lane * 8);
        mbar_wait(sb + B_EPOCH, 0);
        const uint32_t par = (*(volatile uint32_t*)(smem + M_EPOCH) + 1u) & 1u;
        mbar_wait(sb + B_F + 8 * ROUTER_C, 0);
        const int row0 = cta * 16 + w * 4;
        uint4 xr[8];
        {
            const char* xp = (const char*)p.x + (uint32_t)row0 * (D_ * 2) + lane * 16;
            xr[0] = ldg_nc<0>(xp);    xr[1] = ldg_nc<512>(xp);  xr[2] = ldg_nc<1024>(xp); xr[3] = ldg_nc<1536>(xp);
            xr[4] = ldg_nc<2048>(xp); xr[5] = ldg_nc<2560>(xp); xr[6] = ldg_nc<3072>(xp); xr[7] = ldg_nc<3584>(xp);
            float a[8];
#pragma unroll
            for (int i = 0; i < 4; i++) {
                const uint32_t xv[8] = {xr[2 * i].x, xr[2 * i].y, xr[2 * i].z, xr[2 * i].w,
                                        xr[2 * i + 1].x, xr[2 * i + 1].y, xr[2 * i + 1].z, xr[2 * i + 1].w};
                const uint32_t gv[8] = {gw0.x, gw0.y, gw0.z, gw0.w, gw1.x, gw1.y, gw1.z, gw1.w};
                const uint32_t rv[8] = {rw0.x, rw0.y, rw0.z, rw0.w, rw1.x, rw1.y, rw1.z, rw1.w};
                float u = 0.f, v = 0.f;
#pragma unroll
                for (int j = 0; j < 8; j++) {
                    const uint32_t pr = hmul2_bf16(xv[j], gv[j]);
                    u += bflo(pr); u += bfhi(pr);
                    v = fmaf(bflo(xv[j]), bflo(rv[j]), v); v = fmaf(bfhi(xv[j]), bfhi(rv[j]), v);
                }
                a[i] = u; a[4 + i] = v;
            }
            mbar_wait(sb + B_EARLY, 0);
            halve<4, 16>(a); halve<2, 8>(a); halve<1, 4>(a);
            a[0] += __shfl_xor_sync(0xffffffffu, a[0], 1);
            a[0] += __shfl_xor_sync(0xffffffffu, a[0], 2);
            const int row = row0 + ((lane >> 2) & 3);
            const float gate = rbf(sigmoidf_(rbf(a[0])));
            if (lane < 16 && (lane & 3) == 0)
                asm volatile("st.relaxed.gpu.global.u32 [%0], %1;" ::"l"(&p.s->gate[row]), "r"(tagf(gate, par)) : "memory");
            const uint32_t best = __reduce_max_sync(0xffffffffu, lane >= 16 ? router_key(a[0], row) : 0u);
            if (lane == 0) *(volatile uint32_t*)(smem + M_KEY + w * 4) = best;
            side_bar();
            if (t < 8) {
                const uint4 k = *(const uint4*)(smem + M_KEY);
                asm volatile("{.reg .b32 old; atom.relaxed.gpu.global.exch.b32 old, [%0], %1;}" ::"l"(&p.s->keys[t * NCTA + cta]),
                             "r"(max(max(k.x, k.y), max(k.z, k.w)) | (par << 15)) : "memory");
            }
            const uint32_t og = pack_bf16(1.f - gate, 1.f - gate);
#pragma unroll
            for (int i = 0; i < 8; i++) {
                const uint32_t o = __shfl_sync(0xffffffffu, og, 4 * (i >> 1));
                xr[i] = make_uint4(hmul2_bf16(o, xr[i].x), hmul2_bf16(o, xr[i].y), hmul2_bf16(o, xr[i].z), hmul2_bf16(o, xr[i].w));
            }
        }
        mbar_wait(sb + B_FREE, 0);
        __nanosleep(KEY_NS);
        if (w == 0) {
            const uint4 k4 = wait_tags(p.s->keys + gpc * NCTA + lane * 4, 15, par);
            const uint32_t k = __reduce_max_sync(0xffffffffu, max(max(k4.x, k4.y), max(k4.z, k4.w)));
            sts128<M_XS>(sb + lane * 16, ldg_nc<0>(p.x + (0x7fff - (k & 0x7fffu)) * D_ + rank * 256 + lane * 8));
        } else if (w == 1) {
            const uint4 g4 = wait_tags(p.s->gate + own * 128 + lane * 4, 0, par);
            const uint32_t sg = comp ? 0x80000000u : 0u;
            sts128<M_G>(sb + lane * 16, make_uint4((g4.x & ~1u) ^ sg, (g4.y & ~1u) ^ sg, (g4.z & ~1u) ^ sg, (g4.w & ~1u) ^ sg));
            mbar_arrive_warp(sb + B_GATE);
        }
        side_bar();
        char* op = (char*)p.out + (uint32_t)row0 * (D_ * 2) + lane * 16;
        float a[16];
#pragma unroll
        for (int i = 0; i < 16; i++) a[i] = 0.f;
#pragma unroll 1
        for (int i = 0; i < 4; i++) {
            if (i == 2) {
                mbar_wait(sb + B_FREE + 8, 0);
                const uint32_t t2 = clk() + w * (INIT_GAP / 4);
#pragma unroll
                for (int j = 0; j < 8; j++) {
                    sleep_until<20>(t2 + j * INIT_GAP);
                    *(uint4*)(op + j * 512) = xr[j];
                }
                mbar_arrive_warp(sb + B_PUB);
            }
            if (ffn) {
                const float xs0 = __bfloat162float(((const bf16*)(smem + M_XS))[64 * i + (t >> 2)]);
                const float xs1 = __bfloat162float(((const bf16*)(smem + M_XS))[64 * i + 32 + (t >> 2)]);
                const uint32_t wa = sb + 6 * REGION + (i ^ 2) * 8192 + t * 16;
                mbar_wait(sb + B_FFN + 8 * i, 0);
                const uint4 v0 = lds128(wa), v1 = lds128(wa + 4096), v2 = lds128(wa + 2048), v3 = lds128(wa + 6144);
                const uint32_t w0[8] = {v0.x, v0.y, v0.z, v0.w, v1.x, v1.y, v1.z, v1.w};
                const uint32_t w1[8] = {v2.x, v2.y, v2.z, v2.w, v3.x, v3.y, v3.z, v3.w};
#pragma unroll
                for (int k = 0; k < 8; k++) {
                    a[2 * k] = fmaf(xs1, bflo(w1[k]), fmaf(xs0, bflo(w0[k]), a[2 * k]));
                    a[2 * k + 1] = fmaf(xs1, bfhi(w1[k]), fmaf(xs0, bfhi(w0[k]), a[2 * k + 1]));
                }
                if (i == 1) {
                    side_bar();
                    mbar_arrive_if(sb + B_FREE + 16, t == 0);
                }
            }
        }
        if (!ffn) {
            mbar_arrive_warp(sb + B_LOW);
            return;
        }
        halve<8, 16>(a); halve<4, 8>(a); halve<2, 4>(a);
        const uint32_t ho = (lane >> 4) * 128 + (lane & 3) * 32 + ((lane >> 2) & 3) * 8;
        cluster_wait();
#pragma unroll
        for (int k = 0; k < 2; k++)
            asm volatile("st.async.weak.shared::cluster.mbarrier::complete_tx::bytes.v2.f32 [%0], {%1,%2}, [%3];"
                         ::"r"(mapa(sb + (k ? 6 * REGION + w * 512 : M_HX + w * 256) + ho, rank ^ k ^ 1)), "f"(a[0]), "f"(a[1]),
                           "r"(mapa(sb + B_HX, rank ^ k ^ 1)) : "memory");
        mbar_wait_cluster(sb + B_HX, 0);
        const float *hx = (const float*)(smem + M_HX) + lane, *hy = (const float*)(smem + 6 * REGION) + lane;
        const float gs = rbf(((hx[0] + hy[0]) + (hx[64] + hy[128])) + ((hx[128] + hy[256]) + (hx[192] + hy[384])));
        const float us = rbf(((hx[32] + hy[32]) + (hx[96] + hy[160])) + ((hx[160] + hy[288]) + (hx[224] + hy[416])));
        float* hrow = (float*)(smem + M_XS) + w * 32;
        hrow[lane] = rbf(rbf(gs * sigmoidf_(gs)) * us);
        fence_proxy_async_smem();
        mbar_arrive_warp(sb + B_LOW);
        float o0 = 0.f, o1 = 0.f;
#pragma unroll 1
        for (int i = 0; i < 2; i++) {
            float4 hv[4];
            uint32_t vd[16];
#pragma unroll
            for (int k = 0; k < 4; k++) hv[k] = *(const float4*)&hrow[i * 16 + k * 4];
            mbar_wait(sb + B_FFN + 8 * i, 1);
#pragma unroll
            for (int k = 0; k < 16; k++) vd[k] = *(const volatile uint32_t*)(smem + 6 * REGION + 16384 + i * 8192 + k * 512 + t * 4);
#pragma unroll
            for (int k = 0; k < 4; k++) {
                o0 = fmaf(hv[k].x, bflo(vd[4 * k]), o0);     o1 = fmaf(hv[k].x, bfhi(vd[4 * k]), o1);
                o0 = fmaf(hv[k].y, bflo(vd[4 * k + 1]), o0); o1 = fmaf(hv[k].y, bfhi(vd[4 * k + 1]), o1);
                o0 = fmaf(hv[k].z, bflo(vd[4 * k + 2]), o0); o1 = fmaf(hv[k].z, bfhi(vd[4 * k + 2]), o1);
                o0 = fmaf(hv[k].w, bflo(vd[4 * k + 3]), o0); o1 = fmaf(hv[k].w, bfhi(vd[4 * k + 3]), o1);
            }
        }
        asm volatile("st.relaxed.gpu.global.v2.u32 [%0], {%1,%2};" ::"l"(&p.s->part[(cta >> 1) * D_ + rank * 256 + t * 2]),
                     "r"(tagf(o0, par)), "r"(tagf(o1, par)) : "memory");
        red_inc_if(p.s->phint + ((rank * 2 + (w >> 1)) * 16 + (cta >> 3)) * 8 + lane, lane == 0);
    } else {
        const int wg = (warp >> 2) - 2, wq = warp & 3;
        const uint32_t sbd = ((sb & 0x3FFFF) >> 4) + 0x10000;
        const bool lead = (tid & 127) == 0;
        const bool lead0 = lead && !wg, lead1 = lead && wg;
        const int q = lane & 3;
        float acc[64];
        const uint32_t rE = mapa(sb + B_EMPTY, rank ^ 1);
#define RELEASE(n, slot, pred) release_pair<n>(sb + B_EMPTY + 8 * (slot), rE + 8 * (slot), pred)
        const uint32_t ioff = wq * 4096 + (lane >> 2) * 64 + ((q ^ (lane >> 3)) << 4);
        const uint32_t sdst = pin(sb + 6 * REGION + (wg ? 0 : 16384) + ioff);
        unsigned char* gdst = pin(p.s->ab + (blk * 32 + own) * 16384 + ioff);
        unsigned int* hint = pin(p.s->hint + (blk * 4 + ((own >> 1) & 3)) * 32 + rank + lane);
        uint32_t par = 0;
#define GET_PAR() mbar_spin(sb + B_EPOCH, 0); par = (*(volatile uint32_t*)(smem + M_EPOCH) + 1u) & 1u
        cluster_wait();
        if (wg) {
            GET_PAR();
            mbar_spin(sb + B_G0, 0);
            mbar_spin(sb + B_GO1, 0);
        }
#pragma unroll
        for (int c = 0; c < 8; c++) {
            if (!wg || c == 2 || c == 4) mbar_spin(sb + (!wg ? B_F + 8 * c : c == 2 ? B_G2 : B_G4), 0);
            wg_fence();
#pragma unroll
            for (int kk = 0; kk < 4; kk++) {
                wgmma128<0>(acc, desc128(sbd + (wg ? off_xl(c) : off_xe(c)) / 16 + 2 * kk), desc128(sbd + off_d(c) / 16 + 2 * kk), (c | kk) != 0);
                if (c == 7 && kk == 0) wg_commit();
            }
            wg_commit();
            if (c == 3 && !wg) { GET_PAR(); }
            if (c == 7) {
                if (wg) mbar_spin(sb + B_FULL, 0);
                wg_wait<2>();
                mbar_arrive_if(sb + B_GO1, lead0);
            }
            if (c == 2 || c == 4 || c >= 6) wg_wait<1>();
            if (c == 2) RELEASE(2, 1, lead1);
            if (c == 4) { mbar_arrive_if(sb + B_XE, lead0); RELEASE(2, 2, lead1); RELEASE(2, 3, lead1); }
            if (c == 6) RELEASE(2, 4 * wg, lead);
            if (c == 7) mbar_arrive_if(sb + B_GO0, lead1);
        }
        const int rh = wg ^ comp;
        const uint32_t da0 = sbd + rh * 512, db0 = sbd - 0x10000 + 0x400000 + 1024;
        const uint32_t dbe = db0 + 6 * (REGION / 16), dbl = dbe - 1024;
#define STEP(da, db, first) wg_fence();                                                                     \
        _Pragma("unroll") for (int kk = 0; kk < 4; kk++)                                                    \
            wgmma128<1>(acc, desc128((da) + kk * 2), desc64((db) + kk * 256), !((first) && kk == 0));       \
        wg_commit()
#define ACC(i, j) (16 * ((i) >> 1) + 2 * ((i) & 1) + 4 * (j))
#define PW(i, j) pack_bf16(acc[ACC(i, j)], acc[ACC(i, j) + 1])
#define PT(i, j) ((j) == ((i) >> 1) ? (PW(i, j) & ~1u) | par : PW(i, j))
#define PIECE(i) make_uint4(PT(i, 0), PT(i, 1), PT(i, 2), PT(i, 3))
#define PIECES(F) F(0); F(1); sched_cut(); F(2); F(3); sched_cut(); F(4); F(5); sched_cut(); F(6); F(7)
        if (wg) {
            wg_wait<0>();
            fence_regs(acc);
#define STS1(i) sts128<(i) * 512>(sdst, PIECE(i))
            PIECES(STS1);
            STEP(da0, dbe, true);
            fence_proxy_async_smem();
            mbar_arrive_warp(sb + B_FULL + 8);
            RELEASE(1, 5, lead);
        } else {
            wg_wait<0>();
            fence_regs(acc);
            uint4 v[8];
#define STG0(i) v[i] = PIECE(i); stg128<(i) * 512>(gdst, v[i]); if (HINT_AT == (i) + 1) red_inc_if(hint, own < 6 && lane == 0)
            PIECES(STG0);
#define STS0(i) mbar_spin(sb + B_EPOCH, 0); sts128<(i) * 512>(sdst, v[i])
            STS0(0); STS0(1); STS0(2); STS0(3); STS0(4); STS0(5); STS0(6); STS0(7);
            fence_proxy_async_smem();
            mbar_arrive_warp(sb + B_FULL);
            RELEASE(1, 5, lead);
            mbar_arrive_if(sb + B_EARLY, lead);
            mbar_spin(sb + B_FULL, 0);
            mbar_spin(sb + B_GO0, 0);
            STEP(da0, dbe, true);
        }
#pragma unroll
        for (int step = 1; step < 3; step++) {
            mbar_spin(sb + B_FULL + 8 * step, 0);
            STEP(da0 + step * (REGION / 16), step == 1 ? dbl : db0 + step * (REGION / 16), false);
            wg_wait<1>();
            RELEASE(1, step - 1, lead);
            mbar_arrive_if(sb + B_FREE + 8 * (step - 1), lead);
        }
        int slot = 3, ph = 0, pslot = 2;
        float g0 = 0.f, g1 = 0.f;
        uint32_t oa = 0;
        const int lend = 33 - NSTAGE - (SK == NSTAGE && wg);
#pragma unroll 1
        for (int step = 3; step < lend; step++) {
            mbar_wait(sb + B_FULL + 8 * slot, ph);
            STEP(da0 + slot * (REGION / 16), db0 + slot * (REGION / 16), false);
            if (step == 22 + wg) {
                const int r0 = rh * 64 + wq * 16 + (lane >> 2), sr = ((lane >> 2) & 1) * 4 + (lane >> 3);
                mbar_wait(sb + B_GATE, 0);
                g0 = ((const volatile float*)(smem + M_G))[r0];
                g1 = ((const volatile float*)(smem + M_G))[r0 + 8];
                oa = pin(wg ? ((own * 128 + (r0 & ~1)) * D_ + tn * 128 + (lane & 7) * 8) * 2u
                            : sb + rh * 8192 + wq * 2048 + sr * 128 + ((q ^ sr) << 4));
            }
            wg_wait<1>();
            RELEASE(1, pslot, lead);
            pslot = slot;
            if (++slot == NSTAGE) { slot = 0; ph ^= 1; }
        }
        if (SK == NSTAGE && wg) { wg_wait<0>(); RELEASE(1, pslot, lead); }
#pragma unroll 1
        for (int step = lend; step < 32; step++) {
            if (wg && step == 32 - SK) {
                mbar_wait(sb + B_INIT, 0);
                mbar_wait(sb + B_TAIL, 0);
            }
            if (!wg || step < 32 - SK) mbar_wait(sb + B_FULL + 8 * slot, ph);
            STEP(da0 + (step < 32 - NA ? slot : step == 32 - NA ? 6 : pslot) * (REGION / 16), db0 + slot * (REGION / 16), false);
            pslot = slot;
            if (++slot == NSTAGE) { slot = 0; ph ^= 1; }
        }
#define OW(i, j) pack_bf16((((i) & 1) ? g1 : g0) * acc[ACC(i, j)], (((i) & 1) ? g1 : g0) * acc[ACC(i, j) + 1])
        if (!wg) {
            wg_wait<1>();
            mbar_arrive_if(sb + B_TAIL, lead);
            const uint32_t st0 = sb + rh * 8192 + wq * 2048;
            mbar_wait(sb + B_INIT, 0);
            wg_wait<0>();
            fence_regs(acc);
#define OSTS(i) sts128<((i) >> 2) * REGION + ((i) & 1) * 1024>(((i) & 2) ? oa ^ 64 : oa, make_uint4(OW(i, 0), OW(i, 1), OW(i, 2), OW(i, 3)))
#define ORED(h) fence_proxy_async_smem(); __syncwarp();                                                     \
            asm volatile(ELECT "cp.reduce.async.bulk.tensor.4d.global.shared::cta.add.tile.bulk_group [%0, {%2,%3,%3,%4}], [%1];}" \
                         ::"l"(&p.mOut), "r"(st0 + (h) * REGION), "r"(tn * 128 + (h) * 64), "r"(0), "r"(own * 16 + rh * 8 + wq * 2) : "memory")
            OSTS(0); OSTS(1); OSTS(2); OSTS(3);
            ORED(0);
            sched_cut();
            OSTS(4); OSTS(5); OSTS(6); OSTS(7);
            ORED(1);
            bulk_wait_read();
        } else {
            const bool odd = lane & 4;
            char *op = pin((char*)p.out + oa), *opb = pin((char*)p.out + (oa ^ 64) + 1024);
            sched_cut();
            wg_wait<0>();
            fence_regs(acc);
#define REDLINE(i) {                                                                                        \
                uint32_t k[4], r[4];                                                                        \
                _Pragma("unroll") for (int j = 0; j < 4; j++) {                                             \
                    r[j] = __shfl_xor_sync(0xffffffffu, OW((i) + 2, j), 4);                                 \
                    k[j] = OW(i, j);                                                                        \
                }                                                                                           \
                red_bf16x8<((i) & 1) * 8192 + ((i) >> 2) * 128>(op, odd ? r[0] : k[0], odd ? r[1] : k[1], odd ? r[2] : k[2], odd ? r[3] : k[3]);  \
                red_bf16x8<((i) & 1) * 8192 + ((i) >> 2) * 128>(opb, odd ? k[0] : r[0], odd ? k[1] : r[1], odd ? k[2] : r[2], odd ? k[3] : r[3]); }
            REDLINE(0)
            sched_cut();
            REDLINE(1) REDLINE(4) REDLINE(5)
        }
    }
}

typedef CUresult (*EncodeTiledFn)(CUtensorMap*, CUtensorMapDataType, cuuint32_t, void*, const cuuint64_t*, const cuuint64_t*,
                                  const cuuint32_t*, const cuuint32_t*, CUtensorMapInterleave, CUtensorMapSwizzle,
                                  CUtensorMapL2promotion, CUtensorMapFloatOOBfill);

static void make_map(EncodeTiledFn enc, CUtensorMap* m, const void* base, uint64_t cols, uint64_t rows, uint32_t box_rows,
                     CUtensorMapSwizzle sw = CU_TENSOR_MAP_SWIZZLE_128B, uint32_t box_cols = 64) {
    cuuint64_t dims[2] = {cols, rows};
    cuuint64_t str[1] = {cols * 2};
    cuuint32_t box[2] = {box_cols, box_rows};
    cuuint32_t es[2] = {1, 1};
    enc(m, CU_TENSOR_MAP_DATA_TYPE_BFLOAT16, 2, (void*)base, dims, str, box, es, CU_TENSOR_MAP_INTERLEAVE_NONE,
        sw, CU_TENSOR_MAP_L2_PROMOTION_L2_128B, CU_TENSOR_MAP_FLOAT_OOB_FILL_NONE);
}

static void make_map_chunks(EncodeTiledFn enc, CUtensorMap* m, const void* base, uint64_t rows, uint32_t box_rows, uint32_t n = 1) {
    cuuint64_t dims[3] = {64, rows, 8};
    cuuint64_t str[2] = {D_ * 2, 128};
    cuuint32_t box[3] = {64, box_rows, n};
    cuuint32_t es[3] = {1, 1, 1};
    enc(m, CU_TENSOR_MAP_DATA_TYPE_BFLOAT16, 3, (void*)base, dims, str, box, es, CU_TENSOR_MAP_INTERLEAVE_NONE,
        CU_TENSOR_MAP_SWIZZLE_128B, CU_TENSOR_MAP_L2_PROMOTION_L2_128B, CU_TENSOR_MAP_FLOAT_OOB_FILL_NONE);
}

static void make_map_out(EncodeTiledFn enc, CUtensorMap* m, const void* base) {
    cuuint64_t dims[4] = {D_, 4, 2, S_ / 8};
    cuuint64_t str[3] = {2 * D_ * 2, D_ * 2, 8 * D_ * 2};
    cuuint32_t box[4] = {64, 4, 2, 2};
    cuuint32_t es[4] = {1, 1, 1, 1};
    enc(m, CU_TENSOR_MAP_DATA_TYPE_BFLOAT16, 4, (void*)base, dims, str, box, es, CU_TENSOR_MAP_INTERLEAVE_NONE,
        CU_TENSOR_MAP_SWIZZLE_128B, CU_TENSOR_MAP_L2_PROMOTION_NONE, CU_TENSOR_MAP_FLOAT_OOB_FILL_NONE);
}

extern "C" void kernel_launch(void* const* d_in, const int* in_sizes, int n_in, void* d_out, int out_size) {
    (void)in_sizes; (void)n_in; (void)out_size;
    static EncodeTiledFn enc = nullptr;
    static bool fused_ok = false;
    static void* scratch = nullptr;
    if (!enc) {
        void* fn = nullptr;
        cudaDriverEntryPointQueryResult q;
        cudaGetDriverEntryPoint("cuTensorMapEncodeTiled", &fn, cudaEnableDefault, &q);
        enc = (EncodeTiledFn)fn;
        cudaGetSymbolAddress(&scratch, g_s);
        cudaFuncSetAttribute(fused_kernel, cudaFuncAttributeMaxDynamicSharedMemorySize, SMEM_BYTES);
        int dev = 0, nsm = 0, ncl = 0;
        cudaGetDevice(&dev);
        cudaDeviceGetAttribute(&nsm, cudaDevAttrMultiProcessorCount, dev);
        cudaLaunchConfig_t cfg = {};
        cfg.gridDim = dim3(132); cfg.blockDim = dim3(NTHREADS); cfg.dynamicSmemBytes = SMEM_BYTES;
        cudaLaunchAttribute at;
        at.id = cudaLaunchAttributeClusterDimension;
        at.val.clusterDim.x = 2; at.val.clusterDim.y = 1; at.val.clusterDim.z = 1;
        cfg.attrs = &at; cfg.numAttrs = 1;
        fused_ok = cudaOccupancyMaxActiveClusters(&ncl, fused_kernel, &cfg) == cudaSuccess && nsm == 132 && ncl == 66;
        (void)cudaGetLastError();
    }
    if (!fused_ok) {
        const bf16* const* in = (const bf16* const*)d_in;
        fb_hidden<<<S_, D_, 0, cudaStreamPerThread>>>(in[0], in[3], in[4], in[10], in[6]);
        fb_ffn1<<<F_ / 128, 128, 0, cudaStreamPerThread>>>(in[0], in[7], in[8]);
        fb_ffn2<<<D_ / 64, 64, 0, cudaStreamPerThread>>>(in[9]);
        fb_seq<<<S_, D_, 0, cudaStreamPerThread>>>(in[0], in[1], in[2], (bf16*)d_out);
        return;
    }
    Params p;
    p.s = (Scratch*)scratch;
    p.x = (const bf16*)d_in[0];
    p.w_r = (const bf16*)d_in[6];
    p.wg = (const bf16*)d_in[7];
    p.wu = (const bf16*)d_in[8];
    p.wd = (const bf16*)d_in[9];
    p.gate_w = (const bf16*)d_in[10];
    p.out = (bf16*)d_out;
    make_map_chunks(enc, &p.mX1, d_in[0], S_, 64);
    make_map_chunks(enc, &p.mX2, d_in[0], S_, 64, 2);
    make_map(enc, &p.mCre, d_in[1], S_, S_, 128);
    make_map(enc, &p.mCim, d_in[2], S_, S_, 128);
    make_map_chunks(enc, &p.mDre, d_in[3], D_, 128);
    make_map_chunks(enc, &p.mDim, d_in[4], D_, 128);
    make_map(enc, &p.mAB, scratch, 64, 8 * 32 * 128, 64, CU_TENSOR_MAP_SWIZZLE_NONE);
    make_map_out(enc, &p.mOut, d_out);
    make_map(enc, &p.mWg, d_in[7], F_, D_, 64, CU_TENSOR_MAP_SWIZZLE_NONE, 32);
    make_map(enc, &p.mWu, d_in[8], F_, D_, 64, CU_TENSOR_MAP_SWIZZLE_NONE, 32);
    make_map(enc, &p.mWd, d_in[9], D_, F_, 8, CU_TENSOR_MAP_SWIZZLE_NONE, 256);
    fused_kernel<<<132, NTHREADS, SMEM_BYTES, cudaStreamPerThread>>>(p);
}
```

```cpp
#include <cuda_runtime.h>
#include <cuda.h>
#include <cuda_bf16.h>
#include <stdint.h>

typedef __nv_bfloat16 bf16;

constexpr int S_ = 2048, D_ = 512, F_ = 1792;
constexpr int NCTA = 128;
constexpr int NTHREADS = 512;
constexpr int NSTAGE = 6;
constexpr int REGION = 32768;
constexpr int FFN_CTAS = F_ / 16;
constexpr uint32_t SPIN_LIMIT = 1u << 22;
constexpr int PACE = 260;
constexpr int PACE0 = 100;
constexpr int A_GAP = 260;
constexpr int B_GAP = 280;
constexpr int LATE_GAP = 240;
constexpr int INIT_GAP = 360;
constexpr int INIT_NS = 300;
constexpr int PF_T0 = 3000;
constexpr int PF_GAP = 850;
constexpr int PF_N0 = 4;
constexpr int FFN_S0 = 4;
constexpr int FFN_W = 7;
constexpr int ROUTER_C = 4;
constexpr int HINT_AT = 5;
constexpr int SUM_T0 = 15000;
constexpr int PS1 = 24;
constexpr int NA = 3;
constexpr int KEY_NS = 300;
constexpr int SK = 6;

constexpr int OFF_MISC = 7 * REGION;
constexpr int B_F = OFF_MISC;
constexpr int B_G1 = B_F + 64;
constexpr int B_G4 = B_G1 + 8;
constexpr int B_XE = B_G4 + 8;
constexpr int B_GO1 = B_XE + 8;
constexpr int B_GO0 = B_GO1 + 8;
constexpr int B_EPOCH = B_GO0 + 8;
constexpr int B_RETRY = B_EPOCH + 8;
constexpr int B_INIT = B_RETRY + 8;
constexpr int B_FULL = B_INIT + 8;
constexpr int B_EMPTY = B_FULL + 48;
constexpr int B_PUB = B_EMPTY + 48;
constexpr int B_FREE = B_PUB + 8;
constexpr int B_BL = B_FREE + 24;
constexpr int B_TAIL = B_BL + 48;
constexpr int B_HX = B_TAIL + 8;
constexpr int B_FFN = B_HX + 8;
constexpr int B_ROLE = B_FFN + 40;
constexpr int B_EARLY = B_ROLE + 8;
constexpr int B_GATE = B_EARLY + 8;
constexpr int B_G2 = B_GATE + 8;
constexpr int B_LOW = B_G2 + 8;
constexpr int B_G0 = B_LOW + 8;
constexpr int M_EPOCH = B_G0 + 8;
constexpr int M_ROLE = M_EPOCH + 4;
constexpr int M_KEY = OFF_MISC + 416;
constexpr int M_HX = OFF_MISC + 512;
constexpr int M_G = M_HX + 1024;
constexpr int M_XS = M_G + 512;
constexpr int SMEM_BYTES = 232448;
static_assert(M_ROLE + 4 <= M_KEY && M_XS + 512 <= SMEM_BYTES, "smem");

struct Scratch {
    unsigned char ab[8 * 32 * 16384];
    unsigned int hint[8 * 4 * 32];
    unsigned int ready[16 * 32];
    unsigned int gate[S_];
    unsigned int part[FFN_CTAS / 2 * D_];
    unsigned int phint[4 * 16 * 8];
    unsigned int keys[8 * NCTA];
    unsigned int epoch[NCTA + 4];
};
__device__ __align__(1024) Scratch g_s;

struct Params {
    Scratch* s;
    bf16* out;
    const bf16 *x, *gate_w, *w_r, *wg, *wu, *wd;
    CUtensorMap mDre, mDim, mX1, mX2, mCre, mCim, mAB, mOut, mWg, mWu, mWd;
};

#define ELECT "{.reg .pred p; elect.sync _|p, 0xffffffff; @p "
__device__ __forceinline__ uint32_t smem_u32(const void* p) { return (uint32_t)__cvta_generic_to_shared(p); }
__device__ __forceinline__ uint32_t clk() { return (uint32_t)clock64(); }
__device__ __forceinline__ void spin_until(uint32_t t) { while ((int)(clk() - t) < 0) {} }
template <int NS>
__device__ __forceinline__ void sleep_until(uint32_t t) { while ((int)(clk() - t) < 0) __nanosleep(NS); }
__device__ __forceinline__ void mbar_init_elect(uint32_t bar, uint32_t cnt) {
    asm volatile(ELECT "mbarrier.init.shared::cta.b64 [%0], %1;}" ::"r"(bar), "r"(cnt) : "memory");
}
__device__ __forceinline__ void mbar_expect_tx_elect(uint32_t bar, uint32_t bytes) {
    asm volatile(ELECT "mbarrier.arrive.expect_tx.shared::cta.b64 _, [%0], %1;}" ::"r"(bar), "r"(bytes) : "memory");
}
template <int N = 1>
__device__ __forceinline__ void mbar_arrive_elect(uint32_t bar) {
    asm volatile(ELECT "mbarrier.arrive.shared::cta.b64 _, [%0], %1;}" ::"r"(bar), "n"(N) : "memory");
}
__device__ __forceinline__ void mbar_arrive_if(uint32_t bar, bool pred) {
    asm volatile("{.reg .pred p; setp.ne.b32 p, %1, 0; @p mbarrier.arrive.shared::cta.b64 _, [%0];}" ::"r"(bar), "r"((int)pred) : "memory");
}
__device__ __forceinline__ void mbar_arrive_warp(uint32_t bar) {
    __syncwarp();
    mbar_arrive_if(bar, (threadIdx.x & 31) == 0);
}
template <int N>
__device__ __forceinline__ void release_pair(uint32_t bar, uint32_t rbar, bool pred) {
    asm volatile("{.reg .pred p; setp.ne.b32 p, %2, 0; @p mbarrier.arrive.shared::cta.b64 _, [%0], %3;"
                 " @p mbarrier.arrive.shared::cluster.b64 _, [%1], %3;}" ::"r"(bar), "r"(rbar), "r"((int)pred), "n"(N) : "memory");
}
__device__ __forceinline__ uint32_t mapa(uint32_t a, uint32_t cta) {
    uint32_t r;
    asm volatile("mapa.shared::cluster.u32 %0, %1, %2;" : "=r"(r) : "r"(a), "r"(cta));
    return r;
}
__device__ __forceinline__ bool mbar_test(uint32_t bar, uint32_t parity) {
    uint32_t ok;
    asm volatile("{.reg .pred p; mbarrier.test_wait.parity.shared::cta.b64 p, [%1], %2; selp.u32 %0,1,0,p;}"
                 : "=r"(ok) : "r"(bar), "r"(parity) : "memory");
    return ok;
}
__device__ __forceinline__ void mbar_wait(uint32_t bar, uint32_t parity) {
    asm volatile("{.reg .pred p, q; .reg .u32 n; mov.u32 n, 0;\n"
                 "W%=: mbarrier.try_wait.parity.shared::cta.b64 p, [%0], %1;\n"
                 "add.u32 n, n, 1; setp.lt.and.u32 q, n, %2, !p; @q bra W%=; @!p trap;}" ::"r"(bar), "r"(parity), "n"(SPIN_LIMIT) : "memory");
}
__device__ __forceinline__ void mbar_wait_cluster(uint32_t bar, uint32_t parity) {
    asm volatile("{.reg .pred p, q; .reg .u32 n; mov.u32 n, 0;\n"
                 "W%=: mbarrier.try_wait.parity.acquire.cluster.shared::cta.b64 p, [%0], %1;\n"
                 "add.u32 n, n, 1; setp.lt.and.u32 q, n, %2, !p; @q bra W%=; @!p trap;}" ::"r"(bar), "r"(parity), "n"(SPIN_LIMIT) : "memory");
}
__device__ __forceinline__ void mbar_spin(uint32_t bar, uint32_t parity) {
    asm volatile("{.reg .pred p;\nW%=: mbarrier.try_wait.parity.shared::cta.b64 p, [%0], %1; @!p bra W%=;}" ::"r"(bar), "r"(parity) : "memory");
}
__device__ __forceinline__ void cluster_arrive() { asm volatile("barrier.cluster.arrive.relaxed.aligned;" ::: "memory"); }
__device__ __forceinline__ void cluster_wait() { asm volatile("barrier.cluster.wait.acquire.aligned;" ::: "memory"); }
__device__ __forceinline__ void side_bar() { asm volatile("bar.sync 1, 128;" ::: "memory"); }
__device__ __forceinline__ void tma2d_elect(uint32_t dst, const CUtensorMap* m, int c0, int c1, uint32_t bar) {
    asm volatile(ELECT "cp.async.bulk.tensor.2d.shared::cluster.global.mbarrier::complete_tx::bytes [%0], [%1, {%3,%4}], [%2];}"
                 ::"r"(dst), "l"(m), "r"(bar), "r"(c0), "r"(c1) : "memory");
}
__device__ __forceinline__ void tma2d_pair_elect(uint32_t dst, const CUtensorMap* m, int c0, int c1, uint32_t bar) {
    asm volatile(ELECT "cp.async.bulk.tensor.2d.shared::cluster.global.mbarrier::complete_tx::bytes.multicast::cluster"
                 " [%0], [%1, {%3,%4}], [%2], %5;}" ::"r"(dst), "l"(m), "r"(bar), "r"(c0), "r"(c1), "h"((uint16_t)3) : "memory");
}
__device__ __forceinline__ void tma3d_elect(uint32_t dst, const CUtensorMap* m, int row, int chunk, uint32_t bar) {
    asm volatile(ELECT "cp.async.bulk.tensor.3d.shared::cluster.global.mbarrier::complete_tx::bytes [%0], [%1, {%3,%4,%5}], [%2];}"
                 ::"r"(dst), "l"(m), "r"(bar), "r"(0), "r"(row), "r"(chunk) : "memory");
}
__device__ __forceinline__ void bulk_wait_read() {
    asm volatile("cp.async.bulk.commit_group; cp.async.bulk.wait_group.read 0;" ::: "memory");
    __syncwarp();
}
__device__ __forceinline__ void fence_proxy_async_smem() { asm volatile("fence.proxy.async.shared::cta;" ::: "memory"); }
__device__ __forceinline__ uint32_t ld_relaxed(const void* p) {
    uint32_t v;
    asm volatile("ld.relaxed.gpu.global.u32 %0, [%1];" : "=r"(v) : "l"(p) : "memory");
    return v;
}
__device__ __forceinline__ uint4 ld_relaxed4(const void* p) {
    uint4 v;
    asm volatile("ld.relaxed.gpu.global.v4.u32 {%0,%1,%2,%3}, [%4];" : "=r"(v.x), "=r"(v.y), "=r"(v.z), "=r"(v.w) : "l"(p) : "memory");
    return v;
}
__device__ __forceinline__ void red_inc_if(unsigned int* p, bool pred) {
    asm volatile("{.reg .pred p; setp.ne.b32 p, %1, 0; @p red.relaxed.gpu.global.add.u32 [%0], 1;}" ::"l"(p), "r"((int)pred) : "memory");
}
__device__ __forceinline__ uint32_t tagf(float v, uint32_t par) { return (__float_as_uint(v) & ~1u) | par; }
__device__ __forceinline__ uint4 wait_tags(const unsigned int* p, int bit, uint32_t par) {
    uint32_t n = 0;
    while (true) {
        const uint4 v = ld_relaxed4(p);
        const uint32_t m = par ? (v.x & v.y & v.z & v.w) : ~(v.x | v.y | v.z | v.w);
        if (__all_sync(0xffffffffu, (m >> bit) & 1u)) return v;
        __nanosleep(100);
        if (++n > SPIN_LIMIT) __trap();
    }
}
__device__ __forceinline__ void wait_counter(const unsigned int* p, uint32_t want) {
    uint32_t n = 0;
    while (!__all_sync(0xffffffffu, (int)(ld_relaxed(p) - want) >= 0)) {
        __nanosleep(200);
        if (++n > SPIN_LIMIT) __trap();
    }
    asm volatile("fence.acquire.gpu;" ::: "memory");
}
__device__ __forceinline__ uint32_t stale_tags(uint32_t a, uint32_t par) {
    uint32_t r;
    asm volatile("{.reg .b32 v<16>;\n"
                 "ld.shared.u32 v0, [%1]; ld.shared.u32 v1, [%1+256]; ld.shared.u32 v2, [%1+512]; ld.shared.u32 v3, [%1+768];\n"
                 "ld.shared.u32 v4, [%1+4096]; ld.shared.u32 v5, [%1+4352]; ld.shared.u32 v6, [%1+4608]; ld.shared.u32 v7, [%1+4864];\n"
                 "ld.shared.u32 v8, [%1+8192]; ld.shared.u32 v9, [%1+8448]; ld.shared.u32 v10, [%1+8704]; ld.shared.u32 v11, [%1+8960];\n"
                 "ld.shared.u32 v12, [%1+12288]; ld.shared.u32 v13, [%1+12544]; ld.shared.u32 v14, [%1+12800]; ld.shared.u32 v15, [%1+13056];\n"
                 "lop3.b32 v0, v0, v1, %2, 0x7e; lop3.b32 v2, v2, v3, %2, 0x7e; lop3.b32 v4, v4, v5, %2, 0x7e; lop3.b32 v6, v6, v7, %2, 0x7e;\n"
                 "lop3.b32 v8, v8, v9, %2, 0x7e; lop3.b32 v10, v10, v11, %2, 0x7e; lop3.b32 v12, v12, v13, %2, 0x7e; lop3.b32 v14, v14, v15, %2, 0x7e;\n"
                 "lop3.b32 v0, v0, v2, v4, 0xfe; lop3.b32 v6, v6, v8, v10, 0xfe; lop3.b32 v0, v0, v6, v12, 0xfe; or.b32 %0, v0, v14;}"
                 : "=r"(r) : "r"(a), "r"(par) : "memory");
    return r;
}
template <int OFF>
__device__ __forceinline__ uint4 ldg_nc(const void* p) {
    uint4 v;
    asm volatile("ld.global.nc.v4.u32 {%0,%1,%2,%3}, [%4+%5];" : "=r"(v.x), "=r"(v.y), "=r"(v.z), "=r"(v.w) : "l"(p), "n"(OFF));
    return v;
}
template <int OFF>
__device__ __forceinline__ void stg128(void* p, const uint4& v) {
    asm volatile("st.global.v4.u32 [%0+%5], {%1,%2,%3,%4};" ::"l"(p), "r"(v.x), "r"(v.y), "r"(v.z), "r"(v.w), "n"(OFF) : "memory");
}
template <int OFF>
__device__ __forceinline__ void sts128(uint32_t a, const uint4& v) {
    asm volatile("st.shared.v4.u32 [%0+%5], {%1,%2,%3,%4};" ::"r"(a), "r"(v.x), "r"(v.y), "r"(v.z), "r"(v.w), "n"(OFF) : "memory");
}
__device__ __forceinline__ uint4 lds128(uint32_t a) {
    uint4 v;
    asm volatile("ld.shared.v4.u32 {%0,%1,%2,%3}, [%4];" : "=r"(v.x), "=r"(v.y), "=r"(v.z), "=r"(v.w) : "r"(a) : "memory");
    return v;
}
template <int OFF>
__device__ __forceinline__ void red_bf16x8(void* p, uint32_t x, uint32_t y, uint32_t z, uint32_t w) {
    asm volatile("red.relaxed.gpu.global.add.noftz.v4.bf16x2 [%0+%5], {%1,%2,%3,%4};"
                 ::"l"(p), "r"(x), "r"(y), "r"(z), "r"(w), "n"(OFF) : "memory");
}
__device__ __forceinline__ void sched_cut() {
    asm volatile("{.reg .pred p; .reg .u64 t; .reg .u32 a, b;\n"
                 "C%=: mov.u64 t, %%clock64; mov.b64 {a, b}, t; setp.eq.u32 p, a, %0; @p bra C%=;}" ::"n"(0) : "memory");
}
__device__ __forceinline__ uint32_t pin(uint32_t v) { return __shfl_xor_sync(0xffffffffu, v, 0); }
template <class T>
__device__ __forceinline__ T* pin(T* p) { return (T*)__shfl_xor_sync(0xffffffffu, (unsigned long long)p, 0); }
__device__ __forceinline__ float selpf(float a, float b, bool p) {
    float r;
    asm("{.reg .pred q; setp.ne.b32 q, %3, 0; selp.f32 %0, %1, %2, q;}" : "=f"(r) : "f"(a), "f"(b), "r"((int)p));
    return r;
}
template <int N, int MASK, int SZ>
__device__ __forceinline__ void halve(float (&a)[SZ]) {
    const bool up = threadIdx.x & MASK;
#pragma unroll
    for (int j = 0; j < N; j++) a[j] = selpf(a[N + j], a[j], up) + __shfl_xor_sync(0xffffffffu, selpf(a[j], a[N + j], up), MASK);
}
__device__ __forceinline__ float bflo(uint32_t u) { return __uint_as_float(u << 16); }
__device__ __forceinline__ float bfhi(uint32_t u) { return __uint_as_float(u & 0xffff0000u); }
__device__ __forceinline__ uint32_t pack_bf16(float lo, float hi) {
    uint32_t r;
    asm("cvt.rn.bf16x2.f32 %0, %1, %2;" : "=r"(r) : "f"(hi), "f"(lo));
    return r;
}
__device__ __forceinline__ uint32_t hmul2_bf16(uint32_t a, uint32_t b) {
    uint32_t r;
    asm("mul.rn.bf16x2 %0, %1, %2;" : "=r"(r) : "r"(a), "r"(b));
    return r;
}
__device__ __forceinline__ float rbf(float v) { return bflo(pack_bf16(v, 0.f)); }
__device__ __forceinline__ float sigmoidf_(float v) { return __fdividef(1.0f, 1.0f + __expf(-v)); }

__device__ __forceinline__ void wg_fence() { asm volatile("wgmma.fence.sync.aligned;" ::: "memory"); }
__device__ __forceinline__ void wg_commit() { asm volatile("wgmma.commit_group.sync.aligned;" ::: "memory"); }
template <int N> __device__ __forceinline__ void wg_wait() { asm volatile("wgmma.wait_group.sync.aligned %0;" ::"n"(N) : "memory"); }
__device__ __forceinline__ uint64_t desc128(uint32_t lo) { return (uint64_t)lo | (0x40000040ull << 32); }
__device__ __forceinline__ uint64_t desc64(uint32_t lo) { return (uint64_t)lo | (0x80000020ull << 32); }
__device__ __forceinline__ void fence_regs(float (&d)[64]) {
#pragma unroll
    for (int i = 0; i < 64; i++) asm volatile("" : "+f"(d[i])::"memory");
}
template <int TB>
__device__ __forceinline__ void wgmma128(float (&d)[64], uint64_t da, uint64_t db, int scaleD) {
    asm volatile(
        "{ .reg .pred p; setp.ne.b32 p, %66, 0;\n"
        "wgmma.mma_async.sync.aligned.m64n128k16.f32.bf16.bf16 "
        "{%0,%1,%2,%3,%4,%5,%6,%7,%8,%9,%10,%11,%12,%13,%14,%15,%16,%17,%18,%19,%20,%21,%22,%23,%24,%25,%26,%27,%28,%29,%30,%31,"
        "%32,%33,%34,%35,%36,%37,%38,%39,%40,%41,%42,%43,%44,%45,%46,%47,%48,%49,%50,%51,%52,%53,%54,%55,%56,%57,%58,%59,%60,%61,%62,%63}, "
        "%64, %65, p, 1, 1, 0, %67;\n}"
        : "+f"(d[0]), "+f"(d[1]), "+f"(d[2]), "+f"(d[3]), "+f"(d[4]), "+f"(d[5]), "+f"(d[6]), "+f"(d[7]),
          "+f"(d[8]), "+f"(d[9]), "+f"(d[10]), "+f"(d[11]), "+f"(d[12]), "+f"(d[13]), "+f"(d[14]), "+f"(d[15]),
          "+f"(d[16]), "+f"(d[17]), "+f"(d[18]), "+f"(d[19]), "+f"(d[20]), "+f"(d[21]), "+f"(d[22]), "+f"(d[23]),
          "+f"(d[24]), "+f"(d[25]), "+f"(d[26]), "+f"(d[27]), "+f"(d[28]), "+f"(d[29]), "+f"(d[30]), "+f"(d[31]),
          "+f"(d[32]), "+f"(d[33]), "+f"(d[34]), "+f"(d[35]), "+f"(d[36]), "+f"(d[37]), "+f"(d[38]), "+f"(d[39]),
          "+f"(d[40]), "+f"(d[41]), "+f"(d[42]), "+f"(d[43]), "+f"(d[44]), "+f"(d[45]), "+f"(d[46]), "+f"(d[47]),
          "+f"(d[48]), "+f"(d[49]), "+f"(d[50]), "+f"(d[51]), "+f"(d[52]), "+f"(d[53]), "+f"(d[54]), "+f"(d[55]),
          "+f"(d[56]), "+f"(d[57]), "+f"(d[58]), "+f"(d[59]), "+f"(d[60]), "+f"(d[61]), "+f"(d[62]), "+f"(d[63])
        : "l"(da), "l"(db), "r"(scaleD), "n"(TB));
}

__device__ __forceinline__ uint32_t get_role(uint32_t& smid) {
    uint32_t role;
    asm volatile("mov.u32 %0, %%smid;" : "=r"(smid));
    asm("{.reg .pred p, q; .reg .u32 t, a, b; shr.u32 t, %1, 1; mad.lo.u32 a, t, 293, -928; shr.u32 a, a, 8; mad.lo.u32 b, t, 8, -464;"
        " setp.lt.u32 p, t, 32; setp.lt.u32 q, t, 62; selp.u32 a, a, b, q; selp.u32 %0, t, a, p;}" : "=r"(role) : "r"(smid));
    return role;
}
__device__ __forceinline__ int tile_of_step(int step, int own) {
    const int u = step >= 17 ? step - 17 - (step > PS1) : step - 2;
    int e = u + (u >= (own & 14) ? 2 : 0);
    if (step == 16 || step == PS1) e = own ^ 1;
    if (step < 2) e = own;
    return e + (step >= 17 || step == 1 ? 16 : 0);
}
__device__ __forceinline__ uint32_t router_key(float score, int row) {
    const float r = score + 0.0f;
    uint32_t u = pack_bf16(r, 0.f) & 0xffffu;
    u = (u & 0x8000u) ? (~u & 0xffffu) : (u | 0x8000u);
    if (r != r) u = 0;
    return (u << 16) | (uint32_t)(0x7fff - row);
}

#define g_fb_h ((float*)g_s.part)
#define g_fb_upd (g_fb_h + 2048)
#define g_fb_gate (g_fb_h + 4096)
#define g_fb_keys (g_s.part + 8192)
__global__ void fb_hidden(const bf16* x, const bf16* dre, const bf16* dim, const bf16* gw, const bf16* wr) {
    __shared__ float xs[D_];
    const int s = blockIdx.x, t = threadIdx.x;
    xs[t] = __bfloat162float(x[s * D_ + t]);
    __syncthreads();
    float a = 0.f, b = 0.f;
    for (int d = 0; d < D_; d++) { a = fmaf(xs[d], __bfloat162float(dre[t * D_ + d]), a); b = fmaf(xs[d], __bfloat162float(dim[t * D_ + d]), b); }
    ((bf16*)g_s.ab)[s * 1024 + t] = __float2bfloat16(a);
    ((bf16*)g_s.ab)[s * 1024 + 512 + t] = __float2bfloat16(b);
    if (t == 0) {
        float u = 0.f, v = 0.f;
        for (int d = 0; d < D_; d++) { u = fmaf(xs[d], __bfloat162float(gw[d]), u); v = fmaf(xs[d], __bfloat162float(wr[d]), v); }
        g_fb_gate[s] = sigmoidf_(u);
        g_fb_keys[s] = router_key(v, s);
    }
}
__device__ uint32_t fb_best() {
    uint32_t k = 0;
    for (int i = 0; i < S_; i++) k = max(k, g_fb_keys[i]);
    return k;
}
__global__ void fb_ffn1(const bf16* x, const bf16* wg, const bf16* wu) {
    const int f = blockIdx.x * blockDim.x + threadIdx.x, idx = 0x7fff - (int)(fb_best() & 0x7fffu);
    float a = 0.f, b = 0.f;
    for (int d = 0; d < D_; d++) {
        const float xv = __bfloat162float(x[idx * D_ + d]);
        a = fmaf(xv, __bfloat162float(wg[d * F_ + f]), a); b = fmaf(xv, __bfloat162float(wu[d * F_ + f]), b);
    }
    g_fb_h[f] = a * sigmoidf_(a) * b;
}
__global__ void fb_ffn2(const bf16* wd) {
    const int e = blockIdx.x * blockDim.x + threadIdx.x;
    const uint32_t u = fb_best() >> 16, rb = (u & 0x8000u) ? (u & 0x7fffu) : (~u & 0xffffu);
    float a = 0.f;
    for (int f = 0; f < F_; f++) a = fmaf(g_fb_h[f], __bfloat162float(wd[f * D_ + e]), a);
    g_fb_upd[e] = a * sigmoidf_(__uint_as_float(rb << 16));
}
__global__ void fb_seq(const bf16* x, const bf16* cre, const bf16* cim, bf16* out) {
    __shared__ float c[2][S_];
    __shared__ int idx;
    const int t = blockIdx.x, e = threadIdx.x;
    for (int i = e; i < S_; i += D_) { c[0][i] = __bfloat162float(cre[t * S_ + i]); c[1][i] = __bfloat162float(cim[t * S_ + i]); }
    if (e == 0) idx = 0x7fff - (int)(fb_best() & 0x7fffu);
    __syncthreads();
    float y = 0.f;
    for (int s = 0; s < S_; s++)
        y += c[0][s] * __bfloat162float(((const bf16*)g_s.ab)[s * 1024 + e]) - c[1][s] * __bfloat162float(((const bf16*)g_s.ab)[s * 1024 + 512 + e]);
    const float g = g_fb_gate[t];
    out[t * D_ + e] = __float2bfloat16(g * y + (1.f - g) * (__bfloat162float(x[t * D_ + e]) + (t == idx ? g_fb_upd[e] : 0.f)));
}

__device__ __forceinline__ void spare_job(const Params& p, unsigned char* smem, int sp, uint32_t tstart) {
    const int tid = threadIdx.x, warp = tid >> 5, lane = tid & 31;
    const uint32_t e1 = *(volatile unsigned int*)&p.s->epoch[NCTA + sp] + 1u;
    const uint32_t par = e1 & 1u;
    uint32_t* sel = (uint32_t*)smem;
    float* acc = (float*)(smem + 1024);
    __syncthreads();
    if (tid == 0) *(volatile unsigned int*)&p.s->epoch[NCTA + sp] = e1;
    sleep_until<500>(tstart + SUM_T0);
    if (warp < 14) {
        uint32_t n = 0;
        while ((int)(ld_relaxed(p.s->phint + (sp * 16 + warp) * 8) - e1 * 8u) < 0) {
            __nanosleep(100);
            if (++n > SPIN_LIMIT) __trap();
        }
        const unsigned int* src = p.s->part + warp * 4 * D_ + sp * 128 + lane * 4;
        uint4 v[4];
        while (true) {
            uint32_t bad = 0;
#pragma unroll
            for (int i = 0; i < 4; i++) v[i] = ld_relaxed4(src + i * D_);
#pragma unroll
            for (int i = 0; i < 4; i++) bad |= (v[i].x ^ par) | (v[i].y ^ par) | (v[i].z ^ par) | (v[i].w ^ par);
            if (!__any_sync(0xffffffffu, bad & 1u)) break;
            if (++n > SPIN_LIMIT) __trap();
        }
        float4 s = make_float4(0.f, 0.f, 0.f, 0.f);
#pragma unroll
        for (int i = 0; i < 4; i++) {
            s.x += __uint_as_float(v[i].x); s.y += __uint_as_float(v[i].y);
            s.z += __uint_as_float(v[i].z); s.w += __uint_as_float(v[i].w);
        }
        *(float4*)&acc[warp * 128 + lane * 4] = s;
    } else if (warp == 14) {
        const uint4 k4 = wait_tags(p.s->keys + lane * 4, 15, par);
        const uint32_t k = __reduce_max_sync(0xffffffffu, max(max(k4.x, k4.y), max(k4.z, k4.w)));
        const int idx = 0x7fff - (int)(k & 0x7fffu);
        const uint4 g4 = wait_tags(p.s->gate + (idx & ~3), 0, par);
        const uint32_t gw = (idx & 2) ? ((idx & 1) ? g4.w : g4.z) : ((idx & 1) ? g4.y : g4.x);
        const uint32_t u = k >> 16;
        const uint32_t rb = (u & 0x8000u) ? (u & 0x7fffu) : (~u & 0xffffu);
        const float og = 1.f - __uint_as_float(gw & ~1u), rs = sigmoidf_(__uint_as_float(rb << 16));
        if (lane == 0) { sel[0] = idx; sel[1] = pack_bf16(og, og); sel[2] = pack_bf16(rs, rs); }
        sleep_until<500>(tstart + SUM_T0 + 3000);
        wait_counter(p.s->ready + (idx >> 7) * 32, e1 * 8u);
    }
    __syncthreads();
    if (tid < 64) {
        float t0 = 0.f, t1 = 0.f;
#pragma unroll
        for (int i = 0; i < 14; i++) {
            const float2 z = *(const float2*)&acc[i * 128 + tid * 2];
            t0 += z.x; t1 += z.y;
        }
        asm volatile("red.relaxed.gpu.global.add.noftz.bf16x2 [%0], %1;" ::"l"(p.out + sel[0] * D_ + sp * 128 + tid * 2),
                     "r"(hmul2_bf16(sel[1], hmul2_bf16(sel[2], pack_bf16(t0, t1)))) : "memory");
    }
}

__host__ __device__ constexpr int off_d(int c) { return (c < 2 ? 1 : c / 2 + 2) * REGION + (c & 1) * 16384; }
__host__ __device__ constexpr int off_xe(int c) { return (c < 2 ? 6 * REGION : c < 4 ? 16384 : c < 6 ? 0 : 6 * REGION + 16384) + (c & 1) * 8192; }
__host__ __device__ constexpr int off_xl(int c) { return c < 4 ? 2 * REGION + c * 8192 : off_xe(c - 4); }

__global__ void __cluster_dims__(2, 1, 1) __launch_bounds__(NTHREADS, 1)
fused_kernel(const __grid_constant__ Params p) {
    extern __shared__ __align__(1024) unsigned char smem[];
    const uint32_t tstart = clk();
    const uint32_t sb = smem_u32(smem);
    const int tid = threadIdx.x, lane = tid & 31;
    const int rank = blockIdx.x & 1;
    uint32_t t1 = 0;
    if (__any_sync(0xffffffffu, tid == 0)) {
        uint32_t s0;
        const uint32_t r0 = get_role(s0);
        mbar_init_elect(sb + B_F, 1);
        if (r0 < 64) {
#pragma unroll
            for (int c = 0; c < 2; c++) {
                if (c) {
                    spin_until(t1 + PACE);
                    mbar_init_elect(sb + B_F + 8, 1);
                }
                tma3d_elect(sb + off_d(c), &p.mDre + ((r0 >> 2) & 1), (r0 & 24) * 16, c, sb + B_F + 8 * c);
                tma3d_elect(sb + off_xe(c), &p.mX1, (r0 & 3) * 256 + (r0 & 32) * 4 + rank * 64, c, sb + B_F + 8 * c);
                mbar_expect_tx_elect(sb + B_F + 8 * c, 24576);
                if (!c) {
                    t1 = clk() + PACE0;
                    mbar_init_elect(sb + B_G0, 1);
                    tma3d_elect(sb + off_xl(0), &p.mX1, (r0 & 3) * 256 + (r0 & 32) * 4 + rank * 64 + 1024, 0, sb + B_G0);
                    mbar_expect_tx_elect(sb + B_G0, 8192);
                }
            }
        }
    }
    const int warp = __shfl_sync(0xffffffffu, tid >> 5, 0);
    uint32_t smid;
    const uint32_t role = get_role(smid);
    const int gpc = role & 7;
    const int tn = (role >> 3) & 3;
    const int comp = gpc >> 2;
    const int own = (gpc & 3) * 4 + ((role >> 5) & 1) * 2 + rank;
    const int blk = comp * 4 + tn;
    const int cta = gpc * 16 + (role >> 3) * 2 + rank;
    const bool ffn = cta < FFN_CTAS;
    uint32_t epoch = 0;
    if (warp != 0) {
        const uint32_t b1 = sb + B_F + 8 * warp;
        mbar_init_elect(warp < 2 ? b1 + 360 : b1, 1);
        if (warp >= 2 && warp < 5) mbar_init_elect(b1 + 360, warp < 4 ? 1 : 4);
        mbar_init_elect(b1 + 120, warp < 7 ? 5 : warp < 14 ? 4 : warp - 12);
        mbar_init_elect(b1 + 240, 1);
        if (warp == 9 || warp == 15) mbar_expect_tx_elect(b1 + 240, warp == 9 ? 2048 : 4);
        asm volatile("fence.mbarrier_init.release.cluster;" ::: "memory");
        if (tid == 128 && role < 64) epoch = *(volatile unsigned int*)&p.s->epoch[cta];
    }
    if (role >= 64) {
        spare_job(p, smem, smid & 3, tstart);
        return;
    }
    __syncthreads();
    cluster_arrive();
    if (warp == 0) {
#pragma unroll
        for (int c = 2; c < 8; c++) {
            spin_until(t1 + c * PACE);
            tma3d_elect(sb + off_d(c), &p.mDre + comp, tn * 128, c, sb + B_F + 8 * c);
            tma3d_elect(sb + off_xe(c), &p.mX1, own * 64, c, sb + B_F + 8 * c);
            mbar_expect_tx_elect(sb + B_F + 8 * c, 24576);
        }
        tma3d_elect(sb + off_xl(1), &p.mX1, own * 64 + 1024, 1, sb + B_G1);
        mbar_expect_tx_elect(sb + B_G1, 8192);
        spin_until(t1 + 8 * PACE);
        tma3d_elect(sb + off_xl(2), &p.mX2, own * 64 + 1024, 2, sb + B_G2);
        mbar_expect_tx_elect(sb + B_G2, 16384);
        if (tn < 2)
            asm volatile(ELECT "cp.async.bulk.prefetch.tensor.3d.L2.global [%0, {%1,%2,%3}];}"
                         ::"l"(&p.mX2), "r"(0), "r"(own * 64 + 1024), "r"(4 + 2 * tn) : "memory");
    }

    if (warp < 4) {
        const int tab = tile_of_step(lane, own);
        const uint32_t bdst = sb + 16384 + rank * 8192;
        const int brow = blk * 4096 + rank * 64;
        if (warp == 0) {
            mbar_spin(sb + B_XE, 0);
            tma3d_elect(sb + off_xl(4), &p.mX2, own * 64 + 1024, 4, sb + B_G4);
            tma3d_elect(sb + off_xl(6), &p.mX2, own * 64 + 1024, 6, sb + B_G4);
            mbar_expect_tx_elect(sb + B_G4, 32768);
#define LOAD_A() const int e = __shfl_sync(0xffffffffu, tab, step);                                             \
                 const uint32_t bar = sb + 8 * slot;                                                            \
                 mbar_spin(bar + B_EMPTY, ph);                                                                  \
                 tma2d_elect(sb + slot * REGION, &p.mCre + comp, e * 64, own * 128, bar + B_FULL);              \
                 mbar_expect_tx_elect(bar + B_FULL, 16384)
            uint32_t slot = 0, ph = 0;
            int step = 0;
#pragma unroll 1
            for (int i = 0; i < NSTAGE; i++) {
                step = slot = i < 2 ? i ^ 1 : i;
                LOAD_A();
                if (i == 2 || i == 3) spin_until(clk() + A_GAP);
            }
            step = NSTAGE;
            slot = 0; ph = 1;
#pragma unroll 1
            for (int h = 0; h < 3; h++) {
                const int last = h == 0 ? 16 : h == 1 ? PS1 : 32 - NA;
#pragma unroll 1
                for (; step < last; step++) {
                    LOAD_A();
                    tma2d_pair_elect(bdst + slot * REGION, &p.mAB, 0, brow + e * 128, bar + B_BL);
                    mbar_expect_tx_elect(bar + B_BL, 16384);
                    if (++slot == NSTAGE) { slot = 0; ph ^= 1; }
                }
                if (h == 2) break;
                LOAD_A();
                tma2d_elect(bdst + slot * REGION, &p.mAB, 0, brow + e * 128, bar + B_BL);
                tma2d_elect((bdst ^ 8192) + slot * REGION, &p.mAB, 0, (brow ^ 64) + e * 128, bar + B_BL);
                mbar_expect_tx_elect(bar + B_BL, 16384);
                step++;
                if (++slot == NSTAGE) { slot = 0; ph ^= 1; }
            }
            mbar_spin(sb + B_LOW, 0);
            uint32_t aslot = 6;
#pragma unroll 1
            for (; step < 32; step++) {
                const int e = __shfl_sync(0xffffffffu, tab, step);
                const uint32_t bar = sb + 8 * slot;
                tma2d_elect(sb + aslot * REGION, &p.mCre + comp, e * 64, own * 128, bar + B_FULL);
                mbar_expect_tx_elect(bar + B_FULL, 16384);
                mbar_expect_tx_elect(bar + B_BL, 16384);
                mbar_spin(bar + B_EMPTY, ph);
                tma2d_pair_elect(bdst + slot * REGION, &p.mAB, 0, brow + e * 128, bar + B_BL);
                aslot = slot;
                if (++slot == NSTAGE) { slot = 0; ph ^= 1; }
            }
        } else if (warp == 1) {
            if (lane < 4) asm volatile("prefetch.tensormap [%0];" ::"l"(&p.mCre + lane) : "memory");
            __syncwarp();
            cluster_wait();
            if (lane == 0)
                asm volatile("st.async.weak.shared::cluster.mbarrier::complete_tx::bytes.u32 [%0], %1, [%2];"
                             ::"r"(mapa(sb + M_ROLE, rank ^ 1)), "r"(role), "r"(mapa(sb + B_ROLE, rank ^ 1)) : "memory");
            mbar_wait_cluster(sb + B_ROLE, 0);
            if (*(volatile uint32_t*)(smem + M_ROLE) != role) __trap();
            mbar_wait(sb + B_EPOCH, 0);
            const uint32_t want = (*(volatile uint32_t*)(smem + M_EPOCH) + 1u) * 4u;
            const int eh = __shfl_sync(0xffffffffu, tab, 2 + (lane & 3));
            const unsigned int* hp = p.s->hint + (blk * 4 + (eh >> 1)) * 32 + (eh & 1);
            uint32_t seen = __ballot_sync(0xffffffffu, ld_relaxed(hp) == want);
            int rows[4];
#pragma unroll
            for (int i = 0; i < 4; i++) {
                rows[i] = brow + __shfl_sync(0xffffffffu, tab, 2 + i) * 128;
                mbar_expect_tx_elect(sb + B_BL + 8 * (2 + i), 16384);
            }
            mbar_wait(sb + B_EMPTY + 8 * 3, 0);
            mbar_spin(sb + B_EMPTY + 8 * 2, 0);
            uint32_t t3 = 0;
#pragma unroll
            for (int i = 0; i < 4; i++) {
                while (!((seen >> i) & 1u)) seen = __ballot_sync(0xffffffffu, ld_relaxed(hp) == want);
                if (i) spin_until(t3 + B_GAP);
                t3 = clk();
                if (i >= 2) mbar_spin(sb + B_EMPTY + 8 * (2 + i), 0);
                tma2d_pair_elect(bdst + (2 + i) * REGION, &p.mAB, 0, rows[i], sb + B_BL + 8 * (2 + i));
            }
            mbar_wait(sb + B_FREE, 0);
            unsigned char* gdst = p.s->ab + (blk * 32 + own + 16) * 16384;
            t3 = clk();
#pragma unroll 1
            for (int i = 0; i < 16; i++) {
                sleep_until<20>(t3);
                t3 += LATE_GAP;
                asm volatile(ELECT "cp.async.bulk.global.shared::cta.bulk_group [%0], [%1], 1024;}"
                             ::"l"(gdst + i * 1024), "r"(sb + 6 * REGION + i * 1024) : "memory");
            }
            bulk_wait_read();
            mbar_arrive_elect(sb + B_FREE + 8);
            mbar_wait(sb + B_PUB, 0);
            if (lane == 0) {
                asm volatile("fence.proxy.async.global;" ::: "memory");
                asm volatile("red.release.gpu.global.add.u32 [%0], 1;" ::"l"(p.s->ready + (cta >> 3) * 32) : "memory");
            }
            __syncwarp();
            __nanosleep(INIT_NS);
            wait_counter(p.s->ready + own * 32, want * 2u);
            mbar_arrive_elect(sb + B_INIT);
        } else {
            mbar_arrive_elect(sb + B_BL + 8 * (warp & 1));
            uint32_t k = warp == 3 ? 0 : 12;
#define PREFETCH_W() {                                                                                          \
                const char* src = (k >= 8 ? (const char*)p.wd + ((cta >> 5) * 2 + (k >> 1) - 4) * 229376        \
                                          : (const char*)((cta & 32) ? p.wu : p.wg) + ((cta >> 6) * 4 + (k >> 1)) * 229376) \
                                  + ((cta & 31) * 2 + (k & 1)) * 3584;                                          \
                asm volatile(ELECT "cp.async.bulk.prefetch.L2.global [%0], 3584;}" ::"l"(src) : "memory");      \
                k++; }
#pragma unroll 1
            while (k < PF_N0) {
                sleep_until<50>(tstart + PF_T0 + k * PF_GAP);
                __syncwarp();
                PREFETCH_W();
            }
            mbar_wait(sb + B_EPOCH, 0);
            const uint32_t par = (*(volatile uint32_t*)(smem + M_EPOCH) + 1u) & 1u;
            const uint32_t a0 = sb + 16384 + (lane >> 3) * 1028 + ((lane >> 2) & 1) * 144 + (lane & 3) * 32;
            const uint32_t retry = sb + B_RETRY + (warp & 1) * 240;
            uint32_t slot = warp, ph = 0, rph = 0;
            uint32_t j = ffn ? warp & 1 : 12;
#pragma unroll 1
            for (int step = warp; step < 32 || j < 12; step += 2) {
                if (step < 32) {
                    const uint32_t bar = sb + 8 * slot;
                    mbar_wait(bar + B_BL, ph);
#pragma unroll 1
                    while (__any_sync(0xffffffffu, stale_tags(a0 + slot * REGION, par) & 1u)) {
                        const int row = blk * 4096 + __shfl_sync(0xffffffffu, tab, step) * 128;
                        mbar_expect_tx_elect(retry, 16384);
                        tma2d_elect(sb + slot * REGION + 16384, &p.mAB, 0, row, retry);
                        tma2d_elect(sb + slot * REGION + 24576, &p.mAB, 0, row + 64, retry);
                        mbar_spin(retry, rph);
                        rph ^= 1u;
                    }
                    mbar_arrive_elect<4>(bar + B_FULL);
                }
                if (j < 12 && step >= FFN_S0 + j * FFN_W / 4 && __any_sync(0xffffffffu, mbar_test(sb + B_FREE + 2 * (j & 12), 0))) {
                    const uint32_t fb = sb + B_FFN + 4 * (j & 6);
                    if (!(j & 1)) mbar_expect_tx_elect(fb, 8192);
                    tma2d_elect(sb + 6 * REGION + ((j + 4) & 7) * 4096, j < 8 ? &p.mWg + (j & 1) : &p.mWd,
                                j < 8 ? (cta >> 1) * 32 : rank * 256, j < 8 ? rank * 256 + (j >> 1) * 64 : (cta >> 1) * 32 + j * 8 - 64, fb);
                    j += 2;
                }
                if (k < 12) PREFETCH_W();
                slot += 2;
                if (slot >= NSTAGE) { slot -= NSTAGE; ph ^= 1; }
            }
        }
    } else if (warp < 8) {
        const int t = tid - 128, w = warp - 4;
        if (t == 0) {
            *(volatile uint32_t*)(smem + M_EPOCH) = epoch;
            *(volatile unsigned int*)&p.s->epoch[cta] = epoch + 1;
        }
        mbar_arrive_if(sb + B_EPOCH, t == 0);
        const uint4 gw0 = ldg_nc<0>(p.gate_w + lane * 8), gw1 = ldg_nc<512>(p.gate_w + lane * 8);
        const uint4 rw0 = ldg_nc<0>(p.w_r + lane * 8), rw1 = ldg_nc<512>(p.w_r + lane * 8);
        mbar_wait(sb + B_EPOCH, 0);
        const uint32_t par = (*(volatile uint32_t*)(smem + M_EPOCH) + 1u) & 1u;
        mbar_wait(sb + B_F + 8 * ROUTER_C, 0);
        const int row0 = cta * 16 + w * 4;
        uint4 xr[8];
        {
            const char* xp = (const char*)p.x + (uint32_t)row0 * (D_ * 2) + lane * 16;
            xr[0] = ldg_nc<0>(xp);    xr[1] = ldg_nc<512>(xp);  xr[2] = ldg_nc<1024>(xp); xr[3] = ldg_nc<1536>(xp);
            xr[4] = ldg_nc<2048>(xp); xr[5] = ldg_nc<2560>(xp); xr[6] = ldg_nc<3072>(xp); xr[7] = ldg_nc<3584>(xp);
            float a[8];
#pragma unroll
            for (int i = 0; i < 4; i++) {
                const uint32_t xv[8] = {xr[2 * i].x, xr[2 * i].y, xr[2 * i].z, xr[2 * i].w,
                                        xr[2 * i + 1].x, xr[2 * i + 1].y, xr[2 * i + 1].z, xr[2 * i + 1].w};
                const uint32_t gv[8] = {gw0.x, gw0.y, gw0.z, gw0.w, gw1.x, gw1.y, gw1.z, gw1.w};
                const uint32_t rv[8] = {rw0.x, rw0.y, rw0.z, rw0.w, rw1.x, rw1.y, rw1.z, rw1.w};
                float u = 0.f, v = 0.f;
#pragma unroll
                for (int j = 0; j < 8; j++) {
                    const uint32_t pr = hmul2_bf16(xv[j], gv[j]);
                    u += bflo(pr); u += bfhi(pr);
                    v = fmaf(bflo(xv[j]), bflo(rv[j]), v); v = fmaf(bfhi(xv[j]), bfhi(rv[j]), v);
                }
                a[i] = u; a[4 + i] = v;
            }
            mbar_wait(sb + B_EARLY, 0);
            halve<4, 16>(a); halve<2, 8>(a); halve<1, 4>(a);
            a[0] += __shfl_xor_sync(0xffffffffu, a[0], 1);
            a[0] += __shfl_xor_sync(0xffffffffu, a[0], 2);
            const int row = row0 + ((lane >> 2) & 3);
            const float gate = rbf(sigmoidf_(rbf(a[0])));
            if (lane < 16 && (lane & 3) == 0)
                asm volatile("st.relaxed.gpu.global.u32 [%0], %1;" ::"l"(&p.s->gate[row]), "r"(tagf(gate, par)) : "memory");
            const uint32_t best = __reduce_max_sync(0xffffffffu, lane >= 16 ? router_key(a[0], row) : 0u);
            if (lane == 0) *(volatile uint32_t*)(smem + M_KEY + w * 4) = best;
            side_bar();
            if (t < 8) {
                const uint4 k = *(const uint4*)(smem + M_KEY);
                asm volatile("{.reg .b32 old; atom.relaxed.gpu.global.exch.b32 old, [%0], %1;}" ::"l"(&p.s->keys[t * NCTA + cta]),
                             "r"(max(max(k.x, k.y), max(k.z, k.w)) | (par << 15)) : "memory");
            }
            const uint32_t og = pack_bf16(1.f - gate, 1.f - gate);
#pragma unroll
            for (int i = 0; i < 8; i++) {
                const uint32_t o = __shfl_sync(0xffffffffu, og, 4 * (i >> 1));
                xr[i] = make_uint4(hmul2_bf16(o, xr[i].x), hmul2_bf16(o, xr[i].y), hmul2_bf16(o, xr[i].z), hmul2_bf16(o, xr[i].w));
            }
        }
        mbar_wait(sb + B_FREE, 0);
        __nanosleep(KEY_NS);
        if (w == 0) {
            const uint4 k4 = wait_tags(p.s->keys + gpc * NCTA + lane * 4, 15, par);
            const uint32_t k = __reduce_max_sync(0xffffffffu, max(max(k4.x, k4.y), max(k4.z, k4.w)));
            sts128<M_XS>(sb + lane * 16, ldg_nc<0>(p.x + (0x7fff - (k & 0x7fffu)) * D_ + rank * 256 + lane * 8));
        } else if (w == 1) {
            const uint4 g4 = wait_tags(p.s->gate + own * 128 + lane * 4, 0, par);
            const uint32_t sg = comp ? 0x80000000u : 0u;
            sts128<M_G>(sb + lane * 16, make_uint4((g4.x & ~1u) ^ sg, (g4.y & ~1u) ^ sg, (g4.z & ~1u) ^ sg, (g4.w & ~1u) ^ sg));
            mbar_arrive_warp(sb + B_GATE);
        }
        side_bar();
        char* op = (char*)p.out + (uint32_t)row0 * (D_ * 2) + lane * 16;
        float a[16];
#pragma unroll
        for (int i = 0; i < 16; i++) a[i] = 0.f;
#pragma unroll 1
        for (int i = 0; i < 4; i++) {
            if (i == 2) {
                mbar_wait(sb + B_FREE + 8, 0);
                const uint32_t t2 = clk() + w * (INIT_GAP / 4);
#pragma unroll
                for (int j = 0; j < 8; j++) {
                    sleep_until<20>(t2 + j * INIT_GAP);
                    *(uint4*)(op + j * 512) = xr[j];
                }
                mbar_arrive_warp(sb + B_PUB);
            }
            if (ffn) {
                const float xs0 = __bfloat162float(((const bf16*)(smem + M_XS))[64 * i + (t >> 2)]);
                const float xs1 = __bfloat162float(((const bf16*)(smem + M_XS))[64 * i + 32 + (t >> 2)]);
                const uint32_t wa = sb + 6 * REGION + (i ^ 2) * 8192 + t * 16;
                mbar_wait(sb + B_FFN + 8 * i, 0);
                const uint4 v0 = lds128(wa), v1 = lds128(wa + 4096), v2 = lds128(wa + 2048), v3 = lds128(wa + 6144);
                const uint32_t w0[8] = {v0.x, v0.y, v0.z, v0.w, v1.x, v1.y, v1.z, v1.w};
                const uint32_t w1[8] = {v2.x, v2.y, v2.z, v2.w, v3.x, v3.y, v3.z, v3.w};
#pragma unroll
                for (int k = 0; k < 8; k++) {
                    a[2 * k] = fmaf(xs1, bflo(w1[k]), fmaf(xs0, bflo(w0[k]), a[2 * k]));
                    a[2 * k + 1] = fmaf(xs1, bfhi(w1[k]), fmaf(xs0, bfhi(w0[k]), a[2 * k + 1]));
                }
                if (i == 1) {
                    side_bar();
                    mbar_arrive_if(sb + B_FREE + 16, t == 0);
                }
            }
        }
        if (!ffn) {
            mbar_arrive_warp(sb + B_LOW);
            return;
        }
        halve<8, 16>(a); halve<4, 8>(a); halve<2, 4>(a);
        const uint32_t ho = (lane >> 4) * 128 + (lane & 3) * 32 + ((lane >> 2) & 3) * 8;
        cluster_wait();
#pragma unroll
        for (int k = 0; k < 2; k++)
            asm volatile("st.async.weak.shared::cluster.mbarrier::complete_tx::bytes.v2.f32 [%0], {%1,%2}, [%3];"
                         ::"r"(mapa(sb + (k ? 6 * REGION + w * 512 : M_HX + w * 256) + ho, rank ^ k ^ 1)), "f"(a[0]), "f"(a[1]),
                           "r"(mapa(sb + B_HX, rank ^ k ^ 1)) : "memory");
        mbar_wait_cluster(sb + B_HX, 0);
        const float *hx = (const float*)(smem + M_HX) + lane, *hy = (const float*)(smem + 6 * REGION) + lane;
        const float gs = rbf(((hx[0] + hy[0]) + (hx[64] + hy[128])) + ((hx[128] + hy[256]) + (hx[192] + hy[384])));
        const float us = rbf(((hx[32] + hy[32]) + (hx[96] + hy[160])) + ((hx[160] + hy[288]) + (hx[224] + hy[416])));
        float* hrow = (float*)(smem + M_XS) + w * 32;
        hrow[lane] = rbf(rbf(gs * sigmoidf_(gs)) * us);
        fence_proxy_async_smem();
        mbar_arrive_warp(sb + B_LOW);
        float o0 = 0.f, o1 = 0.f;
#pragma unroll 1
        for (int i = 0; i < 2; i++) {
            float4 hv[4];
            uint32_t vd[16];
#pragma unroll
            for (int k = 0; k < 4; k++) hv[k] = *(const float4*)&hrow[i * 16 + k * 4];
            mbar_wait(sb + B_FFN + 8 * i, 1);
#pragma unroll
            for (int k = 0; k < 16; k++) vd[k] = *(const volatile uint32_t*)(smem + 6 * REGION + 16384 + i * 8192 + k * 512 + t * 4);
#pragma unroll
            for (int k = 0; k < 4; k++) {
                o0 = fmaf(hv[k].x, bflo(vd[4 * k]), o0);     o1 = fmaf(hv[k].x, bfhi(vd[4 * k]), o1);
                o0 = fmaf(hv[k].y, bflo(vd[4 * k + 1]), o0); o1 = fmaf(hv[k].y, bfhi(vd[4 * k + 1]), o1);
                o0 = fmaf(hv[k].z, bflo(vd[4 * k + 2]), o0); o1 = fmaf(hv[k].z, bfhi(vd[4 * k + 2]), o1);
                o0 = fmaf(hv[k].w, bflo(vd[4 * k + 3]), o0); o1 = fmaf(hv[k].w, bfhi(vd[4 * k + 3]), o1);
            }
        }
        asm volatile("st.relaxed.gpu.global.v2.u32 [%0], {%1,%2};" ::"l"(&p.s->part[(cta >> 1) * D_ + rank * 256 + t * 2]),
                     "r"(tagf(o0, par)), "r"(tagf(o1, par)) : "memory");
        red_inc_if(p.s->phint + ((rank * 2 + (w >> 1)) * 16 + (cta >> 3)) * 8 + lane, lane == 0);
    } else {
        const int wg = (warp >> 2) - 2, wq = warp & 3;
        const uint32_t sbd = ((sb & 0x3FFFF) >> 4) + 0x10000;
        const bool lead = (tid & 127) == 0;
        const bool lead0 = lead && !wg, lead1 = lead && wg;
        const int q = lane & 3;
        float acc[64];
        const uint32_t rE = mapa(sb + B_EMPTY, rank ^ 1);
#define RELEASE(n, slot, pred) release_pair<n>(sb + B_EMPTY + 8 * (slot), rE + 8 * (slot), pred)
        const uint32_t ioff = wq * 4096 + (lane >> 2) * 64 + ((q ^ (lane >> 3)) << 4);
        const uint32_t sdst = pin(sb + 6 * REGION + (wg ? 0 : 16384) + ioff);
        unsigned char* gdst = pin(p.s->ab + (blk * 32 + own) * 16384 + ioff);
        unsigned int* hint = pin(p.s->hint + (blk * 4 + ((own >> 1) & 3)) * 32 + rank + lane);
        uint32_t par = 0;
#define GET_PAR() mbar_spin(sb + B_EPOCH, 0); par = (*(volatile uint32_t*)(smem + M_EPOCH) + 1u) & 1u
        cluster_wait();
        if (wg) mbar_spin(sb + B_G0, 0);
#pragma unroll
        for (int c = 0; c < 8; c++) {
            if (c == 1 && wg) {
                wg_wait<0>();
                RELEASE(1, 1, lead);
                GET_PAR();
                mbar_spin(sb + B_G1, 0);
            }
            if (!wg || c < 3 || c == 4) mbar_spin(sb + (!wg || c == 0 ? B_F + 8 * c : c == 1 ? B_GO1 : c == 2 ? B_G2 : B_G4), 0);
            const uint32_t xa = sbd + wg * ((off_xl(c) - off_xe(c)) / 16);
            wg_fence();
#pragma unroll
            for (int kk = 0; kk < 4; kk++) {
                wgmma128<0>(acc, desc128(xa + off_xe(c) / 16 + 2 * kk), desc128(sbd + off_d(c) / 16 + 2 * kk), (c | kk) != 0);
                if (c == 7 && kk == 0) wg_commit();
            }
            wg_commit();
            if (c == 3 && !wg) { GET_PAR(); }
            if (c == 7) {
                if (wg) mbar_spin(sb + B_FULL, 0);
                wg_wait<2>();
                mbar_arrive_if(sb + B_GO1, lead0);
            }
            if (c == 4 || c >= 6) wg_wait<1>();
            if (c == 4) { mbar_arrive_if(sb + B_XE, lead0); RELEASE(1, 1, lead0); RELEASE(2, 2, lead1); RELEASE(2, 3, lead1); }
            if (c == 6) RELEASE(2, 4 * wg, lead);
            if (c == 7) mbar_arrive_if(sb + B_GO0, lead1);
        }
        const int rh = wg ^ comp;
        const uint32_t da0 = sbd + rh * 512, db0 = sbd - 0x10000 + 0x400000 + 1024;
        const uint32_t dbe = db0 + 6 * (REGION / 16), dbl = dbe - 1024;
#define STEP(da, db, first) wg_fence();                                                                     \
        _Pragma("unroll") for (int kk = 0; kk < 4; kk++)                                                    \
            wgmma128<1>(acc, desc128((da) + kk * 2), desc64((db) + kk * 256), !((first) && kk == 0));       \
        wg_commit()
#define ACC(i, j) (16 * ((i) >> 1) + 2 * ((i) & 1) + 4 * (j))
#define PW(i, j) pack_bf16(acc[ACC(i, j)], acc[ACC(i, j) + 1])
#define PT(i, j) ((j) == ((i) >> 1) ? (PW(i, j) & ~1u) | par : PW(i, j))
#define PIECE(i) make_uint4(PT(i, 0), PT(i, 1), PT(i, 2), PT(i, 3))
#define PIECES(F) F(0); F(1); sched_cut(); F(2); F(3); F(4); F(5); F(6); F(7)
        if (wg) {
            wg_wait<0>();
            fence_regs(acc);
#define STS1(i) sts128<(i) * 512>(sdst, PIECE(i))
            PIECES(STS1);
            STEP(da0, dbe, true);
            fence_proxy_async_smem();
            mbar_arrive_warp(sb + B_FULL + 8);
            RELEASE(1, 5, lead);
        } else {
            wg_wait<0>();
            fence_regs(acc);
            uint4 v[8];
#define STG0(i) v[i] = PIECE(i); stg128<(i) * 512>(gdst, v[i]); if (HINT_AT == (i) + 1) red_inc_if(hint, own < 6 && lane == 0)
            PIECES(STG0);
#define STS0(i) mbar_spin(sb + B_EPOCH, 0); sts128<(i) * 512>(sdst, v[i])
            STS0(0); STS0(1); STS0(2); STS0(3); STS0(4); STS0(5); STS0(6); STS0(7);
            fence_proxy_async_smem();
            mbar_arrive_warp(sb + B_FULL);
            RELEASE(1, 5, lead);
            mbar_arrive_if(sb + B_EARLY, lead);
            mbar_spin(sb + B_FULL, 0);
            mbar_spin(sb + B_GO0, 0);
            STEP(da0, dbe, true);
        }
#pragma unroll
        for (int step = 1; step < 3; step++) {
            mbar_spin(sb + B_FULL + 8 * step, 0);
            STEP(da0 + step * (REGION / 16), step == 1 ? dbl : db0 + step * (REGION / 16), false);
            wg_wait<1>();
            RELEASE(1, step - 1, lead);
            mbar_arrive_if(sb + B_FREE + 8 * (step - 1), lead);
        }
        int slot = 3, ph = 0, pslot = 2;
        float g0 = 0.f, g1 = 0.f;
        uint32_t oa = 0;
        const int lend = 33 - NSTAGE - (SK == NSTAGE && wg);
#pragma unroll 1
        for (int step = 3; step < lend; step++) {
            mbar_wait(sb + B_FULL + 8 * slot, ph);
            STEP(da0 + slot * (REGION / 16), db0 + slot * (REGION / 16), false);
            if (step == 22 + wg) {
                const int r0 = rh * 64 + wq * 16 + (lane >> 2), sr = ((lane >> 2) & 1) * 4 + (lane >> 3);
                mbar_wait(sb + B_GATE, 0);
                g0 = ((const volatile float*)(smem + M_G))[r0];
                g1 = ((const volatile float*)(smem + M_G))[r0 + 8];
                oa = pin(wg ? ((own * 128 + (r0 & ~1)) * D_ + tn * 128 + (lane & 7) * 8) * 2u
                            : sb + rh * 8192 + wq * 2048 + sr * 128 + ((q ^ sr) << 4));
            }
            wg_wait<1>();
            RELEASE(1, pslot, lead);
            pslot = slot;
            if (++slot == NSTAGE) { slot = 0; ph ^= 1; }
        }
        if (SK == NSTAGE && wg) { wg_wait<0>(); RELEASE(1, pslot, lead); }
#pragma unroll 1
        for (int step = lend; step < 32; step++) {
            if (wg && step == 32 - SK) {
                mbar_wait(sb + B_INIT, 0);
                mbar_wait(sb + B_TAIL, 0);
            }
            if (!wg || step < 32 - SK) mbar_wait(sb + B_FULL + 8 * slot, ph);
            STEP(da0 + (step < 32 - NA ? slot : step == 32 - NA ? 6 : pslot) * (REGION / 16), db0 + slot * (REGION / 16), false);
            pslot = slot;
            if (++slot == NSTAGE) { slot = 0; ph ^= 1; }
        }
#define OW(i, j) pack_bf16((((i) & 1) ? g1 : g0) * acc[ACC(i, j)], (((i) & 1) ? g1 : g0) * acc[ACC(i, j) + 1])
        if (!wg) {
            wg_wait<1>();
            mbar_arrive_if(sb + B_TAIL, lead);
            const uint32_t st0 = sb + rh * 8192 + wq * 2048;
            mbar_wait(sb + B_INIT, 0);
            wg_wait<0>();
            fence_regs(acc);
#define OSTS(i) sts128<((i) >> 2) * REGION + ((i) & 1) * 1024>(((i) & 2) ? oa ^ 64 : oa, make_uint4(OW(i, 0), OW(i, 1), OW(i, 2), OW(i, 3)))
#define ORED(h) fence_proxy_async_smem(); __syncwarp();                                                     \
            asm volatile(ELECT "cp.reduce.async.bulk.tensor.4d.global.shared::cta.add.tile.bulk_group [%0, {%2,%3,%3,%4}], [%1];}" \
                         ::"l"(&p.mOut), "r"(st0 + (h) * REGION), "r"(tn * 128 + (h) * 64), "r"(0), "r"(own * 16 + rh * 8 + wq * 2) : "memory")
            OSTS(0); OSTS(1); OSTS(2); OSTS(3);
            ORED(0);
            sched_cut();
            OSTS(4); OSTS(5); OSTS(6); OSTS(7);
            ORED(1);
            bulk_wait_read();
        } else {
            const bool odd = lane & 4;
            char *op = pin((char*)p.out + oa), *opb = pin((char*)p.out + (oa ^ 64) + 1024);
            sched_cut();
            wg_wait<0>();
            fence_regs(acc);
#define REDLINE(i) {                                                                                        \
                uint32_t k[4], r[4];                                                                        \
                _Pragma("unroll") for (int j = 0; j < 4; j++) {                                             \
                    r[j] = __shfl_xor_sync(0xffffffffu, OW((i) + 2, j), 4);                                 \
                    k[j] = OW(i, j);                                                                        \
                }                                                                                           \
                red_bf16x8<((i) & 1) * 8192 + ((i) >> 2) * 128>(op, odd ? r[0] : k[0], odd ? r[1] : k[1], odd ? r[2] : k[2], odd ? r[3] : k[3]);  \
                red_bf16x8<((i) & 1) * 8192 + ((i) >> 2) * 128>(opb, odd ? k[0] : r[0], odd ? k[1] : r[1], odd ? k[2] : r[2], odd ? k[3] : r[3]); }
            REDLINE(0)
            sched_cut();
            REDLINE(1) REDLINE(4) REDLINE(5)
        }
    }
}

typedef CUresult (*EncodeTiledFn)(CUtensorMap*, CUtensorMapDataType, cuuint32_t, void*, const cuuint64_t*, const cuuint64_t*,
                                  const cuuint32_t*, const cuuint32_t*, CUtensorMapInterleave, CUtensorMapSwizzle,
                                  CUtensorMapL2promotion, CUtensorMapFloatOOBfill);

static void make_map(EncodeTiledFn enc, CUtensorMap* m, const void* base, uint64_t cols, uint64_t rows, uint32_t box_rows,
                     CUtensorMapSwizzle sw = CU_TENSOR_MAP_SWIZZLE_128B, uint32_t box_cols = 64) {
    cuuint64_t dims[2] = {cols, rows};
    cuuint64_t str[1] = {cols * 2};
    cuuint32_t box[2] = {box_cols, box_rows};
    cuuint32_t es[2] = {1, 1};
    enc(m, CU_TENSOR_MAP_DATA_TYPE_BFLOAT16, 2, (void*)base, dims, str, box, es, CU_TENSOR_MAP_INTERLEAVE_NONE,
        sw, CU_TENSOR_MAP_L2_PROMOTION_L2_128B, CU_TENSOR_MAP_FLOAT_OOB_FILL_NONE);
}

static void make_map_chunks(EncodeTiledFn enc, CUtensorMap* m, const void* base, uint64_t rows, uint32_t box_rows, uint32_t n = 1) {
    cuuint64_t dims[3] = {64, rows, 8};
    cuuint64_t str[2] = {D_ * 2, 128};
    cuuint32_t box[3] = {64, box_rows, n};
    cuuint32_t es[3] = {1, 1, 1};
    enc(m, CU_TENSOR_MAP_DATA_TYPE_BFLOAT16, 3, (void*)base, dims, str, box, es, CU_TENSOR_MAP_INTERLEAVE_NONE,
        CU_TENSOR_MAP_SWIZZLE_128B, CU_TENSOR_MAP_L2_PROMOTION_L2_128B, CU_TENSOR_MAP_FLOAT_OOB_FILL_NONE);
}

static void make_map_out(EncodeTiledFn enc, CUtensorMap* m, const void* base) {
    cuuint64_t dims[4] = {D_, 4, 2, S_ / 8};
    cuuint64_t str[3] = {2 * D_ * 2, D_ * 2, 8 * D_ * 2};
    cuuint32_t box[4] = {64, 4, 2, 2};
    cuuint32_t es[4] = {1, 1, 1, 1};
    enc(m, CU_TENSOR_MAP_DATA_TYPE_BFLOAT16, 4, (void*)base, dims, str, box, es, CU_TENSOR_MAP_INTERLEAVE_NONE,
        CU_TENSOR_MAP_SWIZZLE_128B, CU_TENSOR_MAP_L2_PROMOTION_NONE, CU_TENSOR_MAP_FLOAT_OOB_FILL_NONE);
}

extern "C" void kernel_launch(void* const* d_in, const int* in_sizes, int n_in, void* d_out, int out_size) {
    (void)in_sizes; (void)n_in; (void)out_size;
    static EncodeTiledFn enc = nullptr;
    static bool fused_ok = false;
    static void* scratch = nullptr;
    if (!enc) {
        void* fn = nullptr;
        cudaDriverEntryPointQueryResult q;
        cudaGetDriverEntryPoint("cuTensorMapEncodeTiled", &fn, cudaEnableDefault, &q);
        enc = (EncodeTiledFn)fn;
        cudaGetSymbolAddress(&scratch, g_s);
        cudaFuncSetAttribute(fused_kernel, cudaFuncAttributeMaxDynamicSharedMemorySize, SMEM_BYTES);
        int dev = 0, nsm = 0, ncl = 0;
        cudaGetDevice(&dev);
        cudaDeviceGetAttribute(&nsm, cudaDevAttrMultiProcessorCount, dev);
        cudaLaunchConfig_t cfg = {};
        cfg.gridDim = dim3(132); cfg.blockDim = dim3(NTHREADS); cfg.dynamicSmemBytes = SMEM_BYTES;
        cudaLaunchAttribute at;
        at.id = cudaLaunchAttributeClusterDimension;
        at.val.clusterDim.x = 2; at.val.clusterDim.y = 1; at.val.clusterDim.z = 1;
        cfg.attrs = &at; cfg.numAttrs = 1;
        fused_ok = cudaOccupancyMaxActiveClusters(&ncl, fused_kernel, &cfg) == cudaSuccess && nsm == 132 && ncl == 66;
        (void)cudaGetLastError();
    }
    if (!fused_ok) {
        const bf16* const* in = (const bf16* const*)d_in;
        fb_hidden<<<S_, D_, 0, cudaStreamPerThread>>>(in[0], in[3], in[4], in[10], in[6]);
        fb_ffn1<<<F_ / 128, 128, 0, cudaStreamPerThread>>>(in[0], in[7], in[8]);
        fb_ffn2<<<D_ / 64, 64, 0, cudaStreamPerThread>>>(in[9]);
        fb_seq<<<S_, D_, 0, cudaStreamPerThread>>>(in[0], in[1], in[2], (bf16*)d_out);
        return;
    }
    Params p;
    p.s = (Scratch*)scratch;
    p.x = (const bf16*)d_in[0];
    p.w_r = (const bf16*)d_in[6];
    p.wg = (const bf16*)d_in[7];
    p.wu = (const bf16*)d_in[8];
    p.wd = (const bf16*)d_in[9];
    p.gate_w = (const bf16*)d_in[10];
    p.out = (bf16*)d_out;
    make_map_chunks(enc, &p.mX1, d_in[0], S_, 64);
    make_map_chunks(enc, &p.mX2, d_in[0], S_, 64, 2);
    make_map(enc, &p.mCre, d_in[1], S_, S_, 128);
    make_map(enc, &p.mCim, d_in[2], S_, S_, 128);
    make_map_chunks(enc, &p.mDre, d_in[3], D_, 128);
    make_map_chunks(enc, &p.mDim, d_in[4], D_, 128);
    make_map(enc, &p.mAB, scratch, 64, 8 * 32 * 128, 64, CU_TENSOR_MAP_SWIZZLE_NONE);
    make_map_out(enc, &p.mOut, d_out);
    make_map(enc, &p.mWg, d_in[7], F_, D_, 64, CU_TENSOR_MAP_SWIZZLE_NONE, 32);
    make_map(enc, &p.mWu, d_in[8], F_, D_, 64, CU_TENSOR_MAP_SWIZZLE_NONE, 32);
    make_map(enc, &p.mWd, d_in[9], D_, F_, 8, CU_TENSOR_MAP_SWIZZLE_NONE, 256);
    fused_kernel<<<132, NTHREADS, SMEM_BYTES, cudaStreamPerThread>>>(p);
}
```

```cpp
#include <cuda_runtime.h>
#include <cuda.h>
#include <cuda_bf16.h>
#include <stdint.h>

typedef __nv_bfloat16 bf16;

constexpr int S_ = 2048, D_ = 512, F_ = 1792;
constexpr int NCTA = 128;
constexpr int NTHREADS = 512;
constexpr int NSTAGE = 6;
constexpr int REGION = 32768;
constexpr int FFN_CTAS = F_ / 16;
constexpr uint32_t SPIN_LIMIT = 1u << 22;
constexpr int PACE = 260;
constexpr int PACE0 = 100;
constexpr int A_GAP = 260;
constexpr int B_GAP = 280;
constexpr int LATE_GAP = 240;
constexpr int INIT_GAP = 360;
constexpr int INIT_NS = 300;
constexpr int PF_T0 = 3000;
constexpr int PF_GAP = 850;
constexpr int PF_N0 = 4;
constexpr int FFN_S0 = 4;
constexpr int FFN_W = 7;
constexpr int ROUTER_C = 4;
constexpr int HINT_AT = 5;
constexpr int SUM_T0 = 15000;
constexpr int PS1 = 24;
constexpr int NA = 3;
constexpr int KEY_NS = 300;
constexpr int HSK = 2;

constexpr int OFF_MISC = 7 * REGION;
constexpr int B_F = OFF_MISC;
constexpr int B_G1 = B_F + 64;
constexpr int B_G4 = B_G1 + 8;
constexpr int B_XE = B_G4 + 8;
constexpr int B_GO1 = B_XE + 8;
constexpr int B_GO0 = B_GO1 + 8;
constexpr int B_EPOCH = B_GO0 + 8;
constexpr int B_RETRY = B_EPOCH + 8;
constexpr int B_INIT = B_RETRY + 8;
constexpr int B_FULL = B_INIT + 8;
constexpr int B_EMPTY = B_FULL + 48;
constexpr int B_PUB = B_EMPTY + 48;
constexpr int B_FREE = B_PUB + 8;
constexpr int B_BL = B_FREE + 24;
constexpr int B_TAIL = B_BL + 48;
constexpr int B_HX = B_TAIL + 8;
constexpr int B_FFN = B_HX + 8;
constexpr int B_ROLE = B_FFN + 40;
constexpr int B_EARLY = B_ROLE + 8;
constexpr int B_GATE = B_EARLY + 8;
constexpr int B_G2 = B_GATE + 8;
constexpr int B_LOW = B_G2 + 8;
constexpr int B_G0 = B_LOW + 8;
constexpr int M_EPOCH = B_G0 + 8;
constexpr int M_ROLE = M_EPOCH + 4;
constexpr int M_KEY = OFF_MISC + 416;
constexpr int M_HX = OFF_MISC + 512;
constexpr int M_G = M_HX + 1024;
constexpr int M_XS = M_G + 512;
constexpr int SMEM_BYTES = 232448;
static_assert(M_ROLE + 4 <= M_KEY && M_XS + 512 <= SMEM_BYTES, "smem");

struct Scratch {
    unsigned char ab[8 * 32 * 16384];
    unsigned int hint[8 * 4 * 32];
    unsigned int ready[16 * 32];
    unsigned int gate[S_];
    unsigned int part[FFN_CTAS / 2 * D_];
    unsigned int phint[4 * 16 * 8];
    unsigned int keys[8 * NCTA];
    unsigned int epoch[NCTA + 4];
};
__device__ __align__(1024) Scratch g_s;

struct Params {
    Scratch* s;
    bf16* out;
    const bf16 *x, *gate_w, *w_r, *wg, *wu, *wd;
    CUtensorMap mDre, mDim, mX1, mX2, mCre, mCim, mAB, mOut, mWg, mWu, mWd;
};

#define ELECT "{.reg .pred p; elect.sync _|p, 0xffffffff; @p "
__device__ __forceinline__ uint32_t smem_u32(const void* p) { return (uint32_t)__cvta_generic_to_shared(p); }
__device__ __forceinline__ uint32_t clk() { return (uint32_t)clock64(); }
__device__ __forceinline__ void spin_until(uint32_t t) { while ((int)(clk() - t) < 0) {} }
template <int NS>
__device__ __forceinline__ void sleep_until(uint32_t t) { while ((int)(clk() - t) < 0) __nanosleep(NS); }
__device__ __forceinline__ void mbar_init_elect(uint32_t bar, uint32_t cnt) {
    asm volatile(ELECT "mbarrier.init.shared::cta.b64 [%0], %1;}" ::"r"(bar), "r"(cnt) : "memory");
}
__device__ __forceinline__ void mbar_expect_tx_elect(uint32_t bar, uint32_t bytes) {
    asm volatile(ELECT "mbarrier.arrive.expect_tx.shared::cta.b64 _, [%0], %1;}" ::"r"(bar), "r"(bytes) : "memory");
}
template <int N = 1>
__device__ __forceinline__ void mbar_arrive_elect(uint32_t bar) {
    asm volatile(ELECT "mbarrier.arrive.shared::cta.b64 _, [%0], %1;}" ::"r"(bar), "n"(N) : "memory");
}
__device__ __forceinline__ void mbar_arrive_if(uint32_t bar, bool pred) {
    asm volatile("{.reg .pred p; setp.ne.b32 p, %1, 0; @p mbarrier.arrive.shared::cta.b64 _, [%0];}" ::"r"(bar), "r"((int)pred) : "memory");
}
__device__ __forceinline__ void mbar_arrive_warp(uint32_t bar) {
    __syncwarp();
    mbar_arrive_if(bar, (threadIdx.x & 31) == 0);
}
template <int N>
__device__ __forceinline__ void release_pair(uint32_t bar, uint32_t rbar, bool pred) {
    asm volatile("{.reg .pred p; setp.ne.b32 p, %2, 0; @p mbarrier.arrive.shared::cta.b64 _, [%0], %3;"
                 " @p mbarrier.arrive.shared::cluster.b64 _, [%1], %3;}" ::"r"(bar), "r"(rbar), "r"((int)pred), "n"(N) : "memory");
}
__device__ __forceinline__ uint32_t mapa(uint32_t a, uint32_t cta) {
    uint32_t r;
    asm volatile("mapa.shared::cluster.u32 %0, %1, %2;" : "=r"(r) : "r"(a), "r"(cta));
    return r;
}
__device__ __forceinline__ bool mbar_test(uint32_t bar, uint32_t parity) {
    uint32_t ok;
    asm volatile("{.reg .pred p; mbarrier.test_wait.parity.shared::cta.b64 p, [%1], %2; selp.u32 %0,1,0,p;}"
                 : "=r"(ok) : "r"(bar), "r"(parity) : "memory");
    return ok;
}
__device__ __forceinline__ void mbar_wait(uint32_t bar, uint32_t parity) {
    asm volatile("{.reg .pred p, q; .reg .u32 n; mov.u32 n, 0;\n"
                 "W%=: mbarrier.try_wait.parity.shared::cta.b64 p, [%0], %1;\n"
                 "add.u32 n, n, 1; setp.lt.and.u32 q, n, %2, !p; @q bra W%=; @!p trap;}" ::"r"(bar), "r"(parity), "n"(SPIN_LIMIT) : "memory");
}
__device__ __forceinline__ void mbar_wait_cluster(uint32_t bar, uint32_t parity) {
    asm volatile("{.reg .pred p, q; .reg .u32 n; mov.u32 n, 0;\n"
                 "W%=: mbarrier.try_wait.parity.acquire.cluster.shared::cta.b64 p, [%0], %1;\n"
                 "add.u32 n, n, 1; setp.lt.and.u32 q, n, %2, !p; @q bra W%=; @!p trap;}" ::"r"(bar), "r"(parity), "n"(SPIN_LIMIT) : "memory");
}
__device__ __forceinline__ void mbar_spin(uint32_t bar, uint32_t parity) {
    asm volatile("{.reg .pred p;\nW%=: mbarrier.try_wait.parity.shared::cta.b64 p, [%0], %1; @!p bra W%=;}" ::"r"(bar), "r"(parity) : "memory");
}
__device__ __forceinline__ void cluster_arrive() { asm volatile("barrier.cluster.arrive.relaxed.aligned;" ::: "memory"); }
__device__ __forceinline__ void cluster_wait() { asm volatile("barrier.cluster.wait.acquire.aligned;" ::: "memory"); }
__device__ __forceinline__ void side_bar() { asm volatile("bar.sync 1, 128;" ::: "memory"); }
__device__ __forceinline__ void tma2d_elect(uint32_t dst, const CUtensorMap* m, int c0, int c1, uint32_t bar) {
    asm volatile(ELECT "cp.async.bulk.tensor.2d.shared::cluster.global.mbarrier::complete_tx::bytes [%0], [%1, {%3,%4}], [%2];}"
                 ::"r"(dst), "l"(m), "r"(bar), "r"(c0), "r"(c1) : "memory");
}
__device__ __forceinline__ void tma2d_pair_elect(uint32_t dst, const CUtensorMap* m, int c0, int c1, uint32_t bar) {
    asm volatile(ELECT "cp.async.bulk.tensor.2d.shared::cluster.global.mbarrier::complete_tx::bytes.multicast::cluster"
                 " [%0], [%1, {%3,%4}], [%2], %5;}" ::"r"(dst), "l"(m), "r"(bar), "r"(c0), "r"(c1), "h"((uint16_t)3) : "memory");
}
__device__ __forceinline__ void tma3d_elect(uint32_t dst, const CUtensorMap* m, int row, int chunk, uint32_t bar) {
    asm volatile(ELECT "cp.async.bulk.tensor.3d.shared::cluster.global.mbarrier::complete_tx::bytes [%0], [%1, {%3,%4,%5}], [%2];}"
                 ::"r"(dst), "l"(m), "r"(bar), "r"(0), "r"(row), "r"(chunk) : "memory");
}
__device__ __forceinline__ void bulk_wait_read() {
    asm volatile("cp.async.bulk.commit_group; cp.async.bulk.wait_group.read 0;" ::: "memory");
    __syncwarp();
}
__device__ __forceinline__ void fence_proxy_async_smem() { asm volatile("fence.proxy.async.shared::cta;" ::: "memory"); }
__device__ __forceinline__ uint32_t ld_relaxed(const void* p) {
    uint32_t v;
    asm volatile("ld.relaxed.gpu.global.u32 %0, [%1];" : "=r"(v) : "l"(p) : "memory");
    return v;
}
__device__ __forceinline__ uint4 ld_relaxed4(const void* p) {
    uint4 v;
    asm volatile("ld.relaxed.gpu.global.v4.u32 {%0,%1,%2,%3}, [%4];" : "=r"(v.x), "=r"(v.y), "=r"(v.z), "=r"(v.w) : "l"(p) : "memory");
    return v;
}
__device__ __forceinline__ void red_inc_if(unsigned int* p, bool pred) {
    asm volatile("{.reg .pred p; setp.ne.b32 p, %1, 0; @p red.relaxed.gpu.global.add.u32 [%0], 1;}" ::"l"(p), "r"((int)pred) : "memory");
}
__device__ __forceinline__ uint32_t tagf(float v, uint32_t par) { return (__float_as_uint(v) & ~1u) | par; }
__device__ __forceinline__ uint4 wait_tags(const unsigned int* p, int bit, uint32_t par) {
    uint32_t n = 0;
    while (true) {
        const uint4 v = ld_relaxed4(p);
        const uint32_t m = par ? (v.x & v.y & v.z & v.w) : ~(v.x | v.y | v.z | v.w);
        if (__all_sync(0xffffffffu, (m >> bit) & 1u)) return v;
        __nanosleep(100);
        if (++n > SPIN_LIMIT) __trap();
    }
}
__device__ __forceinline__ void wait_counter(const unsigned int* p, uint32_t want) {
    uint32_t n = 0;
    while (!__all_sync(0xffffffffu, (int)(ld_relaxed(p) - want) >= 0)) {
        __nanosleep(200);
        if (++n > SPIN_LIMIT) __trap();
    }
    asm volatile("fence.acquire.gpu;" ::: "memory");
}
__device__ __forceinline__ uint32_t stale_tags(uint32_t a, uint32_t par) {
    uint32_t r;
    asm volatile("{.reg .b32 v<16>;\n"
                 "ld.shared.u32 v0, [%1]; ld.shared.u32 v1, [%1+256]; ld.shared.u32 v2, [%1+512]; ld.shared.u32 v3, [%1+768];\n"
                 "ld.shared.u32 v4, [%1+4096]; ld.shared.u32 v5, [%1+4352]; ld.shared.u32 v6, [%1+4608]; ld.shared.u32 v7, [%1+4864];\n"
                 "ld.shared.u32 v8, [%1+8192]; ld.shared.u32 v9, [%1+8448]; ld.shared.u32 v10, [%1+8704]; ld.shared.u32 v11, [%1+8960];\n"
                 "ld.shared.u32 v12, [%1+12288]; ld.shared.u32 v13, [%1+12544]; ld.shared.u32 v14, [%1+12800]; ld.shared.u32 v15, [%1+13056];\n"
                 "lop3.b32 v0, v0, v1, %2, 0x7e; lop3.b32 v2, v2, v3, %2, 0x7e; lop3.b32 v4, v4, v5, %2, 0x7e; lop3.b32 v6, v6, v7, %2, 0x7e;\n"
                 "lop3.b32 v8, v8, v9, %2, 0x7e; lop3.b32 v10, v10, v11, %2, 0x7e; lop3.b32 v12, v12, v13, %2, 0x7e; lop3.b32 v14, v14, v15, %2, 0x7e;\n"
                 "lop3.b32 v0, v0, v2, v4, 0xfe; lop3.b32 v6, v6, v8, v10, 0xfe; lop3.b32 v0, v0, v6, v12, 0xfe; or.b32 %0, v0, v14;}"
                 : "=r"(r) : "r"(a), "r"(par) : "memory");
    return r;
}
template <int OFF>
__device__ __forceinline__ uint4 ldg_nc(const void* p) {
    uint4 v;
    asm volatile("ld.global.nc.v4.u32 {%0,%1,%2,%3}, [%4+%5];" : "=r"(v.x), "=r"(v.y), "=r"(v.z), "=r"(v.w) : "l"(p), "n"(OFF));
    return v;
}
template <int OFF>
__device__ __forceinline__ void stg128(void* p, const uint4& v) {
    asm volatile("st.global.v4.u32 [%0+%5], {%1,%2,%3,%4};" ::"l"(p), "r"(v.x), "r"(v.y), "r"(v.z), "r"(v.w), "n"(OFF) : "memory");
}
template <int OFF>
__device__ __forceinline__ void sts128(uint32_t a, const uint4& v) {
    asm volatile("st.shared.v4.u32 [%0+%5], {%1,%2,%3,%4};" ::"r"(a), "r"(v.x), "r"(v.y), "r"(v.z), "r"(v.w), "n"(OFF) : "memory");
}
__device__ __forceinline__ uint4 lds128(uint32_t a) {
    uint4 v;
    asm volatile("ld.shared.v4.u32 {%0,%1,%2,%3}, [%4];" : "=r"(v.x), "=r"(v.y), "=r"(v.z), "=r"(v.w) : "r"(a) : "memory");
    return v;
}
template <int OFF>
__device__ __forceinline__ void red_bf16x8(void* p, uint32_t x, uint32_t y, uint32_t z, uint32_t w) {
    asm volatile("red.relaxed.gpu.global.add.noftz.v4.bf16x2 [%0+%5], {%1,%2,%3,%4};"
                 ::"l"(p), "r"(x), "r"(y), "r"(z), "r"(w), "n"(OFF) : "memory");
}
__device__ __forceinline__ void sched_cut() {
    asm volatile("{.reg .pred p; .reg .u64 t; .reg .u32 a, b;\n"
                 "C%=: mov.u64 t, %%clock64; mov.b64 {a, b}, t; setp.eq.u32 p, a, %0; @p bra C%=;}" ::"n"(0) : "memory");
}
__device__ __forceinline__ uint32_t pin(uint32_t v) { return __shfl_xor_sync(0xffffffffu, v, 0); }
template <class T>
__device__ __forceinline__ T* pin(T* p) { return (T*)__shfl_xor_sync(0xffffffffu, (unsigned long long)p, 0); }
__device__ __forceinline__ float selpf(float a, float b, bool p) {
    float r;
    asm("{.reg .pred q; setp.ne.b32 q, %3, 0; selp.f32 %0, %1, %2, q;}" : "=f"(r) : "f"(a), "f"(b), "r"((int)p));
    return r;
}
template <int N, int MASK, int SZ>
__device__ __forceinline__ void halve(float (&a)[SZ]) {
    const bool up = threadIdx.x & MASK;
#pragma unroll
    for (int j = 0; j < N; j++) a[j] = selpf(a[N + j], a[j], up) + __shfl_xor_sync(0xffffffffu, selpf(a[j], a[N + j], up), MASK);
}
__device__ __forceinline__ float bflo(uint32_t u) { return __uint_as_float(u << 16); }
__device__ __forceinline__ float bfhi(uint32_t u) { return __uint_as_float(u & 0xffff0000u); }
__device__ __forceinline__ uint32_t pack_bf16(float lo, float hi) {
    uint32_t r;
    asm("cvt.rn.bf16x2.f32 %0, %1, %2;" : "=r"(r) : "f"(hi), "f"(lo));
    return r;
}
__device__ __forceinline__ uint32_t hmul2_bf16(uint32_t a, uint32_t b) {
    uint32_t r;
    asm("mul.rn.bf16x2 %0, %1, %2;" : "=r"(r) : "r"(a), "r"(b));
    return r;
}
__device__ __forceinline__ float rbf(float v) { return bflo(pack_bf16(v, 0.f)); }
__device__ __forceinline__ float sigmoidf_(float v) { return __fdividef(1.0f, 1.0f + __expf(-v)); }

__device__ __forceinline__ void wg_fence() { asm volatile("wgmma.fence.sync.aligned;" ::: "memory"); }
__device__ __forceinline__ void wg_commit() { asm volatile("wgmma.commit_group.sync.aligned;" ::: "memory"); }
template <int N> __device__ __forceinline__ void wg_wait() { asm volatile("wgmma.wait_group.sync.aligned %0;" ::"n"(N) : "memory"); }
__device__ __forceinline__ uint64_t desc128(uint32_t lo) { return (uint64_t)lo | (0x40000040ull << 32); }
__device__ __forceinline__ uint64_t desc64(uint32_t lo) { return (uint64_t)lo | (0x80000020ull << 32); }
__device__ __forceinline__ void fence_regs(float (&d)[64]) {
#pragma unroll
    for (int i = 0; i < 64; i++) asm volatile("" : "+f"(d[i])::"memory");
}
template <int TB>
__device__ __forceinline__ void wgmma128(float (&d)[64], uint64_t da, uint64_t db, int scaleD) {
    asm volatile(
        "{ .reg .pred p; setp.ne.b32 p, %66, 0;\n"
        "wgmma.mma_async.sync.aligned.m64n128k16.f32.bf16.bf16 "
        "{%0,%1,%2,%3,%4,%5,%6,%7,%8,%9,%10,%11,%12,%13,%14,%15,%16,%17,%18,%19,%20,%21,%22,%23,%24,%25,%26,%27,%28,%29,%30,%31,"
        "%32,%33,%34,%35,%36,%37,%38,%39,%40,%41,%42,%43,%44,%45,%46,%47,%48,%49,%50,%51,%52,%53,%54,%55,%56,%57,%58,%59,%60,%61,%62,%63}, "
        "%64, %65, p, 1, 1, 0, %67;\n}"
        : "+f"(d[0]), "+f"(d[1]), "+f"(d[2]), "+f"(d[3]), "+f"(d[4]), "+f"(d[5]), "+f"(d[6]), "+f"(d[7]),
          "+f"(d[8]), "+f"(d[9]), "+f"(d[10]), "+f"(d[11]), "+f"(d[12]), "+f"(d[13]), "+f"(d[14]), "+f"(d[15]),
          "+f"(d[16]), "+f"(d[17]), "+f"(d[18]), "+f"(d[19]), "+f"(d[20]), "+f"(d[21]), "+f"(d[22]), "+f"(d[23]),
          "+f"(d[24]), "+f"(d[25]), "+f"(d[26]), "+f"(d[27]), "+f"(d[28]), "+f"(d[29]), "+f"(d[30]), "+f"(d[31]),
          "+f"(d[32]), "+f"(d[33]), "+f"(d[34]), "+f"(d[35]), "+f"(d[36]), "+f"(d[37]), "+f"(d[38]), "+f"(d[39]),
          "+f"(d[40]), "+f"(d[41]), "+f"(d[42]), "+f"(d[43]), "+f"(d[44]), "+f"(d[45]), "+f"(d[46]), "+f"(d[47]),
          "+f"(d[48]), "+f"(d[49]), "+f"(d[50]), "+f"(d[51]), "+f"(d[52]), "+f"(d[53]), "+f"(d[54]), "+f"(d[55]),
          "+f"(d[56]), "+f"(d[57]), "+f"(d[58]), "+f"(d[59]), "+f"(d[60]), "+f"(d[61]), "+f"(d[62]), "+f"(d[63])
        : "l"(da), "l"(db), "r"(scaleD), "n"(TB));
}

__device__ __forceinline__ uint32_t get_role(uint32_t& smid) {
    uint32_t role;
    asm volatile("mov.u32 %0, %%smid;" : "=r"(smid));
    asm("{.reg .pred p, q; .reg .u32 t, a, b; shr.u32 t, %1, 1; mad.lo.u32 a, t, 293, -928; shr.u32 a, a, 8; mad.lo.u32 b, t, 8, -464;"
        " setp.lt.u32 p, t, 32; setp.lt.u32 q, t, 62; selp.u32 a, a, b, q; selp.u32 %0, t, a, p;}" : "=r"(role) : "r"(smid));
    return role;
}
__device__ __forceinline__ int tile_of_step(int step, int own) {
    const int u = step >= 17 ? step - 17 - (step > PS1) : step - 2;
    int e = u + (u >= (own & 14) ? 2 : 0);
    if (step == 16 || step == PS1) e = own ^ 1;
    if (step < 2) e = own;
    return e + (step >= 17 || step == 1 ? 16 : 0);
}
__device__ __forceinline__ uint32_t router_key(float score, int row) {
    const float r = score + 0.0f;
    uint32_t u = pack_bf16(r, 0.f) & 0xffffu;
    u = (u & 0x8000u) ? (~u & 0xffffu) : (u | 0x8000u);
    if (r != r) u = 0;
    return (u << 16) | (uint32_t)(0x7fff - row);
}

#define g_fb_h ((float*)g_s.part)
#define g_fb_upd (g_fb_h + 2048)
#define g_fb_gate (g_fb_h + 4096)
#define g_fb_keys (g_s.part + 8192)
__global__ void fb_hidden(const bf16* x, const bf16* dre, const bf16* dim, const bf16* gw, const bf16* wr) {
    __shared__ float xs[D_];
    const int s = blockIdx.x, t = threadIdx.x;
    xs[t] = __bfloat162float(x[s * D_ + t]);
    __syncthreads();
    float a = 0.f, b = 0.f;
    for (int d = 0; d < D_; d++) { a = fmaf(xs[d], __bfloat162float(dre[t * D_ + d]), a); b = fmaf(xs[d], __bfloat162float(dim[t * D_ + d]), b); }
    ((bf16*)g_s.ab)[s * 1024 + t] = __float2bfloat16(a);
    ((bf16*)g_s.ab)[s * 1024 + 512 + t] = __float2bfloat16(b);
    if (t == 0) {
        float u = 0.f, v = 0.f;
        for (int d = 0; d < D_; d++) { u = fmaf(xs[d], __bfloat162float(gw[d]), u); v = fmaf(xs[d], __bfloat162float(wr[d]), v); }
        g_fb_gate[s] = sigmoidf_(u);
        g_fb_keys[s] = router_key(v, s);
    }
}
__device__ uint32_t fb_best() {
    uint32_t k = 0;
    for (int i = 0; i < S_; i++) k = max(k, g_fb_keys[i]);
    return k;
}
__global__ void fb_ffn1(const bf16* x, const bf16* wg, const bf16* wu) {
    const int f = blockIdx.x * blockDim.x + threadIdx.x, idx = 0x7fff - (int)(fb_best() & 0x7fffu);
    float a = 0.f, b = 0.f;
    for (int d = 0; d < D_; d++) {
        const float xv = __bfloat162float(x[idx * D_ + d]);
        a = fmaf(xv, __bfloat162float(wg[d * F_ + f]), a); b = fmaf(xv, __bfloat162float(wu[d * F_ + f]), b);
    }
    g_fb_h[f] = a * sigmoidf_(a) * b;
}
__global__ void fb_ffn2(const bf16* wd) {
    const int e = blockIdx.x * blockDim.x + threadIdx.x;
    const uint32_t u = fb_best() >> 16, rb = (u & 0x8000u) ? (u & 0x7fffu) : (~u & 0xffffu);
    float a = 0.f;
    for (int f = 0; f < F_; f++) a = fmaf(g_fb_h[f], __bfloat162float(wd[f * D_ + e]), a);
    g_fb_upd[e] = a * sigmoidf_(__uint_as_float(rb << 16));
}
__global__ void fb_seq(const bf16* x, const bf16* cre, const bf16* cim, bf16* out) {
    __shared__ float c[2][S_];
    __shared__ int idx;
    const int t = blockIdx.x, e = threadIdx.x;
    for (int i = e; i < S_; i += D_) { c[0][i] = __bfloat162float(cre[t * S_ + i]); c[1][i] = __bfloat162float(cim[t * S_ + i]); }
    if (e == 0) idx = 0x7fff - (int)(fb_best() & 0x7fffu);
    __syncthreads();
    float y = 0.f;
    for (int s = 0; s < S_; s++)
        y += c[0][s] * __bfloat162float(((const bf16*)g_s.ab)[s * 1024 + e]) - c[1][s] * __bfloat162float(((const bf16*)g_s.ab)[s * 1024 + 512 + e]);
    const float g = g_fb_gate[t];
    out[t * D_ + e] = __float2bfloat16(g * y + (1.f - g) * (__bfloat162float(x[t * D_ + e]) + (t == idx ? g_fb_upd[e] : 0.f)));
}

__device__ __forceinline__ void spare_job(const Params& p, unsigned char* smem, int sp, uint32_t tstart) {
    const int tid = threadIdx.x, warp = tid >> 5, lane = tid & 31;
    const uint32_t e1 = *(volatile unsigned int*)&p.s->epoch[NCTA + sp] + 1u;
    const uint32_t par = e1 & 1u;
    uint32_t* sel = (uint32_t*)smem;
    float* acc = (float*)(smem + 1024);
    __syncthreads();
    if (tid == 0) *(volatile unsigned int*)&p.s->epoch[NCTA + sp] = e1;
    sleep_until<500>(tstart + SUM_T0);
    if (warp < 14) {
        uint32_t n = 0;
        while ((int)(ld_relaxed(p.s->phint + (sp * 16 + warp) * 8) - e1 * 8u) < 0) {
            __nanosleep(100);
            if (++n > SPIN_LIMIT) __trap();
        }
        const unsigned int* src = p.s->part + warp * 4 * D_ + sp * 128 + lane * 4;
        uint4 v[4];
        while (true) {
            uint32_t bad = 0;
#pragma unroll
            for (int i = 0; i < 4; i++) v[i] = ld_relaxed4(src + i * D_);
#pragma unroll
            for (int i = 0; i < 4; i++) bad |= (v[i].x ^ par) | (v[i].y ^ par) | (v[i].z ^ par) | (v[i].w ^ par);
            if (!__any_sync(0xffffffffu, bad & 1u)) break;
            if (++n > SPIN_LIMIT) __trap();
        }
        float4 s = make_float4(0.f, 0.f, 0.f, 0.f);
#pragma unroll
        for (int i = 0; i < 4; i++) {
            s.x += __uint_as_float(v[i].x); s.y += __uint_as_float(v[i].y);
            s.z += __uint_as_float(v[i].z); s.w += __uint_as_float(v[i].w);
        }
        *(float4*)&acc[warp * 128 + lane * 4] = s;
    } else if (warp == 14) {
        const uint4 k4 = wait_tags(p.s->keys + lane * 4, 15, par);
        const uint32_t k = __reduce_max_sync(0xffffffffu, max(max(k4.x, k4.y), max(k4.z, k4.w)));
        const int idx = 0x7fff - (int)(k & 0x7fffu);
        const uint4 g4 = wait_tags(p.s->gate + (idx & ~3), 0, par);
        const uint32_t gw = (idx & 2) ? ((idx & 1) ? g4.w : g4.z) : ((idx & 1) ? g4.y : g4.x);
        const uint32_t u = k >> 16;
        const uint32_t rb = (u & 0x8000u) ? (u & 0x7fffu) : (~u & 0xffffu);
        const float og = 1.f - __uint_as_float(gw & ~1u), rs = sigmoidf_(__uint_as_float(rb << 16));
        if (lane == 0) { sel[0] = idx; sel[1] = pack_bf16(og, og); sel[2] = pack_bf16(rs, rs); }
        sleep_until<500>(tstart + SUM_T0 + 3000);
        wait_counter(p.s->ready + (idx >> 7) * 32, e1 * 8u);
    }
    __syncthreads();
    if (tid < 64) {
        float t0 = 0.f, t1 = 0.f;
#pragma unroll
        for (int i = 0; i < 14; i++) {
            const float2 z = *(const float2*)&acc[i * 128 + tid * 2];
            t0 += z.x; t1 += z.y;
        }
        asm volatile("red.relaxed.gpu.global.add.noftz.bf16x2 [%0], %1;" ::"l"(p.out + sel[0] * D_ + sp * 128 + tid * 2),
                     "r"(hmul2_bf16(sel[1], hmul2_bf16(sel[2], pack_bf16(t0, t1)))) : "memory");
    }
}

__host__ __device__ constexpr int off_d(int c) { return (c < 2 ? 1 : c / 2 + 2) * REGION + (c & 1) * 16384; }
__host__ __device__ constexpr int off_xe(int c) { return (c < 2 ? 6 * REGION : c < 4 ? 16384 : c < 6 ? 0 : 6 * REGION + 16384) + (c & 1) * 8192; }
__host__ __device__ constexpr int off_xl(int c) { return c < 4 ? 2 * REGION + c * 8192 : off_xe(c - 4); }

__global__ void __cluster_dims__(2, 1, 1) __launch_bounds__(NTHREADS, 1)
fused_kernel(const __grid_constant__ Params p) {
    extern __shared__ __align__(1024) unsigned char smem[];
    const uint32_t tstart = clk();
    const uint32_t sb = smem_u32(smem);
    const int tid = threadIdx.x, lane = tid & 31;
    const int rank = blockIdx.x & 1;
    uint32_t t1 = 0;
    if (__any_sync(0xffffffffu, tid == 0)) {
        uint32_t s0;
        const uint32_t r0 = get_role(s0);
        mbar_init_elect(sb + B_F, 1);
        if (r0 < 64) {
#pragma unroll
            for (int c = 0; c < 2; c++) {
                if (c) {
                    spin_until(t1 + PACE);
                    mbar_init_elect(sb + B_F + 8, 1);
                }
                tma3d_elect(sb + off_d(c), &p.mDre + ((r0 >> 2) & 1), (r0 & 24) * 16, c, sb + B_F + 8 * c);
                tma3d_elect(sb + off_xe(c), &p.mX1, (r0 & 3) * 256 + (r0 & 32) * 4 + rank * 64, c, sb + B_F + 8 * c);
                mbar_expect_tx_elect(sb + B_F + 8 * c, 24576);
                if (!c) {
                    t1 = clk() + PACE0;
                    mbar_init_elect(sb + B_G0, 1);
                    tma3d_elect(sb + off_xl(0), &p.mX1, (r0 & 3) * 256 + (r0 & 32) * 4 + rank * 64 + 1024, 0, sb + B_G0);
                    mbar_expect_tx_elect(sb + B_G0, 8192);
                }
            }
        }
    }
    const int warp = __shfl_sync(0xffffffffu, tid >> 5, 0);
    uint32_t smid;
    const uint32_t role = get_role(smid);
    const int gpc = role & 7;
    const int tn = (role >> 3) & 3;
    const int comp = gpc >> 2;
    const int own = (gpc & 3) * 4 + ((role >> 5) & 1) * 2 + rank;
    const int blk = comp * 4 + tn;
    const int cta = gpc * 16 + (role >> 3) * 2 + rank;
    const bool ffn = cta < FFN_CTAS;
    uint32_t epoch = 0;
    if (warp != 0) {
        const uint32_t b1 = sb + B_F + 8 * warp;
        mbar_init_elect(warp < 2 ? b1 + 360 : b1, 1);
        if (warp >= 2 && warp < 5) mbar_init_elect(b1 + 360, warp < 4 ? 1 : 4);
        mbar_init_elect(b1 + 120, warp < 7 ? 5 : warp < 14 ? 4 : warp - 12);
        mbar_init_elect(b1 + 240, 1);
        if (warp == 9 || warp == 15) mbar_expect_tx_elect(b1 + 240, warp == 9 ? 2048 : 4);
        asm volatile("fence.mbarrier_init.release.cluster;" ::: "memory");
        if (tid == 128 && role < 64) epoch = *(volatile unsigned int*)&p.s->epoch[cta];
    }
    if (role >= 64) {
        spare_job(p, smem, smid & 3, tstart);
        return;
    }
    __syncthreads();
    cluster_arrive();
    if (warp == 0) {
#pragma unroll
        for (int c = 2; c < 8; c++) {
            spin_until(t1 + c * PACE);
            tma3d_elect(sb + off_d(c), &p.mDre + comp, tn * 128, c, sb + B_F + 8 * c);
            tma3d_elect(sb + off_xe(c), &p.mX1, own * 64, c, sb + B_F + 8 * c);
            mbar_expect_tx_elect(sb + B_F + 8 * c, 24576);
        }
        tma3d_elect(sb + off_xl(1), &p.mX1, own * 64 + 1024, 1, sb + B_G1);
        mbar_expect_tx_elect(sb + B_G1, 8192);
        spin_until(t1 + 8 * PACE);
        tma3d_elect(sb + off_xl(2), &p.mX2, own * 64 + 1024, 2, sb + B_G2);
        mbar_expect_tx_elect(sb + B_G2, 16384);
        if (tn < 2)
            asm volatile(ELECT "cp.async.bulk.prefetch.tensor.3d.L2.global [%0, {%1,%2,%3}];}"
                         ::"l"(&p.mX2), "r"(0), "r"(own * 64 + 1024), "r"(4 + 2 * tn) : "memory");
    }

    if (warp < 4) {
        const int tab = tile_of_step(lane, own);
        const uint32_t bdst = sb + 16384 + rank * 8192;
        const int brow = blk * 4096 + rank * 64;
        if (warp == 0) {
            mbar_spin(sb + B_XE, 0);
            tma3d_elect(sb + off_xl(4), &p.mX2, own * 64 + 1024, 4, sb + B_G4);
            tma3d_elect(sb + off_xl(6), &p.mX2, own * 64 + 1024, 6, sb + B_G4);
            mbar_expect_tx_elect(sb + B_G4, 32768);
#define LOAD_A() const int e = __shfl_sync(0xffffffffu, tab, step);                                             \
                 const uint32_t bar = sb + 8 * slot;                                                            \
                 mbar_spin(bar + B_EMPTY, ph);                                                                  \
                 tma2d_elect(sb + slot * REGION, &p.mCre + comp, e * 64, own * 128, bar + B_FULL);              \
                 mbar_expect_tx_elect(bar + B_FULL, 16384)
            uint32_t slot = 0, ph = 0;
            int step = 0;
#pragma unroll 1
            for (int i = 0; i < NSTAGE; i++) {
                step = slot = i < 2 ? i ^ 1 : i;
                LOAD_A();
                if (i == 2 || i == 3) spin_until(clk() + A_GAP);
            }
            step = NSTAGE;
            slot = 0; ph = 1;
#pragma unroll 1
            for (int h = 0; h < 3; h++) {
                const int last = h == 0 ? 16 : h == 1 ? PS1 : 32 - NA;
#pragma unroll 1
                for (; step < last; step++) {
                    LOAD_A();
                    tma2d_pair_elect(bdst + slot * REGION, &p.mAB, 0, brow + e * 128, bar + B_BL);
                    mbar_expect_tx_elect(bar + B_BL, 16384);
                    if (++slot == NSTAGE) { slot = 0; ph ^= 1; }
                }
                if (h == 2) break;
                LOAD_A();
                tma2d_elect(bdst + slot * REGION, &p.mAB, 0, brow + e * 128, bar + B_BL);
                tma2d_elect((bdst ^ 8192) + slot * REGION, &p.mAB, 0, (brow ^ 64) + e * 128, bar + B_BL);
                mbar_expect_tx_elect(bar + B_BL, 16384);
                step++;
                if (++slot == NSTAGE) { slot = 0; ph ^= 1; }
            }
            mbar_spin(sb + B_LOW, 0);
            uint32_t aslot = 6;
#pragma unroll 1
            for (; step < 32; step++) {
                const int e = __shfl_sync(0xffffffffu, tab, step);
                const uint32_t bar = sb + 8 * slot;
                tma2d_elect(sb + aslot * REGION, &p.mCre + comp, e * 64, own * 128, bar + B_FULL);
                mbar_expect_tx_elect(bar + B_FULL, 16384);
                mbar_expect_tx_elect(bar + B_BL, 16384);
                mbar_spin(bar + B_EMPTY, ph);
                tma2d_pair_elect(bdst + slot * REGION, &p.mAB, 0, brow + e * 128, bar + B_BL);
                aslot = slot;
                if (++slot == NSTAGE) { slot = 0; ph ^= 1; }
            }
        } else if (warp == 1) {
            if (lane < 4) asm volatile("prefetch.tensormap [%0];" ::"l"(&p.mCre + lane) : "memory");
            __syncwarp();
            cluster_wait();
            if (lane == 0)
                asm volatile("st.async.weak.shared::cluster.mbarrier::complete_tx::bytes.u32 [%0], %1, [%2];"
                             ::"r"(mapa(sb + M_ROLE, rank ^ 1)), "r"(role), "r"(mapa(sb + B_ROLE, rank ^ 1)) : "memory");
            mbar_wait_cluster(sb + B_ROLE, 0);
            if (*(volatile uint32_t*)(smem + M_ROLE) != role) __trap();
            mbar_wait(sb + B_EPOCH, 0);
            const uint32_t want = (*(volatile uint32_t*)(smem + M_EPOCH) + 1u) * 4u;
            const int eh = __shfl_sync(0xffffffffu, tab, 2 + (lane & 3));
            const unsigned int* hp = p.s->hint + (blk * 4 + (eh >> 1)) * 32 + (eh & 1);
            uint32_t seen = __ballot_sync(0xffffffffu, ld_relaxed(hp) == want);
            int rows[4];
#pragma unroll
            for (int i = 0; i < 4; i++) {
                rows[i] = brow + __shfl_sync(0xffffffffu, tab, 2 + i) * 128;
                mbar_expect_tx_elect(sb + B_BL + 8 * (2 + i), 16384);
            }
            mbar_wait(sb + B_EMPTY + 8 * 3, 0);
            mbar_spin(sb + B_EMPTY + 8 * 2, 0);
            uint32_t t3 = 0;
#pragma unroll
            for (int i = 0; i < 4; i++) {
                while (!((seen >> i) & 1u)) seen = __ballot_sync(0xffffffffu, ld_relaxed(hp) == want);
                if (i) spin_until(t3 + B_GAP);
                t3 = clk();
                if (i >= 2) mbar_spin(sb + B_EMPTY + 8 * (2 + i), 0);
                tma2d_pair_elect(bdst + (2 + i) * REGION, &p.mAB, 0, rows[i], sb + B_BL + 8 * (2 + i));
            }
            mbar_wait(sb + B_FREE, 0);
            unsigned char* gdst = p.s->ab + (blk * 32 + own + 16) * 16384;
            t3 = clk();
#pragma unroll 1
            for (int i = 0; i < 16; i++) {
                sleep_until<20>(t3);
                t3 += LATE_GAP;
                asm volatile(ELECT "cp.async.bulk.global.shared::cta.bulk_group [%0], [%1], 1024;}"
                             ::"l"(gdst + i * 1024), "r"(sb + 6 * REGION + i * 1024) : "memory");
            }
            bulk_wait_read();
            mbar_arrive_elect(sb + B_FREE + 8);
            mbar_wait(sb + B_PUB, 0);
            if (lane == 0) {
                asm volatile("fence.proxy.async.global;" ::: "memory");
                asm volatile("red.release.gpu.global.add.u32 [%0], 1;" ::"l"(p.s->ready + (cta >> 3) * 32) : "memory");
            }
            __syncwarp();
            __nanosleep(INIT_NS);
            wait_counter(p.s->ready + own * 32, want * 2u);
            mbar_arrive_elect(sb + B_INIT);
        } else {
            mbar_arrive_elect(sb + B_BL + 8 * (warp & 1));
            uint32_t k = warp == 3 ? 0 : 12;
#define PREFETCH_W() {                                                                                          \
                const char* src = (k >= 8 ? (const char*)p.wd + ((cta >> 5) * 2 + (k >> 1) - 4) * 229376        \
                                          : (const char*)((cta & 32) ? p.wu : p.wg) + ((cta >> 6) * 4 + (k >> 1)) * 229376) \
                                  + ((cta & 31) * 2 + (k & 1)) * 3584;                                          \
                asm volatile(ELECT "cp.async.bulk.prefetch.L2.global [%0], 3584;}" ::"l"(src) : "memory");      \
                k++; }
#pragma unroll 1
            while (k < PF_N0) {
                sleep_until<50>(tstart + PF_T0 + k * PF_GAP);
                __syncwarp();
                PREFETCH_W();
            }
            mbar_wait(sb + B_EPOCH, 0);
            const uint32_t par = (*(volatile uint32_t*)(smem + M_EPOCH) + 1u) & 1u;
            const uint32_t a0 = sb + 16384 + (lane >> 3) * 1028 + ((lane >> 2) & 1) * 144 + (lane & 3) * 32;
            const uint32_t retry = sb + B_RETRY + (warp & 1) * 240;
            uint32_t slot = warp, ph = 0, rph = 0;
            uint32_t j = ffn ? warp & 1 : 12;
#pragma unroll 1
            for (int step = warp; step < 32 || j < 12; step += 2) {
                if (step < 32) {
                    const uint32_t bar = sb + 8 * slot;
                    mbar_wait(bar + B_BL, ph);
#pragma unroll 1
                    while (__any_sync(0xffffffffu, stale_tags(a0 + slot * REGION, par) & 1u)) {
                        const int row = blk * 4096 + __shfl_sync(0xffffffffu, tab, step) * 128;
                        mbar_expect_tx_elect(retry, 16384);
                        tma2d_elect(sb + slot * REGION + 16384, &p.mAB, 0, row, retry);
                        tma2d_elect(sb + slot * REGION + 24576, &p.mAB, 0, row + 64, retry);
                        mbar_spin(retry, rph);
                        rph ^= 1u;
                    }
                    mbar_arrive_elect<4>(bar + B_FULL);
                }
                if (j < 12 && step >= FFN_S0 + j * FFN_W / 4 && __any_sync(0xffffffffu, mbar_test(sb + B_FREE + 2 * (j & 12), 0))) {
                    const uint32_t fb = sb + B_FFN + 4 * (j & 6);
                    if (!(j & 1)) mbar_expect_tx_elect(fb, 8192);
                    tma2d_elect(sb + 6 * REGION + ((j + 4) & 7) * 4096, j < 8 ? &p.mWg + (j & 1) : &p.mWd,
                                j < 8 ? (cta >> 1) * 32 : rank * 256, j < 8 ? rank * 256 + (j >> 1) * 64 : (cta >> 1) * 32 + j * 8 - 64, fb);
                    j += 2;
                }
                if (k < 12) PREFETCH_W();
                slot += 2;
                if (slot >= NSTAGE) { slot -= NSTAGE; ph ^= 1; }
            }
        }
    } else if (warp < 8) {
        const int t = tid - 128, w = warp - 4;
        if (t == 0) {
            *(volatile uint32_t*)(smem + M_EPOCH) = epoch;
            *(volatile unsigned int*)&p.s->epoch[cta] = epoch + 1;
        }
        mbar_arrive_if(sb + B_EPOCH, t == 0);
        const uint4 gw0 = ldg_nc<0>(p.gate_w + lane * 8), gw1 = ldg_nc<512>(p.gate_w + lane * 8);
        const uint4 rw0 = ldg_nc<0>(p.w_r + lane * 8), rw1 = ldg_nc<512>(p.w_r + lane * 8);
        mbar_wait(sb + B_EPOCH, 0);
        const uint32_t par = (*(volatile uint32_t*)(smem + M_EPOCH) + 1u) & 1u;
        mbar_wait(sb + B_F + 8 * ROUTER_C, 0);
        const int row0 = cta * 16 + w * 4;
        uint4 xr[8];
        {
            const char* xp = (const char*)p.x + (uint32_t)row0 * (D_ * 2) + lane * 16;
            xr[0] = ldg_nc<0>(xp);    xr[1] = ldg_nc<512>(xp);  xr[2] = ldg_nc<1024>(xp); xr[3] = ldg_nc<1536>(xp);
            xr[4] = ldg_nc<2048>(xp); xr[5] = ldg_nc<2560>(xp); xr[6] = ldg_nc<3072>(xp); xr[7] = ldg_nc<3584>(xp);
            float a[8];
#pragma unroll
            for (int i = 0; i < 4; i++) {
                const uint32_t xv[8] = {xr[2 * i].x, xr[2 * i].y, xr[2 * i].z, xr[2 * i].w,
                                        xr[2 * i + 1].x, xr[2 * i + 1].y, xr[2 * i + 1].z, xr[2 * i + 1].w};
                const uint32_t gv[8] = {gw0.x, gw0.y, gw0.z, gw0.w, gw1.x, gw1.y, gw1.z, gw1.w};
                const uint32_t rv[8] = {rw0.x, rw0.y, rw0.z, rw0.w, rw1.x, rw1.y, rw1.z, rw1.w};
                float u = 0.f, v = 0.f;
#pragma unroll
                for (int j = 0; j < 8; j++) {
                    const uint32_t pr = hmul2_bf16(xv[j], gv[j]);
                    u += bflo(pr); u += bfhi(pr);
                    v = fmaf(bflo(xv[j]), bflo(rv[j]), v); v = fmaf(bfhi(xv[j]), bfhi(rv[j]), v);
                }
                a[i] = u; a[4 + i] = v;
            }
            mbar_wait(sb + B_EARLY, 0);
            halve<4, 16>(a); halve<2, 8>(a); halve<1, 4>(a);
            a[0] += __shfl_xor_sync(0xffffffffu, a[0], 1);
            a[0] += __shfl_xor_sync(0xffffffffu, a[0], 2);
            const int row = row0 + ((lane >> 2) & 3);
            const float gate = rbf(sigmoidf_(rbf(a[0])));
            if (lane < 16 && (lane & 3) == 0)
                asm volatile("st.relaxed.gpu.global.u32 [%0], %1;" ::"l"(&p.s->gate[row]), "r"(tagf(gate, par)) : "memory");
            const uint32_t best = __reduce_max_sync(0xffffffffu, lane >= 16 ? router_key(a[0], row) : 0u);
            if (lane == 0) *(volatile uint32_t*)(smem + M_KEY + w * 4) = best;
            side_bar();
            if (t < 8) {
                const uint4 k = *(const uint4*)(smem + M_KEY);
                asm volatile("{.reg .b32 old; atom.relaxed.gpu.global.exch.b32 old, [%0], %1;}" ::"l"(&p.s->keys[t * NCTA + cta]),
                             "r"(max(max(k.x, k.y), max(k.z, k.w)) | (par << 15)) : "memory");
            }
            const uint32_t og = pack_bf16(1.f - gate, 1.f - gate);
#pragma unroll
            for (int i = 0; i < 8; i++) {
                const uint32_t o = __shfl_sync(0xffffffffu, og, 4 * (i >> 1));
                xr[i] = make_uint4(hmul2_bf16(o, xr[i].x), hmul2_bf16(o, xr[i].y), hmul2_bf16(o, xr[i].z), hmul2_bf16(o, xr[i].w));
            }
        }
        mbar_wait(sb + B_FREE, 0);
        __nanosleep(KEY_NS);
        if (w == 0) {
            const uint4 k4 = wait_tags(p.s->keys + gpc * NCTA + lane * 4, 15, par);
            const uint32_t k = __reduce_max_sync(0xffffffffu, max(max(k4.x, k4.y), max(k4.z, k4.w)));
            sts128<M_XS>(sb + lane * 16, ldg_nc<0>(p.x + (0x7fff - (k & 0x7fffu)) * D_ + rank * 256 + lane * 8));
        } else if (w == 1) {
            const uint4 g4 = wait_tags(p.s->gate + own * 128 + lane * 4, 0, par);
            const uint32_t sg = comp ? 0x80000000u : 0u;
            sts128<M_G>(sb + lane * 16, make_uint4((g4.x & ~1u) ^ sg, (g4.y & ~1u) ^ sg, (g4.z & ~1u) ^ sg, (g4.w & ~1u) ^ sg));
            mbar_arrive_warp(sb + B_GATE);
        }
        side_bar();
        char* op = (char*)p.out + (uint32_t)row0 * (D_ * 2) + lane * 16;
        float a[16];
#pragma unroll
        for (int i = 0; i < 16; i++) a[i] = 0.f;
#pragma unroll 1
        for (int i = 0; i < 4; i++) {
            if (i == 2) {
                mbar_wait(sb + B_FREE + 8, 0);
                const uint32_t t2 = clk() + w * (INIT_GAP / 4);
#pragma unroll
                for (int j = 0; j < 8; j++) {
                    sleep_until<20>(t2 + j * INIT_GAP);
                    *(uint4*)(op + j * 512) = xr[j];
                }
                mbar_arrive_warp(sb + B_PUB);
            }
            if (ffn) {
                const float xs0 = __bfloat162float(((const bf16*)(smem + M_XS))[64 * i + (t >> 2)]);
                const float xs1 = __bfloat162float(((const bf16*)(smem + M_XS))[64 * i + 32 + (t >> 2)]);
                const uint32_t wa = sb + 6 * REGION + (i ^ 2) * 8192 + t * 16;
                mbar_wait(sb + B_FFN + 8 * i, 0);
                const uint4 v0 = lds128(wa), v1 = lds128(wa + 4096), v2 = lds128(wa + 2048), v3 = lds128(wa + 6144);
                const uint32_t w0[8] = {v0.x, v0.y, v0.z, v0.w, v1.x, v1.y, v1.z, v1.w};
                const uint32_t w1[8] = {v2.x, v2.y, v2.z, v2.w, v3.x, v3.y, v3.z, v3.w};
#pragma unroll
                for (int k = 0; k < 8; k++) {
                    a[2 * k] = fmaf(xs1, bflo(w1[k]), fmaf(xs0, bflo(w0[k]), a[2 * k]));
                    a[2 * k + 1] = fmaf(xs1, bfhi(w1[k]), fmaf(xs0, bfhi(w0[k]), a[2 * k + 1]));
                }
                if (i == 1) {
                    side_bar();
                    mbar_arrive_if(sb + B_FREE + 16, t == 0);
                }
            }
        }
        if (!ffn) {
            mbar_arrive_warp(sb + B_LOW);
            return;
        }
        halve<8, 16>(a); halve<4, 8>(a); halve<2, 4>(a);
        const uint32_t ho = (lane >> 4) * 128 + (lane & 3) * 32 + ((lane >> 2) & 3) * 8;
        cluster_wait();
#pragma unroll
        for (int k = 0; k < 2; k++)
            asm volatile("st.async.weak.shared::cluster.mbarrier::complete_tx::bytes.v2.f32 [%0], {%1,%2}, [%3];"
                         ::"r"(mapa(sb + (k ? 6 * REGION + w * 512 : M_HX + w * 256) + ho, rank ^ k ^ 1)), "f"(a[0]), "f"(a[1]),
                           "r"(mapa(sb + B_HX, rank ^ k ^ 1)) : "memory");
        mbar_wait_cluster(sb + B_HX, 0);
        const float *hx = (const float*)(smem + M_HX) + lane, *hy = (const float*)(smem + 6 * REGION) + lane;
        const float gs = rbf(((hx[0] + hy[0]) + (hx[64] + hy[128])) + ((hx[128] + hy[256]) + (hx[192] + hy[384])));
        const float us = rbf(((hx[32] + hy[32]) + (hx[96] + hy[160])) + ((hx[160] + hy[288]) + (hx[224] + hy[416])));
        float* hrow = (float*)(smem + M_XS) + w * 32;
        hrow[lane] = rbf(rbf(gs * sigmoidf_(gs)) * us);
        fence_proxy_async_smem();
        mbar_arrive_warp(sb + B_LOW);
        float o0 = 0.f, o1 = 0.f;
#pragma unroll 1
        for (int i = 0; i < 2; i++) {
            float4 hv[4];
            uint32_t vd[16];
#pragma unroll
            for (int k = 0; k < 4; k++) hv[k] = *(const float4*)&hrow[i * 16 + k * 4];
            mbar_wait(sb + B_FFN + 8 * i, 1);
#pragma unroll
            for (int k = 0; k < 16; k++) vd[k] = *(const volatile uint32_t*)(smem + 6 * REGION + 16384 + i * 8192 + k * 512 + t * 4);
#pragma unroll
            for (int k = 0; k < 4; k++) {
                o0 = fmaf(hv[k].x, bflo(vd[4 * k]), o0);     o1 = fmaf(hv[k].x, bfhi(vd[4 * k]), o1);
                o0 = fmaf(hv[k].y, bflo(vd[4 * k + 1]), o0); o1 = fmaf(hv[k].y, bfhi(vd[4 * k + 1]), o1);
                o0 = fmaf(hv[k].z, bflo(vd[4 * k + 2]), o0); o1 = fmaf(hv[k].z, bfhi(vd[4 * k + 2]), o1);
                o0 = fmaf(hv[k].w, bflo(vd[4 * k + 3]), o0); o1 = fmaf(hv[k].w, bfhi(vd[4 * k + 3]), o1);
            }
        }
        asm volatile("st.relaxed.gpu.global.v2.u32 [%0], {%1,%2};" ::"l"(&p.s->part[(cta >> 1) * D_ + rank * 256 + t * 2]),
                     "r"(tagf(o0, par)), "r"(tagf(o1, par)) : "memory");
        red_inc_if(p.s->phint + ((rank * 2 + (w >> 1)) * 16 + (cta >> 3)) * 8 + lane, lane == 0);
    } else {
        const int wg = (warp >> 2) - 2, wq = warp & 3;
        const uint32_t sbd = ((sb & 0x3FFFF) >> 4) + 0x10000;
        const bool lead = (tid & 127) == 0;
        const bool lead0 = lead && !wg, lead1 = lead && wg;
        const int q = lane & 3;
        float acc[64];
        const uint32_t rE = mapa(sb + B_EMPTY, rank ^ 1);
#define RELEASE(n, slot, pred) release_pair<n>(sb + B_EMPTY + 8 * (slot), rE + 8 * (slot), pred)
        const uint32_t ioff = wq * 4096 + (lane >> 2) * 64 + ((q ^ (lane >> 3)) << 4);
        const uint32_t sdst = pin(sb + 6 * REGION + (wg ? 0 : 16384) + ioff);
        unsigned char* gdst = pin(p.s->ab + (blk * 32 + own) * 16384 + ioff);
        unsigned int* hint = pin(p.s->hint + (blk * 4 + ((own >> 1) & 3)) * 32 + rank + lane);
        uint32_t par = 0;
#define GET_PAR() mbar_spin(sb + B_EPOCH, 0); par = (*(volatile uint32_t*)(smem + M_EPOCH) + 1u) & 1u
        cluster_wait();
        if (wg) mbar_spin(sb + B_G0, 0);
#pragma unroll
        for (int c = 0; c < 8; c++) {
            if (c == 1 && wg) {
                wg_wait<0>();
                RELEASE(1, 1, lead);
                GET_PAR();
                mbar_spin(sb + B_G1, 0);
            }
            if (!wg || c < 3 || c == 4) mbar_spin(sb + (!wg || c == 0 ? B_F + 8 * c : c == 1 ? B_GO1 : c == 2 ? B_G2 : B_G4), 0);
            const uint32_t xa = sbd + wg * ((off_xl(c) - off_xe(c)) / 16);
            wg_fence();
#pragma unroll
            for (int kk = 0; kk < 4; kk++) {
                wgmma128<0>(acc, desc128(xa + off_xe(c) / 16 + 2 * kk), desc128(sbd + off_d(c) / 16 + 2 * kk), (c | kk) != 0);
                if (c == 7 && kk == 0) wg_commit();
            }
            wg_commit();
            if (c == 3 && !wg) { GET_PAR(); }
            if (c == 7) {
                if (wg) mbar_spin(sb + B_FULL, 0);
                wg_wait<2>();
                mbar_arrive_if(sb + B_GO1, lead0);
            }
            if (c == 4 || c >= 6) wg_wait<1>();
            if (c == 4) { mbar_arrive_if(sb + B_XE, lead0); RELEASE(1, 1, lead0); RELEASE(2, 2, lead1); RELEASE(2, 3, lead1); }
            if (c == 6) RELEASE(2, 4 * wg, lead);
            if (c == 7) mbar_arrive_if(sb + B_GO0, lead1);
        }
        const int rh = wg ^ comp;
        const uint32_t da0 = sbd + rh * 512, db0 = sbd - 0x10000 + 0x400000 + 1024;
        const uint32_t dbe = db0 + 6 * (REGION / 16), dbl = dbe - 1024;
#define STEP(da, db, first) wg_fence();                                                                     \
        _Pragma("unroll") for (int kk = 0; kk < 4; kk++)                                                    \
            wgmma128<1>(acc, desc128((da) + kk * 2), desc64((db) + kk * 256), !((first) && kk == 0));       \
        wg_commit()
#define ACC(i, j) (16 * ((i) >> 1) + 2 * ((i) & 1) + 4 * (j))
#define PW(i, j) pack_bf16(acc[ACC(i, j)], acc[ACC(i, j) + 1])
#define PT(i, j) ((j) == ((i) >> 1) ? (PW(i, j) & ~1u) | par : PW(i, j))
#define PIECE(i) make_uint4(PT(i, 0), PT(i, 1), PT(i, 2), PT(i, 3))
#define PIECES(F) F(0); F(1); sched_cut(); F(2); F(3); F(4); F(5); F(6); F(7)
        if (wg) {
            wg_wait<0>();
            fence_regs(acc);
#define STS1(i) sts128<(i) * 512>(sdst, PIECE(i))
            PIECES(STS1);
            STEP(da0, dbe, true);
            fence_proxy_async_smem();
            mbar_arrive_warp(sb + B_FULL + 8);
            RELEASE(1, 5, lead);
        } else {
            wg_wait<0>();
            fence_regs(acc);
            uint4 v[8];
#define STG0(i) v[i] = PIECE(i); stg128<(i) * 512>(gdst, v[i]); if (HINT_AT == (i) + 1) red_inc_if(hint, own < 6 && lane == 0)
            PIECES(STG0);
#define STS0(i) mbar_spin(sb + B_EPOCH, 0); sts128<(i) * 512>(sdst, v[i])
            STS0(0); STS0(1); STS0(2); STS0(3); STS0(4); STS0(5); STS0(6); STS0(7);
            fence_proxy_async_smem();
            mbar_arrive_warp(sb + B_FULL);
            RELEASE(1, 5, lead);
            mbar_arrive_if(sb + B_EARLY, lead);
            mbar_spin(sb + B_FULL, 0);
            mbar_spin(sb + B_GO0, 0);
            STEP(da0, dbe, true);
        }
#pragma unroll
        for (int step = 1; step < 3; step++) {
            mbar_spin(sb + B_FULL + 8 * step, 0);
            STEP(da0 + step * (REGION / 16), step == 1 ? dbl : db0 + step * (REGION / 16), false);
            wg_wait<1>();
            RELEASE(1, step - 1, lead);
            mbar_arrive_if(sb + B_FREE + 8 * (step - 1), lead);
        }
        int slot = 3, ph = 0, pslot = 2;
        float g0 = 0.f, g1 = 0.f;
        uint32_t oa = 0;
#pragma unroll 1
        for (int step = 3; step < 26; step++) {
            mbar_wait(sb + B_FULL + 8 * slot, ph);
            STEP(da0 + slot * (REGION / 16), db0 + slot * (REGION / 16), false);
            if (step == 22 + wg) {
                const int r0 = rh * 64 + wq * 16 + (lane >> 2), sr = ((lane >> 2) & 1) * 4 + (lane >> 3);
                mbar_wait(sb + B_GATE, 0);
                g0 = ((const volatile float*)(smem + M_G))[r0];
                g1 = ((const volatile float*)(smem + M_G))[r0 + 8];
                oa = pin(wg ? ((own * 128 + (r0 & ~1)) * D_ + tn * 128 + (lane & 7) * 8) * 2u
                            : sb + rh * 8192 + wq * 2048 + sr * 128 + ((q ^ sr) << 4));
            }
            wg_wait<1>();
            RELEASE(1, pslot, lead);
            pslot = slot;
            if (++slot == NSTAGE) { slot = 0; ph ^= 1; }
        }
        mbar_wait(sb + B_FULL + 8 * 2, 0);
        wg_fence();
#pragma unroll
        for (int kk = 0; kk < 4; kk++) {
            if (kk == HSK) {
                wg_commit();
                if (wg) {
                    wg_wait<1>();
                    RELEASE(1, 1, lead);
                    mbar_wait(sb + B_INIT, 0);
                    mbar_wait(sb + B_TAIL, 0);
                }
                wg_fence();
            }
            wgmma128<1>(acc, desc128(da0 + 2 * (REGION / 16) + kk * 2), desc64(db0 + 2 * (REGION / 16) + kk * 256), 1);
        }
        wg_commit();
        if (!wg) {
            wg_wait<2>();
            RELEASE(1, 1, lead);
        }
        slot = 3;
#pragma unroll 1
        for (int step = 27; step < 32; step++) {
            if (!wg) mbar_wait(sb + B_FULL + 8 * slot, ph);
            STEP(da0 + (step < 32 - NA ? slot : step == 32 - NA ? 6 : pslot) * (REGION / 16), db0 + slot * (REGION / 16), false);
            pslot = slot;
            if (++slot == NSTAGE) { slot = 0; ph ^= 1; }
        }
#define OW(i, j) pack_bf16((((i) & 1) ? g1 : g0) * acc[ACC(i, j)], (((i) & 1) ? g1 : g0) * acc[ACC(i, j) + 1])
        if (!wg) {
            wg_wait<1>();
            mbar_arrive_if(sb + B_TAIL, lead);
            const uint32_t st0 = sb + rh * 8192 + wq * 2048;
            mbar_wait(sb + B_INIT, 0);
            wg_wait<0>();
            fence_regs(acc);
#define OSTS(i) sts128<((i) >> 2) * REGION + ((i) & 1) * 1024>(((i) & 2) ? oa ^ 64 : oa, make_uint4(OW(i, 0), OW(i, 1), OW(i, 2), OW(i, 3)))
#define ORED(h) fence_proxy_async_smem(); __syncwarp();                                                     \
            asm volatile(ELECT "cp.reduce.async.bulk.tensor.4d.global.shared::cta.add.tile.bulk_group [%0, {%2,%3,%3,%4}], [%1];}" \
                         ::"l"(&p.mOut), "r"(st0 + (h) * REGION), "r"(tn * 128 + (h) * 64), "r"(0), "r"(own * 16 + rh * 8 + wq * 2) : "memory")
            OSTS(0); OSTS(1); OSTS(2); OSTS(3);
            ORED(0);
            sched_cut();
            OSTS(4); OSTS(5); OSTS(6); OSTS(7);
            ORED(1);
            bulk_wait_read();
        } else {
            const bool odd = lane & 4;
            char *op = pin((char*)p.out + oa), *opb = pin((char*)p.out + (oa ^ 64) + 1024);
            sched_cut();
            wg_wait<0>();
            fence_regs(acc);
#define REDLINE(i) {                                                                                        \
                uint32_t k[4], r[4];                                                                        \
                _Pragma("unroll") for (int j = 0; j < 4; j++) {                                             \
                    r[j] = __shfl_xor_sync(0xffffffffu, OW((i) + 2, j), 4);                                 \
                    k[j] = OW(i, j);                                                                        \
                }                                                                                           \
                red_bf16x8<((i) & 1) * 8192 + ((i) >> 2) * 128>(op, odd ? r[0] : k[0], odd ? r[1] : k[1], odd ? r[2] : k[2], odd ? r[3] : k[3]);  \
                red_bf16x8<((i) & 1) * 8192 + ((i) >> 2) * 128>(opb, odd ? k[0] : r[0], odd ? k[1] : r[1], odd ? k[2] : r[2], odd ? k[3] : r[3]); }
            REDLINE(0)
            sched_cut();
            REDLINE(1) REDLINE(4) REDLINE(5)
        }
    }
}

typedef CUresult (*EncodeTiledFn)(CUtensorMap*, CUtensorMapDataType, cuuint32_t, void*, const cuuint64_t*, const cuuint64_t*,
                                  const cuuint32_t*, const cuuint32_t*, CUtensorMapInterleave, CUtensorMapSwizzle,
                                  CUtensorMapL2promotion, CUtensorMapFloatOOBfill);

static void make_map(EncodeTiledFn enc, CUtensorMap* m, const void* base, uint64_t cols, uint64_t rows, uint32_t box_rows,
                     CUtensorMapSwizzle sw = CU_TENSOR_MAP_SWIZZLE_128B, uint32_t box_cols = 64) {
    cuuint64_t dims[2] = {cols, rows};
    cuuint64_t str[1] = {cols * 2};
    cuuint32_t box[2] = {box_cols, box_rows};
    cuuint32_t es[2] = {1, 1};
    enc(m, CU_TENSOR_MAP_DATA_TYPE_BFLOAT16, 2, (void*)base, dims, str, box, es, CU_TENSOR_MAP_INTERLEAVE_NONE,
        sw, CU_TENSOR_MAP_L2_PROMOTION_L2_128B, CU_TENSOR_MAP_FLOAT_OOB_FILL_NONE);
}

static void make_map_chunks(EncodeTiledFn enc, CUtensorMap* m, const void* base, uint64_t rows, uint32_t box_rows, uint32_t n = 1) {
    cuuint64_t dims[3] = {64, rows, 8};
    cuuint64_t str[2] = {D_ * 2, 128};
    cuuint32_t box[3] = {64, box_rows, n};
    cuuint32_t es[3] = {1, 1, 1};
    enc(m, CU_TENSOR_MAP_DATA_TYPE_BFLOAT16, 3, (void*)base, dims, str, box, es, CU_TENSOR_MAP_INTERLEAVE_NONE,
        CU_TENSOR_MAP_SWIZZLE_128B, CU_TENSOR_MAP_L2_PROMOTION_L2_128B, CU_TENSOR_MAP_FLOAT_OOB_FILL_NONE);
}

static void make_map_out(EncodeTiledFn enc, CUtensorMap* m, const void* base) {
    cuuint64_t dims[4] = {D_, 4, 2, S_ / 8};
    cuuint64_t str[3] = {2 * D_ * 2, D_ * 2, 8 * D_ * 2};
    cuuint32_t box[4] = {64, 4, 2, 2};
    cuuint32_t es[4] = {1, 1, 1, 1};
    enc(m, CU_TENSOR_MAP_DATA_TYPE_BFLOAT16, 4, (void*)base, dims, str, box, es, CU_TENSOR_MAP_INTERLEAVE_NONE,
        CU_TENSOR_MAP_SWIZZLE_128B, CU_TENSOR_MAP_L2_PROMOTION_NONE, CU_TENSOR_MAP_FLOAT_OOB_FILL_NONE);
}

extern "C" void kernel_launch(void* const* d_in, const int* in_sizes, int n_in, void* d_out, int out_size) {
    (void)in_sizes; (void)n_in; (void)out_size;
    static EncodeTiledFn enc = nullptr;
    static bool fused_ok = false;
    static void* scratch = nullptr;
    if (!enc) {
        void* fn = nullptr;
        cudaDriverEntryPointQueryResult q;
        cudaGetDriverEntryPoint("cuTensorMapEncodeTiled", &fn, cudaEnableDefault, &q);
        enc = (EncodeTiledFn)fn;
        cudaGetSymbolAddress(&scratch, g_s);
        cudaFuncSetAttribute(fused_kernel, cudaFuncAttributeMaxDynamicSharedMemorySize, SMEM_BYTES);
        int dev = 0, nsm = 0, ncl = 0;
        cudaGetDevice(&dev);
        cudaDeviceGetAttribute(&nsm, cudaDevAttrMultiProcessorCount, dev);
        cudaLaunchConfig_t cfg = {};
        cfg.gridDim = dim3(132); cfg.blockDim = dim3(NTHREADS); cfg.dynamicSmemBytes = SMEM_BYTES;
        cudaLaunchAttribute at;
        at.id = cudaLaunchAttributeClusterDimension;
        at.val.clusterDim.x = 2; at.val.clusterDim.y = 1; at.val.clusterDim.z = 1;
        cfg.attrs = &at; cfg.numAttrs = 1;
        fused_ok = cudaOccupancyMaxActiveClusters(&ncl, fused_kernel, &cfg) == cudaSuccess && nsm == 132 && ncl == 66;
        (void)cudaGetLastError();
    }
    if (!fused_ok) {
        const bf16* const* in = (const bf16* const*)d_in;
        fb_hidden<<<S_, D_, 0, cudaStreamPerThread>>>(in[0], in[3], in[4], in[10], in[6]);
        fb_ffn1<<<F_ / 128, 128, 0, cudaStreamPerThread>>>(in[0], in[7], in[8]);
        fb_ffn2<<<D_ / 64, 64, 0, cudaStreamPerThread>>>(in[9]);
        fb_seq<<<S_, D_, 0, cudaStreamPerThread>>>(in[0], in[1], in[2], (bf16*)d_out);
        return;
    }
    Params p;
    p.s = (Scratch*)scratch;
    p.x = (const bf16*)d_in[0];
    p.w_r = (const bf16*)d_in[6];
    p.wg = (const bf16*)d_in[7];
    p.wu = (const bf16*)d_in[8];
    p.wd = (const bf16*)d_in[9];
    p.gate_w = (const bf16*)d_in[10];
    p.out = (bf16*)d_out;
    make_map_chunks(enc, &p.mX1, d_in[0], S_, 64);
    make_map_chunks(enc, &p.mX2, d_in[0], S_, 64, 2);
    make_map(enc, &p.mCre, d_in[1], S_, S_, 128);
    make_map(enc, &p.mCim, d_in[2], S_, S_, 128);
    make_map_chunks(enc, &p.mDre, d_in[3], D_, 128);
    make_map_chunks(enc, &p.mDim, d_in[4], D_, 128);
    make_map(enc, &p.mAB, scratch, 64, 8 * 32 * 128, 64, CU_TENSOR_MAP_SWIZZLE_NONE);
    make_map_out(enc, &p.mOut, d_out);
    make_map(enc, &p.mWg, d_in[7], F_, D_, 64, CU_TENSOR_MAP_SWIZZLE_NONE, 32);
    make_map(enc, &p.mWu, d_in[8], F_, D_, 64, CU_TENSOR_MAP_SWIZZLE_NONE, 32);
    make_map(enc, &p.mWd, d_in[9], D_, F_, 8, CU_TENSOR_MAP_SWIZZLE_NONE, 256);
    fused_kernel<<<132, NTHREADS, SMEM_BYTES, cudaStreamPerThread>>>(p);
}
```

```cpp
#include <cuda_runtime.h>
#include <cuda.h>
#include <cuda_bf16.h>
#include <stdint.h>

typedef __nv_bfloat16 bf16;

constexpr int S_ = 2048, D_ = 512, F_ = 1792;
constexpr int NCTA = 128;
constexpr int NTHREADS = 512;
constexpr int NSTAGE = 6;
constexpr int REGION = 32768;
constexpr int FFN_CTAS = F_ / 16;
constexpr uint32_t SPIN_LIMIT = 1u << 22;
constexpr int PACE = 260;
constexpr int PACE0 = 100;
constexpr int A_GAP = 260;
constexpr int B_GAP = 280;
constexpr int LATE_GAP = 240;
constexpr int INIT_GAP = 360;
constexpr int INIT_NS = 300;
constexpr int PF_T0 = 3000;
constexpr int PF_GAP = 850;
constexpr int PF_N0 = 4;
constexpr int FFN_S0 = 4;
constexpr int FFN_W = 7;
constexpr int ROUTER_C = 4;
constexpr int HINT_AT = 5;
constexpr int SUM_T0 = 15000;
constexpr int PS1 = 24;
constexpr int NA = 3;
constexpr int KEY_NS = 300;
constexpr int HSK = 2;

constexpr int OFF_MISC = 7 * REGION;
constexpr int B_F = OFF_MISC;
constexpr int B_G1 = B_F + 64;
constexpr int B_G4 = B_G1 + 8;
constexpr int B_XE = B_G4 + 8;
constexpr int B_GO1 = B_XE + 8;
constexpr int B_GO0 = B_GO1 + 8;
constexpr int B_EPOCH = B_GO0 + 8;
constexpr int B_RETRY = B_EPOCH + 8;
constexpr int B_INIT = B_RETRY + 8;
constexpr int B_FULL = B_INIT + 8;
constexpr int B_EMPTY = B_FULL + 48;
constexpr int B_PUB = B_EMPTY + 48;
constexpr int B_FREE = B_PUB + 8;
constexpr int B_BL = B_FREE + 24;
constexpr int B_TAIL = B_BL + 48;
constexpr int B_HX = B_TAIL + 8;
constexpr int B_FFN = B_HX + 8;
constexpr int B_ROLE = B_FFN + 40;
constexpr int B_EARLY = B_ROLE + 8;
constexpr int B_GATE = B_EARLY + 8;
constexpr int B_G2 = B_GATE + 8;
constexpr int B_LOW = B_G2 + 8;
constexpr int B_G0 = B_LOW + 8;
constexpr int M_EPOCH = B_G0 + 8;
constexpr int M_ROLE = M_EPOCH + 4;
constexpr int M_KEY = OFF_MISC + 416;
constexpr int M_HX = OFF_MISC + 512;
constexpr int M_G = M_HX + 1024;
constexpr int M_XS = M_G + 512;
constexpr int SMEM_BYTES = 232448;
static_assert(M_ROLE + 4 <= M_KEY && M_XS + 512 <= SMEM_BYTES, "smem");

struct Scratch {
    unsigned char ab[8 * 32 * 16384];
    unsigned int hint[8 * 4 * 32];
    unsigned int ready[16 * 32];
    unsigned int gate[S_];
    unsigned int part[FFN_CTAS / 2 * D_];
    unsigned int phint[4 * 16 * 8];
    unsigned int keys[8 * NCTA];
    unsigned int epoch[NCTA + 4];
};
__device__ __align__(1024) Scratch g_s;

struct Params {
    Scratch* s;
    bf16* out;
    const bf16 *x, *gate_w, *w_r, *wg, *wu, *wd;
    CUtensorMap mDre, mDim, mX1, mX2, mCre, mCim, mAB, mOut, mWg, mWu, mWd;
};

#define ELECT "{.reg .pred p; elect.sync _|p, 0xffffffff; @p "
__device__ __forceinline__ uint32_t smem_u32(const void* p) { return (uint32_t)__cvta_generic_to_shared(p); }
__device__ __forceinline__ uint32_t clk() { return (uint32_t)clock64(); }
__device__ __forceinline__ void spin_until(uint32_t t) { while ((int)(clk() - t) < 0) {} }
template <int NS>
__device__ __forceinline__ void sleep_until(uint32_t t) { while ((int)(clk() - t) < 0) __nanosleep(NS); }
__device__ __forceinline__ void mbar_init_elect(uint32_t bar, uint32_t cnt) {
    asm volatile(ELECT "mbarrier.init.shared::cta.b64 [%0], %1;}" ::"r"(bar), "r"(cnt) : "memory");
}
__device__ __forceinline__ void mbar_expect_tx_elect(uint32_t bar, uint32_t bytes) {
    asm volatile(ELECT "mbarrier.arrive.expect_tx.shared::cta.b64 _, [%0], %1;}" ::"r"(bar), "r"(bytes) : "memory");
}
template <int N = 1>
__device__ __forceinline__ void mbar_arrive_elect(uint32_t bar) {
    asm volatile(ELECT "mbarrier.arrive.shared::cta.b64 _, [%0], %1;}" ::"r"(bar), "n"(N) : "memory");
}
__device__ __forceinline__ void mbar_arrive_if(uint32_t bar, bool pred) {
    asm volatile("{.reg .pred p; setp.ne.b32 p, %1, 0; @p mbarrier.arrive.shared::cta.b64 _, [%0];}" ::"r"(bar), "r"((int)pred) : "memory");
}
__device__ __forceinline__ void mbar_arrive_warp(uint32_t bar) {
    __syncwarp();
    mbar_arrive_if(bar, (threadIdx.x & 31) == 0);
}
template <int N>
__device__ __forceinline__ void release_pair(uint32_t bar, uint32_t rbar, bool pred) {
    asm volatile("{.reg .pred p; setp.ne.b32 p, %2, 0; @p mbarrier.arrive.shared::cta.b64 _, [%0], %3;"
                 " @p mbarrier.arrive.shared::cluster.b64 _, [%1], %3;}" ::"r"(bar), "r"(rbar), "r"((int)pred), "n"(N) : "memory");
}
__device__ __forceinline__ uint32_t mapa(uint32_t a, uint32_t cta) {
    uint32_t r;
    asm volatile("mapa.shared::cluster.u32 %0, %1, %2;" : "=r"(r) : "r"(a), "r"(cta));
    return r;
}
__device__ __forceinline__ bool mbar_test(uint32_t bar, uint32_t parity) {
    uint32_t ok;
    asm volatile("{.reg .pred p; mbarrier.test_wait.parity.shared::cta.b64 p, [%1], %2; selp.u32 %0,1,0,p;}"
                 : "=r"(ok) : "r"(bar), "r"(parity) : "memory");
    return ok;
}
__device__ __forceinline__ void mbar_wait(uint32_t bar, uint32_t parity) {
    asm volatile("{.reg .pred p, q; .reg .u32 n; mov.u32 n, 0;\n"
                 "W%=: mbarrier.try_wait.parity.shared::cta.b64 p, [%0], %1;\n"
                 "add.u32 n, n, 1; setp.lt.and.u32 q, n, %2, !p; @q bra W%=; @!p trap;}" ::"r"(bar), "r"(parity), "n"(SPIN_LIMIT) : "memory");
}
__device__ __forceinline__ void mbar_wait_cluster(uint32_t bar, uint32_t parity) {
    asm volatile("{.reg .pred p, q; .reg .u32 n; mov.u32 n, 0;\n"
                 "W%=: mbarrier.try_wait.parity.acquire.cluster.shared::cta.b64 p, [%0], %1;\n"
                 "add.u32 n, n, 1; setp.lt.and.u32 q, n, %2, !p; @q bra W%=; @!p trap;}" ::"r"(bar), "r"(parity), "n"(SPIN_LIMIT) : "memory");
}
__device__ __forceinline__ void mbar_spin(uint32_t bar, uint32_t parity) {
    asm volatile("{.reg .pred p;\nW%=: mbarrier.try_wait.parity.shared::cta.b64 p, [%0], %1; @!p bra W%=;}" ::"r"(bar), "r"(parity) : "memory");
}
__device__ __forceinline__ void cluster_arrive() { asm volatile("barrier.cluster.arrive.relaxed.aligned;" ::: "memory"); }
__device__ __forceinline__ void cluster_wait() { asm volatile("barrier.cluster.wait.acquire.aligned;" ::: "memory"); }
__device__ __forceinline__ void side_bar() { asm volatile("bar.sync 1, 128;" ::: "memory"); }
__device__ __forceinline__ void tma2d_elect(uint32_t dst, const CUtensorMap* m, int c0, int c1, uint32_t bar) {
    asm volatile(ELECT "cp.async.bulk.tensor.2d.shared::cluster.global.mbarrier::complete_tx::bytes [%0], [%1, {%3,%4}], [%2];}"
                 ::"r"(dst), "l"(m), "r"(bar), "r"(c0), "r"(c1) : "memory");
}
__device__ __forceinline__ void tma2d_pair_elect(uint32_t dst, const CUtensorMap* m, int c0, int c1, uint32_t bar) {
    asm volatile(ELECT "cp.async.bulk.tensor.2d.shared::cluster.global.mbarrier::complete_tx::bytes.multicast::cluster"
                 " [%0], [%1, {%3,%4}], [%2], %5;}" ::"r"(dst), "l"(m), "r"(bar), "r"(c0), "r"(c1), "h"((uint16_t)3) : "memory");
}
__device__ __forceinline__ void tma3d_elect(uint32_t dst, const CUtensorMap* m, int row, int chunk, uint32_t bar) {
    asm volatile(ELECT "cp.async.bulk.tensor.3d.shared::cluster.global.mbarrier::complete_tx::bytes [%0], [%1, {%3,%4,%5}], [%2];}"
                 ::"r"(dst), "l"(m), "r"(bar), "r"(0), "r"(row), "r"(chunk) : "memory");
}
__device__ __forceinline__ void bulk_wait_read() {
    asm volatile("cp.async.bulk.commit_group; cp.async.bulk.wait_group.read 0;" ::: "memory");
    __syncwarp();
}
__device__ __forceinline__ void fence_proxy_async_smem() { asm volatile("fence.proxy.async.shared::cta;" ::: "memory"); }
__device__ __forceinline__ uint32_t ld_relaxed(const void* p) {
    uint32_t v;
    asm volatile("ld.relaxed.gpu.global.u32 %0, [%1];" : "=r"(v) : "l"(p) : "memory");
    return v;
}
__device__ __forceinline__ uint4 ld_relaxed4(const void* p) {
    uint4 v;
    asm volatile("ld.relaxed.gpu.global.v4.u32 {%0,%1,%2,%3}, [%4];" : "=r"(v.x), "=r"(v.y), "=r"(v.z), "=r"(v.w) : "l"(p) : "memory");
    return v;
}
__device__ __forceinline__ void red_inc_if(unsigned int* p, bool pred) {
    asm volatile("{.reg .pred p; setp.ne.b32 p, %1, 0; @p red.relaxed.gpu.global.add.u32 [%0], 1;}" ::"l"(p), "r"((int)pred) : "memory");
}
__device__ __forceinline__ uint32_t tagf(float v, uint32_t par) { return (__float_as_uint(v) & ~1u) | par; }
__device__ __forceinline__ uint4 wait_tags(const unsigned int* p, int bit, uint32_t par) {
    uint32_t n = 0;
    while (true) {
        const uint4 v = ld_relaxed4(p);
        const uint32_t m = par ? (v.x & v.y & v.z & v.w) : ~(v.x | v.y | v.z | v.w);
        if (__all_sync(0xffffffffu, (m >> bit) & 1u)) return v;
        __nanosleep(100);
        if (++n > SPIN_LIMIT) __trap();
    }
}
__device__ __forceinline__ void wait_counter(const unsigned int* p, uint32_t want) {
    uint32_t n = 0;
    while (!__all_sync(0xffffffffu, (int)(ld_relaxed(p) - want) >= 0)) {
        __nanosleep(200);
        if (++n > SPIN_LIMIT) __trap();
    }
    asm volatile("fence.acquire.gpu;" ::: "memory");
}
__device__ __forceinline__ uint32_t stale_tags(uint32_t a, uint32_t par) {
    uint32_t r;
    asm volatile("{.reg .b32 v<16>;\n"
                 "ld.shared.u32 v0, [%1]; ld.shared.u32 v1, [%1+256]; ld.shared.u32 v2, [%1+512]; ld.shared.u32 v3, [%1+768];\n"
                 "ld.shared.u32 v4, [%1+4096]; ld.shared.u32 v5, [%1+4352]; ld.shared.u32 v6, [%1+4608]; ld.shared.u32 v7, [%1+4864];\n"
                 "ld.shared.u32 v8, [%1+8192]; ld.shared.u32 v9, [%1+8448]; ld.shared.u32 v10, [%1+8704]; ld.shared.u32 v11, [%1+8960];\n"
                 "ld.shared.u32 v12, [%1+12288]; ld.shared.u32 v13, [%1+12544]; ld.shared.u32 v14, [%1+12800]; ld.shared.u32 v15, [%1+13056];\n"
                 "lop3.b32 v0, v0, v1, %2, 0x7e; lop3.b32 v2, v2, v3, %2, 0x7e; lop3.b32 v4, v4, v5, %2, 0x7e; lop3.b32 v6, v6, v7, %2, 0x7e;\n"
                 "lop3.b32 v8, v8, v9, %2, 0x7e; lop3.b32 v10, v10, v11, %2, 0x7e; lop3.b32 v12, v12, v13, %2, 0x7e; lop3.b32 v14, v14, v15, %2, 0x7e;\n"
                 "lop3.b32 v0, v0, v2, v4, 0xfe; lop3.b32 v6, v6, v8, v10, 0xfe; lop3.b32 v0, v0, v6, v12, 0xfe; or.b32 %0, v0, v14;}"
                 : "=r"(r) : "r"(a), "r"(par) : "memory");
    return r;
}
template <int OFF>
__device__ __forceinline__ uint4 ldg_nc(const void* p) {
    uint4 v;
    asm volatile("ld.global.nc.v4.u32 {%0,%1,%2,%3}, [%4+%5];" : "=r"(v.x), "=r"(v.y), "=r"(v.z), "=r"(v.w) : "l"(p), "n"(OFF));
    return v;
}
template <int OFF>
__device__ __forceinline__ void stg128(void* p, const uint4& v) {
    asm volatile("st.global.v4.u32 [%0+%5], {%1,%2,%3,%4};" ::"l"(p), "r"(v.x), "r"(v.y), "r"(v.z), "r"(v.w), "n"(OFF) : "memory");
}
template <int OFF>
__device__ __forceinline__ void sts128(uint32_t a, const uint4& v) {
    asm volatile("st.shared.v4.u32 [%0+%5], {%1,%2,%3,%4};" ::"r"(a), "r"(v.x), "r"(v.y), "r"(v.z), "r"(v.w), "n"(OFF) : "memory");
}
__device__ __forceinline__ uint4 lds128(uint32_t a) {
    uint4 v;
    asm volatile("ld.shared.v4.u32 {%0,%1,%2,%3}, [%4];" : "=r"(v.x), "=r"(v.y), "=r"(v.z), "=r"(v.w) : "r"(a) : "memory");
    return v;
}
template <int OFF>
__device__ __forceinline__ void red_bf16x8(void* p, uint32_t x, uint32_t y, uint32_t z, uint32_t w) {
    asm volatile("red.relaxed.gpu.global.add.noftz.v4.bf16x2 [%0+%5], {%1,%2,%3,%4};"
                 ::"l"(p), "r"(x), "r"(y), "r"(z), "r"(w), "n"(OFF) : "memory");
}
__device__ __forceinline__ void sched_cut() {
    asm volatile("{.reg .pred p; .reg .u64 t; .reg .u32 a, b;\n"
                 "C%=: mov.u64 t, %%clock64; mov.b64 {a, b}, t; setp.eq.u32 p, a, %0; @p bra C%=;}" ::"n"(0) : "memory");
}
__device__ __forceinline__ uint32_t pin(uint32_t v) { return __shfl_xor_sync(0xffffffffu, v, 0); }
template <class T>
__device__ __forceinline__ T* pin(T* p) { return (T*)__shfl_xor_sync(0xffffffffu, (unsigned long long)p, 0); }
__device__ __forceinline__ float selpf(float a, float b, bool p) {
    float r;
    asm("{.reg .pred q; setp.ne.b32 q, %3, 0; selp.f32 %0, %1, %2, q;}" : "=f"(r) : "f"(a), "f"(b), "r"((int)p));
    return r;
}
template <int N, int MASK, int SZ>
__device__ __forceinline__ void halve(float (&a)[SZ]) {
    const bool up = threadIdx.x & MASK;
#pragma unroll
    for (int j = 0; j < N; j++) a[j] = selpf(a[N + j], a[j], up) + __shfl_xor_sync(0xffffffffu, selpf(a[j], a[N + j], up), MASK);
}
__device__ __forceinline__ float bflo(uint32_t u) { return __uint_as_float(u << 16); }
__device__ __forceinline__ float bfhi(uint32_t u) { return __uint_as_float(u & 0xffff0000u); }
__device__ __forceinline__ uint32_t pack_bf16(float lo, float hi) {
    uint32_t r;
    asm("cvt.rn.bf16x2.f32 %0, %1, %2;" : "=r"(r) : "f"(hi), "f"(lo));
    return r;
}
__device__ __forceinline__ uint32_t hmul2_bf16(uint32_t a, uint32_t b) {
    uint32_t r;
    asm("mul.rn.bf16x2 %0, %1, %2;" : "=r"(r) : "r"(a), "r"(b));
    return r;
}
__device__ __forceinline__ float rbf(float v) { return bflo(pack_bf16(v, 0.f)); }
__device__ __forceinline__ float sigmoidf_(float v) { return __fdividef(1.0f, 1.0f + __expf(-v)); }

__device__ __forceinline__ void wg_fence() { asm volatile("wgmma.fence.sync.aligned;" ::: "memory"); }
__device__ __forceinline__ void wg_commit() { asm volatile("wgmma.commit_group.sync.aligned;" ::: "memory"); }
template <int N> __device__ __forceinline__ void wg_wait() { asm volatile("wgmma.wait_group.sync.aligned %0;" ::"n"(N) : "memory"); }
__device__ __forceinline__ uint64_t desc128(uint32_t lo) { return (uint64_t)lo | (0x40000040ull << 32); }
__device__ __forceinline__ uint64_t desc64(uint32_t lo) { return (uint64_t)lo | (0x80000020ull << 32); }
__device__ __forceinline__ void fence_regs(float (&d)[64]) {
#pragma unroll
    for (int i = 0; i < 64; i++) asm volatile("" : "+f"(d[i])::"memory");
}
template <int TB>
__device__ __forceinline__ void wgmma128(float (&d)[64], uint64_t da, uint64_t db, int scaleD) {
    asm volatile(
        "{ .reg .pred p; setp.ne.b32 p, %66, 0;\n"
        "wgmma.mma_async.sync.aligned.m64n128k16.f32.bf16.bf16 "
        "{%0,%1,%2,%3,%4,%5,%6,%7,%8,%9,%10,%11,%12,%13,%14,%15,%16,%17,%18,%19,%20,%21,%22,%23,%24,%25,%26,%27,%28,%29,%30,%31,"
        "%32,%33,%34,%35,%36,%37,%38,%39,%40,%41,%42,%43,%44,%45,%46,%47,%48,%49,%50,%51,%52,%53,%54,%55,%56,%57,%58,%59,%60,%61,%62,%63}, "
        "%64, %65, p, 1, 1, 0, %67;\n}"
        : "+f"(d[0]), "+f"(d[1]), "+f"(d[2]), "+f"(d[3]), "+f"(d[4]), "+f"(d[5]), "+f"(d[6]), "+f"(d[7]),
          "+f"(d[8]), "+f"(d[9]), "+f"(d[10]), "+f"(d[11]), "+f"(d[12]), "+f"(d[13]), "+f"(d[14]), "+f"(d[15]),
          "+f"(d[16]), "+f"(d[17]), "+f"(d[18]), "+f"(d[19]), "+f"(d[20]), "+f"(d[21]), "+f"(d[22]), "+f"(d[23]),
          "+f"(d[24]), "+f"(d[25]), "+f"(d[26]), "+f"(d[27]), "+f"(d[28]), "+f"(d[29]), "+f"(d[30]), "+f"(d[31]),
          "+f"(d[32]), "+f"(d[33]), "+f"(d[34]), "+f"(d[35]), "+f"(d[36]), "+f"(d[37]), "+f"(d[38]), "+f"(d[39]),
          "+f"(d[40]), "+f"(d[41]), "+f"(d[42]), "+f"(d[43]), "+f"(d[44]), "+f"(d[45]), "+f"(d[46]), "+f"(d[47]),
          "+f"(d[48]), "+f"(d[49]), "+f"(d[50]), "+f"(d[51]), "+f"(d[52]), "+f"(d[53]), "+f"(d[54]), "+f"(d[55]),
          "+f"(d[56]), "+f"(d[57]), "+f"(d[58]), "+f"(d[59]), "+f"(d[60]), "+f"(d[61]), "+f"(d[62]), "+f"(d[63])
        : "l"(da), "l"(db), "r"(scaleD), "n"(TB));
}

__device__ __forceinline__ uint32_t get_role(uint32_t& smid) {
    uint32_t role;
    asm volatile("mov.u32 %0, %%smid;" : "=r"(smid));
    asm("{.reg .pred p, q; .reg .u32 t, a, b; shr.u32 t, %1, 1; mad.lo.u32 a, t, 293, -928; shr.u32 a, a, 8; mad.lo.u32 b, t, 8, -464;"
        " setp.lt.u32 p, t, 32; setp.lt.u32 q, t, 62; selp.u32 a, a, b, q; selp.u32 %0, t, a, p;}" : "=r"(role) : "r"(smid));
    return role;
}
__device__ __forceinline__ int tile_of_step(int step, int own) {
    const int u = step >= 17 ? step - 17 - (step > PS1) : step - 2;
    int e = u + (u >= (own & 14) ? 2 : 0);
    if (step == 16 || step == PS1) e = own ^ 1;
    if (step < 2) e = own;
    return e + (step >= 17 || step == 1 ? 16 : 0);
}
__device__ __forceinline__ uint32_t router_key(float score, int row) {
    const float r = score + 0.0f;
    uint32_t u = pack_bf16(r, 0.f) & 0xffffu;
    u = (u & 0x8000u) ? (~u & 0xffffu) : (u | 0x8000u);
    if (r != r) u = 0;
    return (u << 16) | (uint32_t)(0x7fff - row);
}

#define g_fb_h ((float*)g_s.part)
#define g_fb_upd (g_fb_h + 2048)
#define g_fb_gate (g_fb_h + 4096)
#define g_fb_keys (g_s.part + 8192)
__global__ void fb_hidden(const bf16* x, const bf16* dre, const bf16* dim, const bf16* gw, const bf16* wr) {
    __shared__ float xs[D_];
    const int s = blockIdx.x, t = threadIdx.x;
    xs[t] = __bfloat162float(x[s * D_ + t]);
    __syncthreads();
    float a = 0.f, b = 0.f;
    for (int d = 0; d < D_; d++) { a = fmaf(xs[d], __bfloat162float(dre[t * D_ + d]), a); b = fmaf(xs[d], __bfloat162float(dim[t * D_ + d]), b); }
    ((bf16*)g_s.ab)[s * 1024 + t] = __float2bfloat16(a);
    ((bf16*)g_s.ab)[s * 1024 + 512 + t] = __float2bfloat16(b);
    if (t == 0) {
        float u = 0.f, v = 0.f;
        for (int d = 0; d < D_; d++) { u = fmaf(xs[d], __bfloat162float(gw[d]), u); v = fmaf(xs[d], __bfloat162float(wr[d]), v); }
        g_fb_gate[s] = sigmoidf_(u);
        g_fb_keys[s] = router_key(v, s);
    }
}
__device__ uint32_t fb_best() {
    uint32_t k = 0;
    for (int i = 0; i < S_; i++) k = max(k, g_fb_keys[i]);
    return k;
}
__global__ void fb_ffn1(const bf16* x, const bf16* wg, const bf16* wu) {
    const int f = blockIdx.x * blockDim.x + threadIdx.x, idx = 0x7fff - (int)(fb_best() & 0x7fffu);
    float a = 0.f, b = 0.f;
    for (int d = 0; d < D_; d++) {
        const float xv = __bfloat162float(x[idx * D_ + d]);
        a = fmaf(xv, __bfloat162float(wg[d * F_ + f]), a); b = fmaf(xv, __bfloat162float(wu[d * F_ + f]), b);
    }
    g_fb_h[f] = a * sigmoidf_(a) * b;
}
__global__ void fb_ffn2(const bf16* wd) {
    const int e = blockIdx.x * blockDim.x + threadIdx.x;
    const uint32_t u = fb_best() >> 16, rb = (u & 0x8000u) ? (u & 0x7fffu) : (~u & 0xffffu);
    float a = 0.f;
    for (int f = 0; f < F_; f++) a = fmaf(g_fb_h[f], __bfloat162float(wd[f * D_ + e]), a);
    g_fb_upd[e] = a * sigmoidf_(__uint_as_float(rb << 16));
}
__global__ void fb_seq(const bf16* x, const bf16* cre, const bf16* cim, bf16* out) {
    __shared__ float c[2][S_];
    __shared__ int idx;
    const int t = blockIdx.x, e = threadIdx.x;
    for (int i = e; i < S_; i += D_) { c[0][i] = __bfloat162float(cre[t * S_ + i]); c[1][i] = __bfloat162float(cim[t * S_ + i]); }
    if (e == 0) idx = 0x7fff - (int)(fb_best() & 0x7fffu);
    __syncthreads();
    float y = 0.f;
    for (int s = 0; s < S_; s++)
        y += c[0][s] * __bfloat162float(((const bf16*)g_s.ab)[s * 1024 + e]) - c[1][s] * __bfloat162float(((const bf16*)g_s.ab)[s * 1024 + 512 + e]);
    const float g = g_fb_gate[t];
    out[t * D_ + e] = __float2bfloat16(g * y + (1.f - g) * (__bfloat162float(x[t * D_ + e]) + (t == idx ? g_fb_upd[e] : 0.f)));
}

__device__ __forceinline__ void spare_job(const Params& p, unsigned char* smem, int sp, uint32_t tstart) {
    const int tid = threadIdx.x, warp = tid >> 5, lane = tid & 31;
    const uint32_t e1 = *(volatile unsigned int*)&p.s->epoch[NCTA + sp] + 1u;
    const uint32_t par = e1 & 1u;
    uint32_t* sel = (uint32_t*)smem;
    float* acc = (float*)(smem + 1024);
    __syncthreads();
    if (tid == 0) *(volatile unsigned int*)&p.s->epoch[NCTA + sp] = e1;
    sleep_until<500>(tstart + SUM_T0);
    if (warp < 14) {
        uint32_t n = 0;
        while ((int)(ld_relaxed(p.s->phint + (sp * 16 + warp) * 8) - e1 * 8u) < 0) {
            __nanosleep(100);
            if (++n > SPIN_LIMIT) __trap();
        }
        const unsigned int* src = p.s->part + warp * 4 * D_ + sp * 128 + lane * 4;
        uint4 v[4];
        while (true) {
            uint32_t bad = 0;
#pragma unroll
            for (int i = 0; i < 4; i++) v[i] = ld_relaxed4(src + i * D_);
#pragma unroll
            for (int i = 0; i < 4; i++) bad |= (v[i].x ^ par) | (v[i].y ^ par) | (v[i].z ^ par) | (v[i].w ^ par);
            if (!__any_sync(0xffffffffu, bad & 1u)) break;
            if (++n > SPIN_LIMIT) __trap();
        }
        float4 s = make_float4(0.f, 0.f, 0.f, 0.f);
#pragma unroll
        for (int i = 0; i < 4; i++) {
            s.x += __uint_as_float(v[i].x); s.y += __uint_as_float(v[i].y);
            s.z += __uint_as_float(v[i].z); s.w += __uint_as_float(v[i].w);
        }
        *(float4*)&acc[warp * 128 + lane * 4] = s;
    } else if (warp == 14) {
        const uint4 k4 = wait_tags(p.s->keys + lane * 4, 15, par);
        const uint32_t k = __reduce_max_sync(0xffffffffu, max(max(k4.x, k4.y), max(k4.z, k4.w)));
        const int idx = 0x7fff - (int)(k & 0x7fffu);
        const uint4 g4 = wait_tags(p.s->gate + (idx & ~3), 0, par);
        const uint32_t gw = (idx & 2) ? ((idx & 1) ? g4.w : g4.z) : ((idx & 1) ? g4.y : g4.x);
        const uint32_t u = k >> 16;
        const uint32_t rb = (u & 0x8000u) ? (u & 0x7fffu) : (~u & 0xffffu);
        const float og = 1.f - __uint_as_float(gw & ~1u), rs = sigmoidf_(__uint_as_float(rb << 16));
        if (lane == 0) { sel[0] = idx; sel[1] = pack_bf16(og, og); sel[2] = pack_bf16(rs, rs); }
        sleep_until<500>(tstart + SUM_T0 + 3000);
        wait_counter(p.s->ready + (idx >> 7) * 32, e1 * 8u);
    }
    __syncthreads();
    if (tid < 64) {
        float t0 = 0.f, t1 = 0.f;
#pragma unroll
        for (int i = 0; i < 14; i++) {
            const float2 z = *(const float2*)&acc[i * 128 + tid * 2];
            t0 += z.x; t1 += z.y;
        }
        asm volatile("red.relaxed.gpu.global.add.noftz.bf16x2 [%0], %1;" ::"l"(p.out + sel[0] * D_ + sp * 128 + tid * 2),
                     "r"(hmul2_bf16(sel[1], hmul2_bf16(sel[2], pack_bf16(t0, t1)))) : "memory");
    }
}

__host__ __device__ constexpr int off_d(int c) { return (c < 2 ? 1 : c / 2 + 2) * REGION + (c & 1) * 16384; }
__host__ __device__ constexpr int off_xe(int c) { return (c < 2 ? 6 * REGION : c < 4 ? 16384 : c < 6 ? 0 : 6 * REGION + 16384) + (c & 1) * 8192; }
__host__ __device__ constexpr int off_xl(int c) { return c < 4 ? 2 * REGION + c * 8192 : off_xe(c - 4); }

__global__ void __cluster_dims__(2, 1, 1) __launch_bounds__(NTHREADS, 1)
fused_kernel(const __grid_constant__ Params p) {
    extern __shared__ __align__(1024) unsigned char smem[];
    const uint32_t tstart = clk();
    const uint32_t sb = smem_u32(smem);
    const int tid = threadIdx.x, lane = tid & 31;
    const int rank = blockIdx.x & 1;
    uint32_t t1 = 0;
    if (__any_sync(0xffffffffu, tid == 0)) {
        uint32_t s0;
        const uint32_t r0 = get_role(s0);
        mbar_init_elect(sb + B_F, 1);
        if (r0 < 64) {
#pragma unroll
            for (int c = 0; c < 2; c++) {
                if (c) {
                    spin_until(t1 + PACE);
                    mbar_init_elect(sb + B_F + 8, 1);
                }
                tma3d_elect(sb + off_d(c), &p.mDre + ((r0 >> 2) & 1), (r0 & 24) * 16, c, sb + B_F + 8 * c);
                tma3d_elect(sb + off_xe(c), &p.mX1, (r0 & 3) * 256 + (r0 & 32) * 4 + rank * 64, c, sb + B_F + 8 * c);
                mbar_expect_tx_elect(sb + B_F + 8 * c, 24576);
                if (!c) {
                    t1 = clk() + PACE0;
                    mbar_init_elect(sb + B_G0, 1);
                    tma3d_elect(sb + off_xl(0), &p.mX1, (r0 & 3) * 256 + (r0 & 32) * 4 + rank * 64 + 1024, 0, sb + B_G0);
                    mbar_expect_tx_elect(sb + B_G0, 8192);
                }
            }
        }
    }
    const int warp = __shfl_sync(0xffffffffu, tid >> 5, 0);
    uint32_t smid;
    const uint32_t role = get_role(smid);
    const int gpc = role & 7;
    const int tn = (role >> 3) & 3;
    const int comp = gpc >> 2;
    const int own = (gpc & 3) * 4 + ((role >> 5) & 1) * 2 + rank;
    const int blk = comp * 4 + tn;
    const int cta = gpc * 16 + (role >> 3) * 2 + rank;
    const bool ffn = cta < FFN_CTAS;
    uint32_t epoch = 0;
    if (warp != 0) {
        const uint32_t b1 = sb + B_F + 8 * warp;
        mbar_init_elect(warp < 2 ? b1 + 360 : b1, 1);
        if (warp >= 2 && warp < 5) mbar_init_elect(b1 + 360, warp < 4 ? 1 : 4);
        mbar_init_elect(b1 + 120, warp < 7 ? 5 : warp < 14 ? 4 : warp - 12);
        mbar_init_elect(b1 + 240, 1);
        if (warp == 9 || warp == 15) mbar_expect_tx_elect(b1 + 240, warp == 9 ? 2048 : 4);
        asm volatile("fence.mbarrier_init.release.cluster;" ::: "memory");
        if (tid == 128 && role < 64) epoch = *(volatile unsigned int*)&p.s->epoch[cta];
    }
    if (role >= 64) {
        spare_job(p, smem, smid & 3, tstart);
        return;
    }
    __syncthreads();
    cluster_arrive();
    if (warp == 0) {
#pragma unroll
        for (int c = 2; c < 8; c++) {
            spin_until(t1 + c * PACE);
            tma3d_elect(sb + off_d(c), &p.mDre + comp, tn * 128, c, sb + B_F + 8 * c);
            tma3d_elect(sb + off_xe(c), &p.mX1, own * 64, c, sb + B_F + 8 * c);
            mbar_expect_tx_elect(sb + B_F + 8 * c, 24576);
        }
        tma3d_elect(sb + off_xl(1), &p.mX1, own * 64 + 1024, 1, sb + B_G1);
        mbar_expect_tx_elect(sb + B_G1, 8192);
        spin_until(t1 + 8 * PACE);
        tma3d_elect(sb + off_xl(2), &p.mX2, own * 64 + 1024, 2, sb + B_G2);
        mbar_expect_tx_elect(sb + B_G2, 16384);
        if (tn < 2)
            asm volatile(ELECT "cp.async.bulk.prefetch.tensor.3d.L2.global [%0, {%1,%2,%3}];}"
                         ::"l"(&p.mX2), "r"(0), "r"(own * 64 + 1024), "r"(4 + 2 * tn) : "memory");
    }

    if (warp < 4) {
        const int tab = tile_of_step(lane, own);
        const uint32_t bdst = sb + 16384 + rank * 8192;
        const int brow = blk * 4096 + rank * 64;
        if (warp == 0) {
            mbar_spin(sb + B_XE, 0);
            tma3d_elect(sb + off_xl(4), &p.mX2, own * 64 + 1024, 4, sb + B_G4);
            tma3d_elect(sb + off_xl(6), &p.mX2, own * 64 + 1024, 6, sb + B_G4);
            mbar_expect_tx_elect(sb + B_G4, 32768);
#define LOAD_A() const int e = __shfl_sync(0xffffffffu, tab, step);                                             \
                 const uint32_t bar = sb + 8 * slot;                                                            \
                 mbar_spin(bar + B_EMPTY, ph);                                                                  \
                 tma2d_elect(sb + slot * REGION, &p.mCre + comp, e * 64, own * 128, bar + B_FULL);              \
                 mbar_expect_tx_elect(bar + B_FULL, 16384)
            uint32_t slot = 0, ph = 0;
            int step = 0;
#pragma unroll 1
            for (int i = 0; i < NSTAGE; i++) {
                step = slot = i < 2 ? i ^ 1 : i;
                LOAD_A();
                if (i == 2 || i == 3) spin_until(clk() + A_GAP);
            }
            step = NSTAGE;
            slot = 0; ph = 1;
#pragma unroll 1
            for (int h = 0; h < 3; h++) {
                const int last = h == 0 ? 16 : h == 1 ? PS1 : 32 - NA;
#pragma unroll 1
                for (; step < last; step++) {
                    LOAD_A();
                    tma2d_pair_elect(bdst + slot * REGION, &p.mAB, 0, brow + e * 128, bar + B_BL);
                    mbar_expect_tx_elect(bar + B_BL, 16384);
                    if (++slot == NSTAGE) { slot = 0; ph ^= 1; }
                }
                if (h == 2) break;
                LOAD_A();
                tma2d_elect(bdst + slot * REGION, &p.mAB, 0, brow + e * 128, bar + B_BL);
                tma2d_elect((bdst ^ 8192) + slot * REGION, &p.mAB, 0, (brow ^ 64) + e * 128, bar + B_BL);
                mbar_expect_tx_elect(bar + B_BL, 16384);
                step++;
                if (++slot == NSTAGE) { slot = 0; ph ^= 1; }
            }
            mbar_spin(sb + B_LOW, 0);
            uint32_t aslot = 6;
#pragma unroll 1
            for (; step < 32; step++) {
                const int e = __shfl_sync(0xffffffffu, tab, step);
                const uint32_t bar = sb + 8 * slot;
                tma2d_elect(sb + aslot * REGION, &p.mCre + comp, e * 64, own * 128, bar + B_FULL);
                mbar_expect_tx_elect(bar + B_FULL, 16384);
                mbar_expect_tx_elect(bar + B_BL, 16384);
                mbar_spin(bar + B_EMPTY, ph);
                tma2d_pair_elect(bdst + slot * REGION, &p.mAB, 0, brow + e * 128, bar + B_BL);
                aslot = slot;
                if (++slot == NSTAGE) { slot = 0; ph ^= 1; }
            }
        } else if (warp == 1) {
            if (lane < 4) asm volatile("prefetch.tensormap [%0];" ::"l"(&p.mCre + lane) : "memory");
            __syncwarp();
            cluster_wait();
            if (lane == 0)
                asm volatile("st.async.weak.shared::cluster.mbarrier::complete_tx::bytes.u32 [%0], %1, [%2];"
                             ::"r"(mapa(sb + M_ROLE, rank ^ 1)), "r"(role), "r"(mapa(sb + B_ROLE, rank ^ 1)) : "memory");
            mbar_wait_cluster(sb + B_ROLE, 0);
            if (*(volatile uint32_t*)(smem + M_ROLE) != role) __trap();
            mbar_wait(sb + B_EPOCH, 0);
            const uint32_t want = (*(volatile uint32_t*)(smem + M_EPOCH) + 1u) * 4u;
            const int eh = __shfl_sync(0xffffffffu, tab, 2 + (lane & 3));
            const unsigned int* hp = p.s->hint + (blk * 4 + (eh >> 1)) * 32 + (eh & 1);
            uint32_t seen = __ballot_sync(0xffffffffu, ld_relaxed(hp) == want);
            int rows[4];
#pragma unroll
            for (int i = 0; i < 4; i++) {
                rows[i] = brow + __shfl_sync(0xffffffffu, tab, 2 + i) * 128;
                mbar_expect_tx_elect(sb + B_BL + 8 * (2 + i), 16384);
            }
            mbar_wait(sb + B_EMPTY + 8 * 3, 0);
            mbar_spin(sb + B_EMPTY + 8 * 2, 0);
            uint32_t t3 = 0;
#pragma unroll
            for (int i = 0; i < 4; i++) {
                while (!((seen >> i) & 1u)) seen = __ballot_sync(0xffffffffu, ld_relaxed(hp) == want);
                if (i) spin_until(t3 + B_GAP);
                t3 = clk();
                if (i >= 2) mbar_spin(sb + B_EMPTY + 8 * (2 + i), 0);
                tma2d_pair_elect(bdst + (2 + i) * REGION, &p.mAB, 0, rows[i], sb + B_BL + 8 * (2 + i));
            }
            mbar_wait(sb + B_FREE, 0);
            unsigned char* gdst = p.s->ab + (blk * 32 + own + 16) * 16384;
            t3 = clk();
#pragma unroll 1
            for (int i = 0; i < 16; i++) {
                sleep_until<20>(t3);
                t3 += LATE_GAP;
                asm volatile(ELECT "cp.async.bulk.global.shared::cta.bulk_group [%0], [%1], 1024;}"
                             ::"l"(gdst + i * 1024), "r"(sb + 6 * REGION + i * 1024) : "memory");
            }
            bulk_wait_read();
            mbar_arrive_elect(sb + B_FREE + 8);
            mbar_wait(sb + B_PUB, 0);
            if (lane == 0) {
                asm volatile("fence.proxy.async.global;" ::: "memory");
                asm volatile("red.release.gpu.global.add.u32 [%0], 1;" ::"l"(p.s->ready + (cta >> 3) * 32) : "memory");
            }
            __syncwarp();
            __nanosleep(INIT_NS);
            wait_counter(p.s->ready + own * 32, want * 2u);
            mbar_arrive_elect(sb + B_INIT);
        } else {
            mbar_arrive_elect(sb + B_BL + 8 * (warp & 1));
            uint32_t k = warp == 3 ? 0 : 12;
#define PREFETCH_W() {                                                                                          \
                const char* src = (k >= 8 ? (const char*)p.wd + ((cta >> 5) * 2 + (k >> 1) - 4) * 229376        \
                                          : (const char*)((cta & 32) ? p.wu : p.wg) + ((cta >> 6) * 4 + (k >> 1)) * 229376) \
                                  + ((cta & 31) * 2 + (k & 1)) * 3584;                                          \
                asm volatile(ELECT "cp.async.bulk.prefetch.L2.global [%0], 3584;}" ::"l"(src) : "memory");      \
                k++; }
#pragma unroll 1
            while (k < PF_N0) {
                sleep_until<50>(tstart + PF_T0 + k * PF_GAP);
                __syncwarp();
                PREFETCH_W();
            }
            mbar_wait(sb + B_EPOCH, 0);
            const uint32_t par = (*(volatile uint32_t*)(smem + M_EPOCH) + 1u) & 1u;
            const uint32_t a0 = sb + 16384 + (lane >> 3) * 1028 + ((lane >> 2) & 1) * 144 + (lane & 3) * 32;
            const uint32_t retry = sb + B_RETRY + (warp & 1) * 240;
            uint32_t slot = warp, ph = 0, rph = 0;
            uint32_t j = ffn ? warp & 1 : 12;
#pragma unroll 1
            for (int step = warp; step < 32 || j < 12;) {
                const bool go = step < (j < 8 ? 32 - NA : 32);
                if (go) {
                    const uint32_t bar = sb + 8 * slot;
                    mbar_wait(bar + B_BL, ph);
#pragma unroll 1
                    while (__any_sync(0xffffffffu, stale_tags(a0 + slot * REGION, par) & 1u)) {
                        const int row = blk * 4096 + __shfl_sync(0xffffffffu, tab, step) * 128;
                        mbar_expect_tx_elect(retry, 16384);
                        tma2d_elect(sb + slot * REGION + 16384, &p.mAB, 0, row, retry);
                        tma2d_elect(sb + slot * REGION + 24576, &p.mAB, 0, row + 64, retry);
                        mbar_spin(retry, rph);
                        rph ^= 1u;
                    }
                    mbar_arrive_elect<4>(bar + B_FULL);
                }
                if (j < 12 && step >= FFN_S0 + j * FFN_W / 4 && __any_sync(0xffffffffu, mbar_test(sb + B_FREE + 2 * (j & 12), 0))) {
                    const uint32_t fb = sb + B_FFN + 4 * (j & 6);
                    if (!(j & 1)) mbar_expect_tx_elect(fb, 8192);
                    tma2d_elect(sb + 6 * REGION + ((j + 4) & 7) * 4096, j < 8 ? &p.mWg + (j & 1) : &p.mWd,
                                j < 8 ? (cta >> 1) * 32 : rank * 256, j < 8 ? rank * 256 + (j >> 1) * 64 : (cta >> 1) * 32 + j * 8 - 64, fb);
                    j += 2;
                }
                if (k < 12) PREFETCH_W();
                if (go) {
                    step += 2;
                    slot += 2;
                    if (slot >= NSTAGE) { slot -= NSTAGE; ph ^= 1; }
                }
            }
        }
    } else if (warp < 8) {
        const int t = tid - 128, w = warp - 4;
        if (t == 0) {
            *(volatile uint32_t*)(smem + M_EPOCH) = epoch;
            *(volatile unsigned int*)&p.s->epoch[cta] = epoch + 1;
        }
        mbar_arrive_if(sb + B_EPOCH, t == 0);
        const uint4 gw0 = ldg_nc<0>(p.gate_w + lane * 8), gw1 = ldg_nc<512>(p.gate_w + lane * 8);
        const uint4 rw0 = ldg_nc<0>(p.w_r + lane * 8), rw1 = ldg_nc<512>(p.w_r + lane * 8);
        mbar_wait(sb + B_EPOCH, 0);
        const uint32_t par = (*(volatile uint32_t*)(smem + M_EPOCH) + 1u) & 1u;
        mbar_wait(sb + B_F + 8 * ROUTER_C, 0);
        const int row0 = cta * 16 + w * 4;
        uint4 xr[8];
        {
            const char* xp = (const char*)p.x + (uint32_t)row0 * (D_ * 2) + lane * 16;
            xr[0] = ldg_nc<0>(xp);    xr[1] = ldg_nc<512>(xp);  xr[2] = ldg_nc<1024>(xp); xr[3] = ldg_nc<1536>(xp);
            xr[4] = ldg_nc<2048>(xp); xr[5] = ldg_nc<2560>(xp); xr[6] = ldg_nc<3072>(xp); xr[7] = ldg_nc<3584>(xp);
            float a[8];
#pragma unroll
            for (int i = 0; i < 4; i++) {
                const uint32_t xv[8] = {xr[2 * i].x, xr[2 * i].y, xr[2 * i].z, xr[2 * i].w,
                                        xr[2 * i + 1].x, xr[2 * i + 1].y, xr[2 * i + 1].z, xr[2 * i + 1].w};
                const uint32_t gv[8] = {gw0.x, gw0.y, gw0.z, gw0.w, gw1.x, gw1.y, gw1.z, gw1.w};
                const uint32_t rv[8] = {rw0.x, rw0.y, rw0.z, rw0.w, rw1.x, rw1.y, rw1.z, rw1.w};
                float u = 0.f, v = 0.f;
#pragma unroll
                for (int j = 0; j < 8; j++) {
                    const uint32_t pr = hmul2_bf16(xv[j], gv[j]);
                    u += bflo(pr); u += bfhi(pr);
                    v = fmaf(bflo(xv[j]), bflo(rv[j]), v); v = fmaf(bfhi(xv[j]), bfhi(rv[j]), v);
                }
                a[i] = u; a[4 + i] = v;
            }
            mbar_wait(sb + B_EARLY, 0);
            halve<4, 16>(a); halve<2, 8>(a); halve<1, 4>(a);
            a[0] += __shfl_xor_sync(0xffffffffu, a[0], 1);
            a[0] += __shfl_xor_sync(0xffffffffu, a[0], 2);
            const int row = row0 + ((lane >> 2) & 3);
            const float gate = rbf(sigmoidf_(rbf(a[0])));
            if (lane < 16 && (lane & 3) == 0)
                asm volatile("st.relaxed.gpu.global.u32 [%0], %1;" ::"l"(&p.s->gate[row]), "r"(tagf(gate, par)) : "memory");
            const uint32_t best = __reduce_max_sync(0xffffffffu, lane >= 16 ? router_key(a[0], row) : 0u);
            if (lane == 0) *(volatile uint32_t*)(smem + M_KEY + w * 4) = best;
            side_bar();
            if (t < 8) {
                const uint4 k = *(const uint4*)(smem + M_KEY);
                asm volatile("{.reg .b32 old; atom.relaxed.gpu.global.exch.b32 old, [%0], %1;}" ::"l"(&p.s->keys[t * NCTA + cta]),
                             "r"(max(max(k.x, k.y), max(k.z, k.w)) | (par << 15)) : "memory");
            }
            const uint32_t og = pack_bf16(1.f - gate, 1.f - gate);
#pragma unroll
            for (int i = 0; i < 8; i++) {
                const uint32_t o = __shfl_sync(0xffffffffu, og, 4 * (i >> 1));
                xr[i] = make_uint4(hmul2_bf16(o, xr[i].x), hmul2_bf16(o, xr[i].y), hmul2_bf16(o, xr[i].z), hmul2_bf16(o, xr[i].w));
            }
        }
        mbar_wait(sb + B_FREE, 0);
        __nanosleep(KEY_NS);
        if (w == 0) {
            const uint4 k4 = wait_tags(p.s->keys + gpc * NCTA + lane * 4, 15, par);
            const uint32_t k = __reduce_max_sync(0xffffffffu, max(max(k4.x, k4.y), max(k4.z, k4.w)));
            sts128<M_XS>(sb + lane * 16, ldg_nc<0>(p.x + (0x7fff - (k & 0x7fffu)) * D_ + rank * 256 + lane * 8));
        } else if (w == 1) {
            const uint4 g4 = wait_tags(p.s->gate + own * 128 + lane * 4, 0, par);
            const uint32_t sg = comp ? 0x80000000u : 0u;
            sts128<M_G>(sb + lane * 16, make_uint4((g4.x & ~1u) ^ sg, (g4.y & ~1u) ^ sg, (g4.z & ~1u) ^ sg, (g4.w & ~1u) ^ sg));
            mbar_arrive_warp(sb + B_GATE);
        }
        side_bar();
        char* op = (char*)p.out + (uint32_t)row0 * (D_ * 2) + lane * 16;
        float a[16];
#pragma unroll
        for (int i = 0; i < 16; i++) a[i] = 0.f;
#pragma unroll 1
        for (int i = 0; i < 4; i++) {
            if (i == 2) {
                mbar_wait(sb + B_FREE + 8, 0);
                const uint32_t t2 = clk() + w * (INIT_GAP / 4);
#pragma unroll
                for (int j = 0; j < 8; j++) {
                    sleep_until<20>(t2 + j * INIT_GAP);
                    *(uint4*)(op + j * 512) = xr[j];
                }
                mbar_arrive_warp(sb + B_PUB);
            }
            if (ffn) {
                const float xs0 = __bfloat162float(((const bf16*)(smem + M_XS))[64 * i + (t >> 2)]);
                const float xs1 = __bfloat162float(((const bf16*)(smem + M_XS))[64 * i + 32 + (t >> 2)]);
                const uint32_t wa = sb + 6 * REGION + (i ^ 2) * 8192 + t * 16;
                mbar_wait(sb + B_FFN + 8 * i, 0);
                const uint4 v0 = lds128(wa), v1 = lds128(wa + 4096), v2 = lds128(wa + 2048), v3 = lds128(wa + 6144);
                const uint32_t w0[8] = {v0.x, v0.y, v0.z, v0.w, v1.x, v1.y, v1.z, v1.w};
                const uint32_t w1[8] = {v2.x, v2.y, v2.z, v2.w, v3.x, v3.y, v3.z, v3.w};
#pragma unroll
                for (int k = 0; k < 8; k++) {
                    a[2 * k] = fmaf(xs1, bflo(w1[k]), fmaf(xs0, bflo(w0[k]), a[2 * k]));
                    a[2 * k + 1] = fmaf(xs1, bfhi(w1[k]), fmaf(xs0, bfhi(w0[k]), a[2 * k + 1]));
                }
                if (i == 1) {
                    side_bar();
                    mbar_arrive_if(sb + B_FREE + 16, t == 0);
                }
            }
        }
        if (!ffn) {
            mbar_arrive_warp(sb + B_LOW);
            return;
        }
        halve<8, 16>(a); halve<4, 8>(a); halve<2, 4>(a);
        const uint32_t ho = (lane >> 4) * 128 + (lane & 3) * 32 + ((lane >> 2) & 3) * 8;
        cluster_wait();
#pragma unroll
        for (int k = 0; k < 2; k++)
            asm volatile("st.async.weak.shared::cluster.mbarrier::complete_tx::bytes.v2.f32 [%0], {%1,%2}, [%3];"
                         ::"r"(mapa(sb + (k ? 6 * REGION + w * 512 : M_HX + w * 256) + ho, rank ^ k ^ 1)), "f"(a[0]), "f"(a[1]),
                           "r"(mapa(sb + B_HX, rank ^ k ^ 1)) : "memory");
        mbar_wait_cluster(sb + B_HX, 0);
        const float *hx = (const float*)(smem + M_HX) + lane, *hy = (const float*)(smem + 6 * REGION) + lane;
        const float gs = rbf(((hx[0] + hy[0]) + (hx[64] + hy[128])) + ((hx[128] + hy[256]) + (hx[192] + hy[384])));
        const float us = rbf(((hx[32] + hy[32]) + (hx[96] + hy[160])) + ((hx[160] + hy[288]) + (hx[224] + hy[416])));
        float* hrow = (float*)(smem + M_XS) + w * 32;
        hrow[lane] = rbf(rbf(gs * sigmoidf_(gs)) * us);
        fence_proxy_async_smem();
        mbar_arrive_warp(sb + B_LOW);
        float o0 = 0.f, o1 = 0.f;
#pragma unroll 1
        for (int i = 0; i < 2; i++) {
            float4 hv[4];
            uint32_t vd[16];
#pragma unroll
            for (int k = 0; k < 4; k++) hv[k] = *(const float4*)&hrow[i * 16 + k * 4];
            mbar_wait(sb + B_FFN + 8 * i, 1);
#pragma unroll
            for (int k = 0; k < 16; k++) vd[k] = *(const volatile uint32_t*)(smem + 6 * REGION + 16384 + i * 8192 + k * 512 + t * 4);
#pragma unroll
            for (int k = 0; k < 4; k++) {
                o0 = fmaf(hv[k].x, bflo(vd[4 * k]), o0);     o1 = fmaf(hv[k].x, bfhi(vd[4 * k]), o1);
                o0 = fmaf(hv[k].y, bflo(vd[4 * k + 1]), o0); o1 = fmaf(hv[k].y, bfhi(vd[4 * k + 1]), o1);
                o0 = fmaf(hv[k].z, bflo(vd[4 * k + 2]), o0); o1 = fmaf(hv[k].z, bfhi(vd[4 * k + 2]), o1);
                o0 = fmaf(hv[k].w, bflo(vd[4 * k + 3]), o0); o1 = fmaf(hv[k].w, bfhi(vd[4 * k + 3]), o1);
            }
        }
        asm volatile("st.relaxed.gpu.global.v2.u32 [%0], {%1,%2};" ::"l"(&p.s->part[(cta >> 1) * D_ + rank * 256 + t * 2]),
                     "r"(tagf(o0, par)), "r"(tagf(o1, par)) : "memory");
        red_inc_if(p.s->phint + ((rank * 2 + (w >> 1)) * 16 + (cta >> 3)) * 8 + lane, lane == 0);
    } else {
        const int wg = (warp >> 2) - 2, wq = warp & 3;
        const uint32_t sbd = ((sb & 0x3FFFF) >> 4) + 0x10000;
        const bool lead = (tid & 127) == 0;
        const bool lead0 = lead && !wg, lead1 = lead && wg;
        const int q = lane & 3;
        float acc[64];
        const uint32_t rE = mapa(sb + B_EMPTY, rank ^ 1);
#define RELEASE(n, slot, pred) release_pair<n>(sb + B_EMPTY + 8 * (slot), rE + 8 * (slot), pred)
        const uint32_t ioff = wq * 4096 + (lane >> 2) * 64 + ((q ^ (lane >> 3)) << 4);
        const uint32_t sdst = pin(sb + 6 * REGION + (wg ? 0 : 16384) + ioff);
        unsigned char* gdst = pin(p.s->ab + (blk * 32 + own) * 16384 + ioff);
        unsigned int* hint = pin(p.s->hint + (blk * 4 + ((own >> 1) & 3)) * 32 + rank + lane);
        uint32_t par = 0;
#define GET_PAR() mbar_spin(sb + B_EPOCH, 0); par = (*(volatile uint32_t*)(smem + M_EPOCH) + 1u) & 1u
        cluster_wait();
        if (wg) mbar_spin(sb + B_G0, 0);
#pragma unroll
        for (int c = 0; c < 8; c++) {
            if (c == 1 && wg) {
                wg_wait<0>();
                RELEASE(1, 1, lead);
                GET_PAR();
                mbar_spin(sb + B_G1, 0);
            }
            if (!wg || c < 3 || c == 4) mbar_spin(sb + (!wg || c == 0 ? B_F + 8 * c : c == 1 ? B_GO1 : c == 2 ? B_G2 : B_G4), 0);
            const uint32_t xa = sbd + wg * ((off_xl(c) - off_xe(c)) / 16);
            wg_fence();
#pragma unroll
            for (int kk = 0; kk < 4; kk++) {
                wgmma128<0>(acc, desc128(xa + off_xe(c) / 16 + 2 * kk), desc128(sbd + off_d(c) / 16 + 2 * kk), (c | kk) != 0);
                if (c == 7 && kk == 0) wg_commit();
            }
            wg_commit();
            if (c == 3 && !wg) { GET_PAR(); }
            if (c == 7) {
                if (wg) mbar_spin(sb + B_FULL, 0);
                wg_wait<2>();
                mbar_arrive_if(sb + B_GO1, lead0);
            }
            if (c == 4 || c >= 6) wg_wait<1>();
            if (c == 4) { mbar_arrive_if(sb + B_XE, lead0); RELEASE(1, 1, lead0); RELEASE(2, 2, lead1); RELEASE(2, 3, lead1); }
            if (c == 6) RELEASE(2, 4 * wg, lead);
            if (c == 7) mbar_arrive_if(sb + B_GO0, lead1);
        }
        const int rh = wg ^ comp;
        const uint32_t da0 = sbd + rh * 512, db0 = sbd - 0x10000 + 0x400000 + 1024;
        const uint32_t dbe = db0 + 6 * (REGION / 16), dbl = dbe - 1024;
#define STEP(da, db, first) wg_fence();                                                                     \
        _Pragma("unroll") for (int kk = 0; kk < 4; kk++)                                                    \
            wgmma128<1>(acc, desc128((da) + kk * 2), desc64((db) + kk * 256), !((first) && kk == 0));       \
        wg_commit()
#define ACC(i, j) (16 * ((i) >> 1) + 2 * ((i) & 1) + 4 * (j))
#define PW(i, j) pack_bf16(acc[ACC(i, j)], acc[ACC(i, j) + 1])
#define PT(i, j) ((j) == ((i) >> 1) ? (PW(i, j) & ~1u) | par : PW(i, j))
#define PIECE(i) make_uint4(PT(i, 0), PT(i, 1), PT(i, 2), PT(i, 3))
#define PIECES(F) F(0); F(1); sched_cut(); F(2); F(3); F(4); F(5); F(6); F(7)
        if (wg) {
            wg_wait<0>();
            fence_regs(acc);
#define STS1(i) sts128<(i) * 512>(sdst, PIECE(i))
            PIECES(STS1);
            STEP(da0, dbe, true);
            fence_proxy_async_smem();
            mbar_arrive_warp(sb + B_FULL + 8);
            RELEASE(1, 5, lead);
        } else {
            wg_wait<0>();
            fence_regs(acc);
            uint4 v[8];
#define STG0(i) v[i] = PIECE(i); stg128<(i) * 512>(gdst, v[i]); if (HINT_AT == (i) + 1) red_inc_if(hint, own < 6 && lane == 0)
            PIECES(STG0);
#define STS0(i) mbar_spin(sb + B_EPOCH, 0); sts128<(i) * 512>(sdst, v[i])
            STS0(0); STS0(1); STS0(2); STS0(3); STS0(4); STS0(5); STS0(6); STS0(7);
            fence_proxy_async_smem();
            mbar_arrive_warp(sb + B_FULL);
            RELEASE(1, 5, lead);
            mbar_arrive_if(sb + B_EARLY, lead);
            mbar_spin(sb + B_FULL, 0);
            mbar_spin(sb + B_GO0, 0);
            STEP(da0, dbe, true);
        }
#pragma unroll
        for (int step = 1; step < 3; step++) {
            mbar_spin(sb + B_FULL + 8 * step, 0);
            STEP(da0 + step * (REGION / 16), step == 1 ? dbl : db0 + step * (REGION / 16), false);
            wg_wait<1>();
            RELEASE(1, step - 1, lead);
            mbar_arrive_if(sb + B_FREE + 8 * (step - 1), lead);
        }
        int slot = 3, ph = 0, pslot = 2;
        float g0 = 0.f, g1 = 0.f;
        uint32_t oa = 0;
#pragma unroll 1
        for (int step = 3; step < 26; step++) {
            mbar_wait(sb + B_FULL + 8 * slot, ph);
            STEP(da0 + slot * (REGION / 16), db0 + slot * (REGION / 16), false);
            if (step == 22 + wg) {
                const int r0 = rh * 64 + wq * 16 + (lane >> 2), sr = ((lane >> 2) & 1) * 4 + (lane >> 3);
                mbar_wait(sb + B_GATE, 0);
                g0 = ((const volatile float*)(smem + M_G))[r0];
                g1 = ((const volatile float*)(smem + M_G))[r0 + 8];
                oa = pin(wg ? ((own * 128 + (r0 & ~1)) * D_ + tn * 128 + (lane & 7) * 8) * 2u
                            : sb + rh * 8192 + wq * 2048 + sr * 128 + ((q ^ sr) << 4));
            }
            wg_wait<1>();
            RELEASE(1, pslot, lead);
            pslot = slot;
            if (++slot == NSTAGE) { slot = 0; ph ^= 1; }
        }
        mbar_wait(sb + B_FULL + 8 * 2, 0);
        wg_fence();
#pragma unroll
        for (int kk = 0; kk < 4; kk++) {
            if (kk == HSK) {
                wg_commit();
                if (wg) {
                    wg_wait<1>();
                    RELEASE(1, 1, lead);
                    mbar_wait(sb + B_INIT, 0);
                    mbar_wait(sb + B_TAIL, 0);
                }
                wg_fence();
            }
            wgmma128<1>(acc, desc128(da0 + 2 * (REGION / 16) + kk * 2), desc64(db0 + 2 * (REGION / 16) + kk * 256), 1);
        }
        wg_commit();
        if (!wg) {
            wg_wait<2>();
            RELEASE(1, 1, lead);
        }
        slot = 3;
#pragma unroll 1
        for (int step = 27; step < 32; step++) {
            if (!wg) mbar_wait(sb + B_FULL + 8 * slot, ph);
            STEP(da0 + (step < 32 - NA ? slot : step == 32 - NA ? 6 : pslot) * (REGION / 16), db0 + slot * (REGION / 16), false);
            pslot = slot;
            if (++slot == NSTAGE) { slot = 0; ph ^= 1; }
        }
#define OW(i, j) pack_bf16((((i) & 1) ? g1 : g0) * acc[ACC(i, j)], (((i) & 1) ? g1 : g0) * acc[ACC(i, j) + 1])
        if (!wg) {
            wg_wait<1>();
            mbar_arrive_if(sb + B_TAIL, lead);
            const uint32_t st0 = sb + rh * 8192 + wq * 2048;
            mbar_wait(sb + B_INIT, 0);
            wg_wait<0>();
            fence_regs(acc);
#define OSTS(i) sts128<((i) >> 2) * REGION + ((i) & 1) * 1024>(((i) & 2) ? oa ^ 64 : oa, make_uint4(OW(i, 0), OW(i, 1), OW(i, 2), OW(i, 3)))
#define ORED(h) fence_proxy_async_smem(); __syncwarp();                                                     \
            asm volatile(ELECT "cp.reduce.async.bulk.tensor.4d.global.shared::cta.add.tile.bulk_group [%0, {%2,%3,%3,%4}], [%1];}" \
                         ::"l"(&p.mOut), "r"(st0 + (h) * REGION), "r"(tn * 128 + (h) * 64), "r"(0), "r"(own * 16 + rh * 8 + wq * 2) : "memory")
            OSTS(0); OSTS(1); OSTS(2); OSTS(3);
            ORED(0);
            sched_cut();
            OSTS(4); OSTS(5); OSTS(6); OSTS(7);
            ORED(1);
            bulk_wait_read();
        } else {
            const bool odd = lane & 4;
            char *op = pin((char*)p.out + oa), *opb = pin((char*)p.out + (oa ^ 64) + 1024);
            sched_cut();
            wg_wait<0>();
            fence_regs(acc);
#define REDLINE(i) {                                                                                        \
                uint32_t k[4], r[4];                                                                        \
                _Pragma("unroll") for (int j = 0; j < 4; j++) {                                             \
                    r[j] = __shfl_xor_sync(0xffffffffu, OW((i) + 2, j), 4);                                 \
                    k[j] = OW(i, j);                                                                        \
                }                                                                                           \
                red_bf16x8<((i) & 1) * 8192 + ((i) >> 2) * 128>(op, odd ? r[0] : k[0], odd ? r[1] : k[1], odd ? r[2] : k[2], odd ? r[3] : k[3]);  \
                red_bf16x8<((i) & 1) * 8192 + ((i) >> 2) * 128>(opb, odd ? k[0] : r[0], odd ? k[1] : r[1], odd ? k[2] : r[2], odd ? k[3] : r[3]); }
            REDLINE(0)
            sched_cut();
            REDLINE(1) REDLINE(4) REDLINE(5)
        }
    }
}

typedef CUresult (*EncodeTiledFn)(CUtensorMap*, CUtensorMapDataType, cuuint32_t, void*, const cuuint64_t*, const cuuint64_t*,
                                  const cuuint32_t*, const cuuint32_t*, CUtensorMapInterleave, CUtensorMapSwizzle,
                                  CUtensorMapL2promotion, CUtensorMapFloatOOBfill);

static void make_map(EncodeTiledFn enc, CUtensorMap* m, const void* base, uint64_t cols, uint64_t rows, uint32_t box_rows,
                     CUtensorMapSwizzle sw = CU_TENSOR_MAP_SWIZZLE_128B, uint32_t box_cols = 64) {
    cuuint64_t dims[2] = {cols, rows};
    cuuint64_t str[1] = {cols * 2};
    cuuint32_t box[2] = {box_cols, box_rows};
    cuuint32_t es[2] = {1, 1};
    enc(m, CU_TENSOR_MAP_DATA_TYPE_BFLOAT16, 2, (void*)base, dims, str, box, es, CU_TENSOR_MAP_INTERLEAVE_NONE,
        sw, CU_TENSOR_MAP_L2_PROMOTION_L2_128B, CU_TENSOR_MAP_FLOAT_OOB_FILL_NONE);
}

static void make_map_chunks(EncodeTiledFn enc, CUtensorMap* m, const void* base, uint64_t rows, uint32_t box_rows, uint32_t n = 1) {
    cuuint64_t dims[3] = {64, rows, 8};
    cuuint64_t str[2] = {D_ * 2, 128};
    cuuint32_t box[3] = {64, box_rows, n};
    cuuint32_t es[3] = {1, 1, 1};
    enc(m, CU_TENSOR_MAP_DATA_TYPE_BFLOAT16, 3, (void*)base, dims, str, box, es, CU_TENSOR_MAP_INTERLEAVE_NONE,
        CU_TENSOR_MAP_SWIZZLE_128B, CU_TENSOR_MAP_L2_PROMOTION_L2_128B, CU_TENSOR_MAP_FLOAT_OOB_FILL_NONE);
}

static void make_map_out(EncodeTiledFn enc, CUtensorMap* m, const void* base) {
    cuuint64_t dims[4] = {D_, 4, 2, S_ / 8};
    cuuint64_t str[3] = {2 * D_ * 2, D_ * 2, 8 * D_ * 2};
    cuuint32_t box[4] = {64, 4, 2, 2};
    cuuint32_t es[4] = {1, 1, 1, 1};
    enc(m, CU_TENSOR_MAP_DATA_TYPE_BFLOAT16, 4, (void*)base, dims, str, box, es, CU_TENSOR_MAP_INTERLEAVE_NONE,
        CU_TENSOR_MAP_SWIZZLE_128B, CU_TENSOR_MAP_L2_PROMOTION_NONE, CU_TENSOR_MAP_FLOAT_OOB_FILL_NONE);
}

extern "C" void kernel_launch(void* const* d_in, const int* in_sizes, int n_in, void* d_out, int out_size) {
    (void)in_sizes; (void)n_in; (void)out_size;
    static EncodeTiledFn enc = nullptr;
    static bool fused_ok = false;
    static void* scratch = nullptr;
    if (!enc) {
        void* fn = nullptr;
        cudaDriverEntryPointQueryResult q;
        cudaGetDriverEntryPoint("cuTensorMapEncodeTiled", &fn, cudaEnableDefault, &q);
        enc = (EncodeTiledFn)fn;
        cudaGetSymbolAddress(&scratch, g_s);
        cudaFuncSetAttribute(fused_kernel, cudaFuncAttributeMaxDynamicSharedMemorySize, SMEM_BYTES);
        int dev = 0, nsm = 0, ncl = 0;
        cudaGetDevice(&dev);
        cudaDeviceGetAttribute(&nsm, cudaDevAttrMultiProcessorCount, dev);
        cudaLaunchConfig_t cfg = {};
        cfg.gridDim = dim3(132); cfg.blockDim = dim3(NTHREADS); cfg.dynamicSmemBytes = SMEM_BYTES;
        cudaLaunchAttribute at;
        at.id = cudaLaunchAttributeClusterDimension;
        at.val.clusterDim.x = 2; at.val.clusterDim.y = 1; at.val.clusterDim.z = 1;
        cfg.attrs = &at; cfg.numAttrs = 1;
        fused_ok = cudaOccupancyMaxActiveClusters(&ncl, fused_kernel, &cfg) == cudaSuccess && nsm == 132 && ncl == 66;
        (void)cudaGetLastError();
    }
    if (!fused_ok) {
        const bf16* const* in = (const bf16* const*)d_in;
        fb_hidden<<<S_, D_, 0, cudaStreamPerThread>>>(in[0], in[3], in[4], in[10], in[6]);
        fb_ffn1<<<F_ / 128, 128, 0, cudaStreamPerThread>>>(in[0], in[7], in[8]);
        fb_ffn2<<<D_ / 64, 64, 0, cudaStreamPerThread>>>(in[9]);
        fb_seq<<<S_, D_, 0, cudaStreamPerThread>>>(in[0], in[1], in[2], (bf16*)d_out);
        return;
    }
    Params p;
    p.s = (Scratch*)scratch;
    p.x = (const bf16*)d_in[0];
    p.w_r = (const bf16*)d_in[6];
    p.wg = (const bf16*)d_in[7];
    p.wu = (const bf16*)d_in[8];
    p.wd = (const bf16*)d_in[9];
    p.gate_w = (const bf16*)d_in[10];
    p.out = (bf16*)d_out;
    make_map_chunks(enc, &p.mX1, d_in[0], S_, 64);
    make_map_chunks(enc, &p.mX2, d_in[0], S_, 64, 2);
    make_map(enc, &p.mCre, d_in[1], S_, S_, 128);
    make_map(enc, &p.mCim, d_in[2], S_, S_, 128);
    make_map_chunks(enc, &p.mDre, d_in[3], D_, 128);
    make_map_chunks(enc, &p.mDim, d_in[4], D_, 128);
    make_map(enc, &p.mAB, scratch, 64, 8 * 32 * 128, 64, CU_TENSOR_MAP_SWIZZLE_NONE);
    make_map_out(enc, &p.mOut, d_out);
    make_map(enc, &p.mWg, d_in[7], F_, D_, 64, CU_TENSOR_MAP_SWIZZLE_NONE, 32);
    make_map(enc, &p.mWu, d_in[8], F_, D_, 64, CU_TENSOR_MAP_SWIZZLE_NONE, 32);
    make_map(enc, &p.mWd, d_in[9], D_, F_, 8, CU_TENSOR_MAP_SWIZZLE_NONE, 256);
    fused_kernel<<<132, NTHREADS, SMEM_BYTES, cudaStreamPerThread>>>(p);
}
```

```cpp
#include <cuda_runtime.h>
#include <cuda.h>
#include <cuda_bf16.h>
#include <stdint.h>

typedef __nv_bfloat16 bf16;

constexpr int S_ = 2048, D_ = 512, F_ = 1792;
constexpr int NCTA = 128;
constexpr int NTHREADS = 512;
constexpr int NSTAGE = 6;
constexpr int REGION = 32768;
constexpr int FFN_CTAS = F_ / 16;
constexpr uint32_t SPIN_LIMIT = 1u << 22;
constexpr int PACE = 260;
constexpr int PACE0 = 100;
constexpr int A_GAP = 260;
constexpr int B_GAP = 280;
constexpr int LATE_GAP = 240;
constexpr int INIT_GAP = 360;
constexpr int INIT_NS = 300;
constexpr int PF_T0 = 3000;
constexpr int PF_GAP = 850;
constexpr int PF_N0 = 4;
constexpr int FFN_S0 = 4;
constexpr int FFN_W = 7;
constexpr int ROUTER_C = 4;
constexpr int HINT_AT = 5;
constexpr int SUM_T0 = 15000;
constexpr int PS1 = 24;
constexpr int NA = 3;
constexpr int KEY_NS = 300;
constexpr int HSK = 2;

constexpr int OFF_MISC = 7 * REGION;
constexpr int B_F = OFF_MISC;
constexpr int B_G1 = B_F + 64;
constexpr int B_G4 = B_G1 + 8;
constexpr int B_XE = B_G4 + 8;
constexpr int B_GO1 = B_XE + 8;
constexpr int B_GO0 = B_GO1 + 8;
constexpr int B_EPOCH = B_GO0 + 8;
constexpr int B_RETRY = B_EPOCH + 8;
constexpr int B_INIT = B_RETRY + 8;
constexpr int B_FULL = B_INIT + 8;
constexpr int B_EMPTY = B_FULL + 48;
constexpr int B_PUB = B_EMPTY + 48;
constexpr int B_FREE = B_PUB + 8;
constexpr int B_BL = B_FREE + 24;
constexpr int B_TAIL = B_BL + 48;
constexpr int B_HX = B_TAIL + 8;
constexpr int B_FFN = B_HX + 8;
constexpr int B_ROLE = B_FFN + 40;
constexpr int B_EARLY = B_ROLE + 8;
constexpr int B_GATE = B_EARLY + 8;
constexpr int B_G2 = B_GATE + 8;
constexpr int B_LOW = B_G2 + 8;
constexpr int B_G0 = B_LOW + 8;
constexpr int M_EPOCH = B_G0 + 8;
constexpr int M_ROLE = M_EPOCH + 4;
constexpr int M_KEY = OFF_MISC + 416;
constexpr int M_HX = OFF_MISC + 512;
constexpr int M_G = M_HX + 1024;
constexpr int M_XS = M_G + 512;
constexpr int SMEM_BYTES = 232448;
static_assert(M_ROLE + 4 <= M_KEY && M_XS + 512 <= SMEM_BYTES, "smem");

struct Scratch {
    unsigned char ab[8 * 32 * 16384];
    unsigned int hint[8 * 4 * 32];
    unsigned int ready[16 * 32];
    unsigned int gate[S_];
    unsigned int part[FFN_CTAS / 2 * D_];
    unsigned int phint[4 * 16 * 8];
    unsigned int keys[8 * NCTA];
    unsigned int epoch[NCTA + 4];
};
__device__ __align__(1024) Scratch g_s;

struct Params {
    Scratch* s;
    bf16* out;
    const bf16 *x, *gate_w, *w_r, *wg, *wu, *wd;
    CUtensorMap mDre, mDim, mX1, mX2, mCre, mCim, mAB, mOut, mWg, mWu, mWd;
};

#define ELECT "{.reg .pred p; elect.sync _|p, 0xffffffff; @p "
__device__ __forceinline__ uint32_t smem_u32(const void* p) { return (uint32_t)__cvta_generic_to_shared(p); }
__device__ __forceinline__ uint32_t clk() { return (uint32_t)clock64(); }
__device__ __forceinline__ void spin_until(uint32_t t) { while ((int)(clk() - t) < 0) {} }
template <int NS>
__device__ __forceinline__ void sleep_until(uint32_t t) { while ((int)(clk() - t) < 0) __nanosleep(NS); }
__device__ __forceinline__ void mbar_init_elect(uint32_t bar, uint32_t cnt) {
    asm volatile(ELECT "mbarrier.init.shared::cta.b64 [%0], %1;}" ::"r"(bar), "r"(cnt) : "memory");
}
__device__ __forceinline__ void mbar_expect_tx_elect(uint32_t bar, uint32_t bytes) {
    asm volatile(ELECT "mbarrier.arrive.expect_tx.shared::cta.b64 _, [%0], %1;}" ::"r"(bar), "r"(bytes) : "memory");
}
template <int N = 1>
__device__ __forceinline__ void mbar_arrive_elect(uint32_t bar) {
    asm volatile(ELECT "mbarrier.arrive.shared::cta.b64 _, [%0], %1;}" ::"r"(bar), "n"(N) : "memory");
}
__device__ __forceinline__ void mbar_arrive_if(uint32_t bar, bool pred) {
    asm volatile("{.reg .pred p; setp.ne.b32 p, %1, 0; @p mbarrier.arrive.shared::cta.b64 _, [%0];}" ::"r"(bar), "r"((int)pred) : "memory");
}
__device__ __forceinline__ void mbar_arrive_warp(uint32_t bar) {
    __syncwarp();
    mbar_arrive_if(bar, (threadIdx.x & 31) == 0);
}
template <int N>
__device__ __forceinline__ void release_pair(uint32_t bar, uint32_t rbar, bool pred) {
    asm volatile("{.reg .pred p; setp.ne.b32 p, %2, 0; @p mbarrier.arrive.shared::cta.b64 _, [%0], %3;"
                 " @p mbarrier.arrive.shared::cluster.b64 _, [%1], %3;}" ::"r"(bar), "r"(rbar), "r"((int)pred), "n"(N) : "memory");
}
__device__ __forceinline__ uint32_t mapa(uint32_t a, uint32_t cta) {
    uint32_t r;
    asm volatile("mapa.shared::cluster.u32 %0, %1, %2;" : "=r"(r) : "r"(a), "r"(cta));
    return r;
}
__device__ __forceinline__ bool mbar_test(uint32_t bar, uint32_t parity) {
    uint32_t ok;
    asm volatile("{.reg .pred p; mbarrier.test_wait.parity.shared::cta.b64 p, [%1], %2; selp.u32 %0,1,0,p;}"
                 : "=r"(ok) : "r"(bar), "r"(parity) : "memory");
    return ok;
}
__device__ __forceinline__ void mbar_wait(uint32_t bar, uint32_t parity) {
    asm volatile("{.reg .pred p, q; .reg .u32 n; mov.u32 n, 0;\n"
                 "W%=: mbarrier.try_wait.parity.shared::cta.b64 p, [%0], %1;\n"
                 "add.u32 n, n, 1; setp.lt.and.u32 q, n, %2, !p; @q bra W%=; @!p trap;}" ::"r"(bar), "r"(parity), "n"(SPIN_LIMIT) : "memory");
}
__device__ __forceinline__ void mbar_wait_cluster(uint32_t bar, uint32_t parity) {
    asm volatile("{.reg .pred p, q; .reg .u32 n; mov.u32 n, 0;\n"
                 "W%=: mbarrier.try_wait.parity.acquire.cluster.shared::cta.b64 p, [%0], %1;\n"
                 "add.u32 n, n, 1; setp.lt.and.u32 q, n, %2, !p; @q bra W%=; @!p trap;}" ::"r"(bar), "r"(parity), "n"(SPIN_LIMIT) : "memory");
}
__device__ __forceinline__ void mbar_spin(uint32_t bar, uint32_t parity) {
    asm volatile("{.reg .pred p;\nW%=: mbarrier.try_wait.parity.shared::cta.b64 p, [%0], %1; @!p bra W%=;}" ::"r"(bar), "r"(parity) : "memory");
}
__device__ __forceinline__ void cluster_arrive() { asm volatile("barrier.cluster.arrive.relaxed.aligned;" ::: "memory"); }
__device__ __forceinline__ void cluster_wait() { asm volatile("barrier.cluster.wait.acquire.aligned;" ::: "memory"); }
__device__ __forceinline__ void side_bar() { asm volatile("bar.sync 1, 128;" ::: "memory"); }
__device__ __forceinline__ void tma2d_elect(uint32_t dst, const CUtensorMap* m, int c0, int c1, uint32_t bar) {
    asm volatile(ELECT "cp.async.bulk.tensor.2d.shared::cluster.global.mbarrier::complete_tx::bytes [%0], [%1, {%3,%4}], [%2];}"
                 ::"r"(dst), "l"(m), "r"(bar), "r"(c0), "r"(c1) : "memory");
}
__device__ __forceinline__ void tma2d_pair_elect(uint32_t dst, const CUtensorMap* m, int c0, int c1, uint32_t bar) {
    asm volatile(ELECT "cp.async.bulk.tensor.2d.shared::cluster.global.mbarrier::complete_tx::bytes.multicast::cluster"
                 " [%0], [%1, {%3,%4}], [%2], %5;}" ::"r"(dst), "l"(m), "r"(bar), "r"(c0), "r"(c1), "h"((uint16_t)3) : "memory");
}
__device__ __forceinline__ void tma3d_elect(uint32_t dst, const CUtensorMap* m, int row, int chunk, uint32_t bar) {
    asm volatile(ELECT "cp.async.bulk.tensor.3d.shared::cluster.global.mbarrier::complete_tx::bytes [%0], [%1, {%3,%4,%5}], [%2];}"
                 ::"r"(dst), "l"(m), "r"(bar), "r"(0), "r"(row), "r"(chunk) : "memory");
}
__device__ __forceinline__ void bulk_wait_read() {
    asm volatile("cp.async.bulk.commit_group; cp.async.bulk.wait_group.read 0;" ::: "memory");
    __syncwarp();
}
__device__ __forceinline__ void fence_proxy_async_smem() { asm volatile("fence.proxy.async.shared::cta;" ::: "memory"); }
__device__ __forceinline__ uint32_t ld_relaxed(const void* p) {
    uint32_t v;
    asm volatile("ld.relaxed.gpu.global.u32 %0, [%1];" : "=r"(v) : "l"(p) : "memory");
    return v;
}
__device__ __forceinline__ uint4 ld_relaxed4(const void* p) {
    uint4 v;
    asm volatile("ld.relaxed.gpu.global.v4.u32 {%0,%1,%2,%3}, [%4];" : "=r"(v.x), "=r"(v.y), "=r"(v.z), "=r"(v.w) : "l"(p) : "memory");
    return v;
}
__device__ __forceinline__ void red_inc_if(unsigned int* p, bool pred) {
    asm volatile("{.reg .pred p; setp.ne.b32 p, %1, 0; @p red.relaxed.gpu.global.add.u32 [%0], 1;}" ::"l"(p), "r"((int)pred) : "memory");
}
__device__ __forceinline__ uint32_t tagf(float v, uint32_t par) { return (__float_as_uint(v) & ~1u) | par; }
__device__ __forceinline__ uint4 wait_tags(const unsigned int* p, int bit, uint32_t par) {
    uint32_t n = 0;
    while (true) {
        const uint4 v = ld_relaxed4(p);
        const uint32_t m = par ? (v.x & v.y & v.z & v.w) : ~(v.x | v.y | v.z | v.w);
        if (__all_sync(0xffffffffu, (m >> bit) & 1u)) return v;
        __nanosleep(100);
        if (++n > SPIN_LIMIT) __trap();
    }
}
__device__ __forceinline__ void wait_counter(const unsigned int* p, uint32_t want) {
    uint32_t n = 0;
    while (!__all_sync(0xffffffffu, (int)(ld_relaxed(p) - want) >= 0)) {
        __nanosleep(200);
        if (++n > SPIN_LIMIT) __trap();
    }
    asm volatile("fence.acquire.gpu;" ::: "memory");
}
__device__ __forceinline__ uint32_t stale_tags(uint32_t a, uint32_t par) {
    uint32_t r;
    asm volatile("{.reg .b32 v<16>;\n"
                 "ld.shared.u32 v0, [%1]; ld.shared.u32 v1, [%1+256]; ld.shared.u32 v2, [%1+512]; ld.shared.u32 v3, [%1+768];\n"
                 "ld.shared.u32 v4, [%1+4096]; ld.shared.u32 v5, [%1+4352]; ld.shared.u32 v6, [%1+4608]; ld.shared.u32 v7, [%1+4864];\n"
                 "ld.shared.u32 v8, [%1+8192]; ld.shared.u32 v9, [%1+8448]; ld.shared.u32 v10, [%1+8704]; ld.shared.u32 v11, [%1+8960];\n"
                 "ld.shared.u32 v12, [%1+12288]; ld.shared.u32 v13, [%1+12544]; ld.shared.u32 v14, [%1+12800]; ld.shared.u32 v15, [%1+13056];\n"
                 "lop3.b32 v0, v0, v1, %2, 0x7e; lop3.b32 v2, v2, v3, %2, 0x7e; lop3.b32 v4, v4, v5, %2, 0x7e; lop3.b32 v6, v6, v7, %2, 0x7e;\n"
                 "lop3.b32 v8, v8, v9, %2, 0x7e; lop3.b32 v10, v10, v11, %2, 0x7e; lop3.b32 v12, v12, v13, %2, 0x7e; lop3.b32 v14, v14, v15, %2, 0x7e;\n"
                 "lop3.b32 v0, v0, v2, v4, 0xfe; lop3.b32 v6, v6, v8, v10, 0xfe; lop3.b32 v0, v0, v6, v12, 0xfe; or.b32 %0, v0, v14;}"
                 : "=r"(r) : "r"(a), "r"(par) : "memory");
    return r;
}
template <int OFF>
__device__ __forceinline__ uint4 ldg_nc(const void* p) {
    uint4 v;
    asm volatile("ld.global.nc.v4.u32 {%0,%1,%2,%3}, [%4+%5];" : "=r"(v.x), "=r"(v.y), "=r"(v.z), "=r"(v.w) : "l"(p), "n"(OFF));
    return v;
}
template <int OFF>
__device__ __forceinline__ void stg128(void* p, const uint4& v) {
    asm volatile("st.global.v4.u32 [%0+%5], {%1,%2,%3,%4};" ::"l"(p), "r"(v.x), "r"(v.y), "r"(v.z), "r"(v.w), "n"(OFF) : "memory");
}
template <int OFF>
__device__ __forceinline__ void sts128(uint32_t a, const uint4& v) {
    asm volatile("st.shared.v4.u32 [%0+%5], {%1,%2,%3,%4};" ::"r"(a), "r"(v.x), "r"(v.y), "r"(v.z), "r"(v.w), "n"(OFF) : "memory");
}
__device__ __forceinline__ uint4 lds128(uint32_t a) {
    uint4 v;
    asm volatile("ld.shared.v4.u32 {%0,%1,%2,%3}, [%4];" : "=r"(v.x), "=r"(v.y), "=r"(v.z), "=r"(v.w) : "r"(a) : "memory");
    return v;
}
template <int OFF>
__device__ __forceinline__ void red_bf16x8(void* p, uint32_t x, uint32_t y, uint32_t z, uint32_t w) {
    asm volatile("red.relaxed.gpu.global.add.noftz.v4.bf16x2 [%0+%5], {%1,%2,%3,%4};"
                 ::"l"(p), "r"(x), "r"(y), "r"(z), "r"(w), "n"(OFF) : "memory");
}
__device__ __forceinline__ void sched_cut() {
    asm volatile("{.reg .pred p; .reg .u64 t; .reg .u32 a, b;\n"
                 "C%=: mov.u64 t, %%clock64; mov.b64 {a, b}, t; setp.eq.u32 p, a, %0; @p bra C%=;}" ::"n"(0) : "memory");
}
__device__ __forceinline__ uint32_t pin(uint32_t v) { return __shfl_xor_sync(0xffffffffu, v, 0); }
template <class T>
__device__ __forceinline__ T* pin(T* p) { return (T*)__shfl_xor_sync(0xffffffffu, (unsigned long long)p, 0); }
__device__ __forceinline__ float selpf(float a, float b, bool p) {
    float r;
    asm("{.reg .pred q; setp.ne.b32 q, %3, 0; selp.f32 %0, %1, %2, q;}" : "=f"(r) : "f"(a), "f"(b), "r"((int)p));
    return r;
}
template <int N, int MASK, int SZ>
__device__ __forceinline__ void halve(float (&a)[SZ]) {
    const bool up = threadIdx.x & MASK;
#pragma unroll
    for (int j = 0; j < N; j++) a[j] = selpf(a[N + j], a[j], up) + __shfl_xor_sync(0xffffffffu, selpf(a[j], a[N + j], up), MASK);
}
__device__ __forceinline__ float bflo(uint32_t u) { return __uint_as_float(u << 16); }
__device__ __forceinline__ float bfhi(uint32_t u) { return __uint_as_float(u & 0xffff0000u); }
__device__ __forceinline__ uint32_t pack_bf16(float lo, float hi) {
    uint32_t r;
    asm("cvt.rn.bf16x2.f32 %0, %1, %2;" : "=r"(r) : "f"(hi), "f"(lo));
    return r;
}
__device__ __forceinline__ uint32_t hmul2_bf16(uint32_t a, uint32_t b) {
    uint32_t r;
    asm("mul.rn.bf16x2 %0, %1, %2;" : "=r"(r) : "r"(a), "r"(b));
    return r;
}
__device__ __forceinline__ float rbf(float v) { return bflo(pack_bf16(v, 0.f)); }
__device__ __forceinline__ float sigmoidf_(float v) { return __fdividef(1.0f, 1.0f + __expf(-v)); }

__device__ __forceinline__ void wg_fence() { asm volatile("wgmma.fence.sync.aligned;" ::: "memory"); }
__device__ __forceinline__ void wg_commit() { asm volatile("wgmma.commit_group.sync.aligned;" ::: "memory"); }
template <int N> __device__ __forceinline__ void wg_wait() { asm volatile("wgmma.wait_group.sync.aligned %0;" ::"n"(N) : "memory"); }
__device__ __forceinline__ uint64_t desc128(uint32_t lo) { return (uint64_t)lo | (0x40000040ull << 32); }
__device__ __forceinline__ uint64_t desc64(uint32_t lo) { return (uint64_t)lo | (0x80000020ull << 32); }
__device__ __forceinline__ void fence_regs(float (&d)[64]) {
#pragma unroll
    for (int i = 0; i < 64; i++) asm volatile("" : "+f"(d[i])::"memory");
}
template <int TB>
__device__ __forceinline__ void wgmma128(float (&d)[64], uint64_t da, uint64_t db, int scaleD) {
    asm volatile(
        "{ .reg .pred p; setp.ne.b32 p, %66, 0;\n"
        "wgmma.mma_async.sync.aligned.m64n128k16.f32.bf16.bf16 "
        "{%0,%1,%2,%3,%4,%5,%6,%7,%8,%9,%10,%11,%12,%13,%14,%15,%16,%17,%18,%19,%20,%21,%22,%23,%24,%25,%26,%27,%28,%29,%30,%31,"
        "%32,%33,%34,%35,%36,%37,%38,%39,%40,%41,%42,%43,%44,%45,%46,%47,%48,%49,%50,%51,%52,%53,%54,%55,%56,%57,%58,%59,%60,%61,%62,%63}, "
        "%64, %65, p, 1, 1, 0, %67;\n}"
        : "+f"(d[0]), "+f"(d[1]), "+f"(d[2]), "+f"(d[3]), "+f"(d[4]), "+f"(d[5]), "+f"(d[6]), "+f"(d[7]),
          "+f"(d[8]), "+f"(d[9]), "+f"(d[10]), "+f"(d[11]), "+f"(d[12]), "+f"(d[13]), "+f"(d[14]), "+f"(d[15]),
          "+f"(d[16]), "+f"(d[17]), "+f"(d[18]), "+f"(d[19]), "+f"(d[20]), "+f"(d[21]), "+f"(d[22]), "+f"(d[23]),
          "+f"(d[24]), "+f"(d[25]), "+f"(d[26]), "+f"(d[27]), "+f"(d[28]), "+f"(d[29]), "+f"(d[30]), "+f"(d[31]),
          "+f"(d[32]), "+f"(d[33]), "+f"(d[34]), "+f"(d[35]), "+f"(d[36]), "+f"(d[37]), "+f"(d[38]), "+f"(d[39]),
          "+f"(d[40]), "+f"(d[41]), "+f"(d[42]), "+f"(d[43]), "+f"(d[44]), "+f"(d[45]), "+f"(d[46]), "+f"(d[47]),
          "+f"(d[48]), "+f"(d[49]), "+f"(d[50]), "+f"(d[51]), "+f"(d[52]), "+f"(d[53]), "+f"(d[54]), "+f"(d[55]),
          "+f"(d[56]), "+f"(d[57]), "+f"(d[58]), "+f"(d[59]), "+f"(d[60]), "+f"(d[61]), "+f"(d[62]), "+f"(d[63])
        : "l"(da), "l"(db), "r"(scaleD), "n"(TB));
}

__device__ __forceinline__ uint32_t get_role(uint32_t& smid) {
    uint32_t role;
    asm volatile("mov.u32 %0, %%smid;" : "=r"(smid));
    asm("{.reg .pred p, q; .reg .u32 t, a, b; shr.u32 t, %1, 1; mad.lo.u32 a, t, 293, -928; shr.u32 a, a, 8; mad.lo.u32 b, t, 8, -464;"
        " setp.lt.u32 p, t, 32; setp.lt.u32 q, t, 62; selp.u32 a, a, b, q; selp.u32 %0, t, a, p;}" : "=r"(role) : "r"(smid));
    return role;
}
__device__ __forceinline__ int tile_of_step(int step, int own) {
    const int u = step >= 17 ? step - 17 - (step > PS1) : step - 2;
    int e = u + (u >= (own & 14) ? 2 : 0);
    if (step == 16 || step == PS1) e = own ^ 1;
    if (step < 2) e = own;
    return e + (step >= 17 || step == 1 ? 16 : 0);
}
__device__ __forceinline__ uint32_t router_key(float score, int row) {
    const float r = score + 0.0f;
    uint32_t u = pack_bf16(r, 0.f) & 0xffffu;
    u = (u & 0x8000u) ? (~u & 0xffffu) : (u | 0x8000u);
    if (r != r) u = 0;
    return (u << 16) | (uint32_t)(0x7fff - row);
}

#define g_fb_h ((float*)g_s.part)
#define g_fb_upd (g_fb_h + 2048)
#define g_fb_gate (g_fb_h + 4096)
#define g_fb_keys (g_s.part + 8192)
__global__ void fb_hidden(const bf16* x, const bf16* dre, const bf16* dim, const bf16* gw, const bf16* wr) {
    __shared__ float xs[D_];
    const int s = blockIdx.x, t = threadIdx.x;
    xs[t] = __bfloat162float(x[s * D_ + t]);
    __syncthreads();
    float a = 0.f, b = 0.f;
    for (int d = 0; d < D_; d++) { a = fmaf(xs[d], __bfloat162float(dre[t * D_ + d]), a); b = fmaf(xs[d], __bfloat162float(dim[t * D_ + d]), b); }
    ((bf16*)g_s.ab)[s * 1024 + t] = __float2bfloat16(a);
    ((bf16*)g_s.ab)[s * 1024 + 512 + t] = __float2bfloat16(b);
    if (t == 0) {
        float u = 0.f, v = 0.f;
        for (int d = 0; d < D_; d++) { u = fmaf(xs[d], __bfloat162float(gw[d]), u); v = fmaf(xs[d], __bfloat162float(wr[d]), v); }
        g_fb_gate[s] = sigmoidf_(u);
        g_fb_keys[s] = router_key(v, s);
    }
}
__device__ uint32_t fb_best() {
    uint32_t k = 0;
    for (int i = 0; i < S_; i++) k = max(k, g_fb_keys[i]);
    return k;
}
__global__ void fb_ffn1(const bf16* x, const bf16* wg, const bf16* wu) {
    const int f = blockIdx.x * blockDim.x + threadIdx.x, idx = 0x7fff - (int)(fb_best() & 0x7fffu);
    float a = 0.f, b = 0.f;
    for (int d = 0; d < D_; d++) {
        const float xv = __bfloat162float(x[idx * D_ + d]);
        a = fmaf(xv, __bfloat162float(wg[d * F_ + f]), a); b = fmaf(xv, __bfloat162float(wu[d * F_ + f]), b);
    }
    g_fb_h[f] = a * sigmoidf_(a) * b;
}
__global__ void fb_ffn2(const bf16* wd) {
    const int e = blockIdx.x * blockDim.x + threadIdx.x;
    const uint32_t u = fb_best() >> 16, rb = (u & 0x8000u) ? (u & 0x7fffu) : (~u & 0xffffu);
    float a = 0.f;
    for (int f = 0; f < F_; f++) a = fmaf(g_fb_h[f], __bfloat162float(wd[f * D_ + e]), a);
    g_fb_upd[e] = a * sigmoidf_(__uint_as_float(rb << 16));
}
__global__ void fb_seq(const bf16* x, const bf16* cre, const bf16* cim, bf16* out) {
    __shared__ float c[2][S_];
    __shared__ int idx;
    const int t = blockIdx.x, e = threadIdx.x;
    for (int i = e; i < S_; i += D_) { c[0][i] = __bfloat162float(cre[t * S_ + i]); c[1][i] = __bfloat162float(cim[t * S_ + i]); }
    if (e == 0) idx = 0x7fff - (int)(fb_best() & 0x7fffu);
    __syncthreads();
    float y = 0.f;
    for (int s = 0; s < S_; s++)
        y += c[0][s] * __bfloat162float(((const bf16*)g_s.ab)[s * 1024 + e]) - c[1][s] * __bfloat162float(((const bf16*)g_s.ab)[s * 1024 + 512 + e]);
    const float g = g_fb_gate[t];
    out[t * D_ + e] = __float2bfloat16(g * y + (1.f - g) * (__bfloat162float(x[t * D_ + e]) + (t == idx ? g_fb_upd[e] : 0.f)));
}

__device__ __forceinline__ void spare_job(const Params& p, unsigned char* smem, int sp, uint32_t tstart) {
    const int tid = threadIdx.x, warp = tid >> 5, lane = tid & 31;
    const uint32_t e1 = *(volatile unsigned int*)&p.s->epoch[NCTA + sp] + 1u;
    const uint32_t par = e1 & 1u;
    uint32_t* sel = (uint32_t*)smem;
    float* acc = (float*)(smem + 1024);
    __syncthreads();
    if (tid == 0) *(volatile unsigned int*)&p.s->epoch[NCTA + sp] = e1;
    sleep_until<500>(tstart + SUM_T0);
    if (warp < 14) {
        uint32_t n = 0;
        while ((int)(ld_relaxed(p.s->phint + (sp * 16 + warp) * 8) - e1 * 8u) < 0) {
            __nanosleep(100);
            if (++n > SPIN_LIMIT) __trap();
        }
        const unsigned int* src = p.s->part + warp * 4 * D_ + sp * 128 + lane * 4;
        uint4 v[4];
        while (true) {
            uint32_t bad = 0;
#pragma unroll
            for (int i = 0; i < 4; i++) v[i] = ld_relaxed4(src + i * D_);
#pragma unroll
            for (int i = 0; i < 4; i++) bad |= (v[i].x ^ par) | (v[i].y ^ par) | (v[i].z ^ par) | (v[i].w ^ par);
            if (!__any_sync(0xffffffffu, bad & 1u)) break;
            if (++n > SPIN_LIMIT) __trap();
        }
        float4 s = make_float4(0.f, 0.f, 0.f, 0.f);
#pragma unroll
        for (int i = 0; i < 4; i++) {
            s.x += __uint_as_float(v[i].x); s.y += __uint_as_float(v[i].y);
            s.z += __uint_as_float(v[i].z); s.w += __uint_as_float(v[i].w);
        }
        *(float4*)&acc[warp * 128 + lane * 4] = s;
    } else if (warp == 14) {
        const uint4 k4 = wait_tags(p.s->keys + lane * 4, 15, par);
        const uint32_t k = __reduce_max_sync(0xffffffffu, max(max(k4.x, k4.y), max(k4.z, k4.w)));
        const int idx = 0x7fff - (int)(k & 0x7fffu);
        const uint4 g4 = wait_tags(p.s->gate + (idx & ~3), 0, par);
        const uint32_t gw = (idx & 2) ? ((idx & 1) ? g4.w : g4.z) : ((idx & 1) ? g4.y : g4.x);
        const uint32_t u = k >> 16;
        const uint32_t rb = (u & 0x8000u) ? (u & 0x7fffu) : (~u & 0xffffu);
        const float og = 1.f - __uint_as_float(gw & ~1u), rs = sigmoidf_(__uint_as_float(rb << 16));
        if (lane == 0) { sel[0] = idx; sel[1] = pack_bf16(og, og); sel[2] = pack_bf16(rs, rs); }
        sleep_until<500>(tstart + SUM_T0 + 3000);
        wait_counter(p.s->ready + (idx >> 7) * 32, e1 * 8u);
    }
    __syncthreads();
    if (tid < 64) {
        float t0 = 0.f, t1 = 0.f;
#pragma unroll
        for (int i = 0; i < 14; i++) {
            const float2 z = *(const float2*)&acc[i * 128 + tid * 2];
            t0 += z.x; t1 += z.y;
        }
        asm volatile("red.relaxed.gpu.global.add.noftz.bf16x2 [%0], %1;" ::"l"(p.out + sel[0] * D_ + sp * 128 + tid * 2),
                     "r"(hmul2_bf16(sel[1], hmul2_bf16(sel[2], pack_bf16(t0, t1)))) : "memory");
    }
}

__host__ __device__ constexpr int off_d(int c) { return (c < 2 ? 1 : c / 2 + 2) * REGION + (c & 1) * 16384; }
__host__ __device__ constexpr int off_xe(int c) { return (c < 2 ? 6 * REGION : c < 4 ? 16384 : c < 6 ? 0 : 6 * REGION + 16384) + (c & 1) * 8192; }
__host__ __device__ constexpr int off_xl(int c) { return c < 4 ? 2 * REGION + c * 8192 : off_xe(c - 4); }

__global__ void __cluster_dims__(2, 1, 1) __launch_bounds__(NTHREADS, 1)
fused_kernel(const __grid_constant__ Params p) {
    extern __shared__ __align__(1024) unsigned char smem[];
    const uint32_t tstart = clk();
    const uint32_t sb = smem_u32(smem);
    const int tid = threadIdx.x, lane = tid & 31;
    const int rank = blockIdx.x & 1;
    uint32_t t1 = 0;
    if (__any_sync(0xffffffffu, tid == 0)) {
        uint32_t s0;
        const uint32_t r0 = get_role(s0);
        mbar_init_elect(sb + B_F, 1);
        if (r0 < 64) {
#pragma unroll
            for (int c = 0; c < 2; c++) {
                if (c) {
                    spin_until(t1 + PACE);
                    mbar_init_elect(sb + B_F + 8, 1);
                }
                tma3d_elect(sb + off_d(c), &p.mDre + ((r0 >> 2) & 1), (r0 & 24) * 16, c, sb + B_F + 8 * c);
                tma3d_elect(sb + off_xe(c), &p.mX1, (r0 & 3) * 256 + (r0 & 32) * 4 + rank * 64, c, sb + B_F + 8 * c);
                mbar_expect_tx_elect(sb + B_F + 8 * c, 24576);
                if (!c) {
                    t1 = clk() + PACE0;
                    mbar_init_elect(sb + B_G0, 1);
                    tma3d_elect(sb + off_xl(0), &p.mX1, (r0 & 3) * 256 + (r0 & 32) * 4 + rank * 64 + 1024, 0, sb + B_G0);
                    mbar_expect_tx_elect(sb + B_G0, 8192);
                }
            }
        }
    }
    const int warp = __shfl_sync(0xffffffffu, tid >> 5, 0);
    uint32_t smid;
    const uint32_t role = get_role(smid);
    const int gpc = role & 7;
    const int tn = (role >> 3) & 3;
    const int comp = gpc >> 2;
    const int own = (gpc & 3) * 4 + ((role >> 5) & 1) * 2 + rank;
    const int blk = comp * 4 + tn;
    const int cta = gpc * 16 + (role >> 3) * 2 + rank;
    const bool ffn = cta < FFN_CTAS;
    uint32_t epoch = 0;
    if (warp != 0) {
        const uint32_t b1 = sb + B_F + 8 * warp;
        mbar_init_elect(warp < 2 ? b1 + 360 : b1, 1);
        if (warp >= 2 && warp < 5) mbar_init_elect(b1 + 360, warp < 4 ? 1 : 4);
        mbar_init_elect(b1 + 120, warp < 7 ? 5 : warp < 14 ? 4 : warp - 12);
        mbar_init_elect(b1 + 240, 1);
        if (warp == 9 || warp == 15) mbar_expect_tx_elect(b1 + 240, warp == 9 ? 2048 : 4);
        asm volatile("fence.mbarrier_init.release.cluster;" ::: "memory");
        if (tid == 128 && role < 64) epoch = *(volatile unsigned int*)&p.s->epoch[cta];
    }
    if (role >= 64) {
        spare_job(p, smem, smid & 3, tstart);
        return;
    }
    __syncthreads();
    cluster_arrive();
    if (warp == 0) {
#pragma unroll
        for (int c = 2; c < 8; c++) {
            spin_until(t1 + c * PACE);
            tma3d_elect(sb + off_d(c), &p.mDre + comp, tn * 128, c, sb + B_F + 8 * c);
            tma3d_elect(sb + off_xe(c), &p.mX1, own * 64, c, sb + B_F + 8 * c);
            mbar_expect_tx_elect(sb + B_F + 8 * c, 24576);
        }
        tma3d_elect(sb + off_xl(1), &p.mX1, own * 64 + 1024, 1, sb + B_G1);
        mbar_expect_tx_elect(sb + B_G1, 8192);
        spin_until(t1 + 8 * PACE);
        tma3d_elect(sb + off_xl(2), &p.mX2, own * 64 + 1024, 2, sb + B_G2);
        mbar_expect_tx_elect(sb + B_G2, 16384);
        if (tn < 2)
            asm volatile(ELECT "cp.async.bulk.prefetch.tensor.3d.L2.global [%0, {%1,%2,%3}];}"
                         ::"l"(&p.mX2), "r"(0), "r"(own * 64 + 1024), "r"(4 + 2 * tn) : "memory");
    }

    if (warp < 4) {
        const int tab = tile_of_step(lane, own);
        const uint32_t bdst = sb + 16384 + rank * 8192;
        const int brow = blk * 4096 + rank * 64;
        if (warp == 0) {
            mbar_spin(sb + B_XE, 0);
            tma3d_elect(sb + off_xl(4), &p.mX2, own * 64 + 1024, 4, sb + B_G4);
            tma3d_elect(sb + off_xl(6), &p.mX2, own * 64 + 1024, 6, sb + B_G4);
            mbar_expect_tx_elect(sb + B_G4, 32768);
#define LOAD_A() const int e = __shfl_sync(0xffffffffu, tab, step);                                             \
                 const uint32_t bar = sb + 8 * slot;                                                            \
                 mbar_spin(bar + B_EMPTY, ph);                                                                  \
                 tma2d_elect(sb + slot * REGION, &p.mCre + comp, e * 64, own * 128, bar + B_FULL);              \
                 mbar_expect_tx_elect(bar + B_FULL, 16384)
            uint32_t slot = 0, ph = 0;
            int step = 0;
#pragma unroll 1
            for (int i = 0; i < NSTAGE; i++) {
                step = slot = i < 2 ? i ^ 1 : i;
                LOAD_A();
                if (i == 2 || i == 3) spin_until(clk() + A_GAP);
            }
            step = NSTAGE;
            slot = 0; ph = 1;
#pragma unroll 1
            for (int h = 0; h < 3; h++) {
                const int last = h == 0 ? 16 : h == 1 ? PS1 : 32 - NA;
#pragma unroll 1
                for (; step < last; step++) {
                    LOAD_A();
                    tma2d_pair_elect(bdst + slot * REGION, &p.mAB, 0, brow + e * 128, bar + B_BL);
                    mbar_expect_tx_elect(bar + B_BL, 16384);
                    if (++slot == NSTAGE) { slot = 0; ph ^= 1; }
                }
                if (h == 2) break;
                LOAD_A();
                tma2d_elect(bdst + slot * REGION, &p.mAB, 0, brow + e * 128, bar + B_BL);
                tma2d_elect((bdst ^ 8192) + slot * REGION, &p.mAB, 0, (brow ^ 64) + e * 128, bar + B_BL);
                mbar_expect_tx_elect(bar + B_BL, 16384);
                step++;
                if (++slot == NSTAGE) { slot = 0; ph ^= 1; }
            }
            mbar_spin(sb + B_LOW, 0);
            uint32_t aslot = 6;
#pragma unroll 1
            for (; step < 32; step++) {
                const int e = __shfl_sync(0xffffffffu, tab, step);
                const uint32_t bar = sb + 8 * slot;
                tma2d_elect(sb + aslot * REGION, &p.mCre + comp, e * 64, own * 128, bar + B_FULL);
                mbar_expect_tx_elect(bar + B_FULL, 16384);
                mbar_expect_tx_elect(bar + B_BL, 16384);
                mbar_spin(bar + B_EMPTY, ph);
                tma2d_pair_elect(bdst + slot * REGION, &p.mAB, 0, brow + e * 128, bar + B_BL);
                aslot = slot;
                if (++slot == NSTAGE) { slot = 0; ph ^= 1; }
            }
        } else if (warp == 1) {
            if (lane < 4) asm volatile("prefetch.tensormap [%0];" ::"l"(&p.mCre + lane) : "memory");
            __syncwarp();
            cluster_wait();
            if (lane == 0)
                asm volatile("st.async.weak.shared::cluster.mbarrier::complete_tx::bytes.u32 [%0], %1, [%2];"
                             ::"r"(mapa(sb + M_ROLE, rank ^ 1)), "r"(role), "r"(mapa(sb + B_ROLE, rank ^ 1)) : "memory");
            mbar_wait_cluster(sb + B_ROLE, 0);
            if (*(volatile uint32_t*)(smem + M_ROLE) != role) __trap();
            mbar_wait(sb + B_EPOCH, 0);
            const uint32_t want = (*(volatile uint32_t*)(smem + M_EPOCH) + 1u) * 4u;
            const int eh = __shfl_sync(0xffffffffu, tab, 2 + (lane & 3));
            const unsigned int* hp = p.s->hint + (blk * 4 + (eh >> 1)) * 32 + (eh & 1);
            uint32_t seen = __ballot_sync(0xffffffffu, ld_relaxed(hp) == want);
            int rows[4];
#pragma unroll
            for (int i = 0; i < 4; i++) {
                rows[i] = brow + __shfl_sync(0xffffffffu, tab, 2 + i) * 128;
                mbar_expect_tx_elect(sb + B_BL + 8 * (2 + i), 16384);
            }
            mbar_wait(sb + B_EMPTY + 8 * 3, 0);
            mbar_spin(sb + B_EMPTY + 8 * 2, 0);
            uint32_t t3 = 0;
#pragma unroll
            for (int i = 0; i < 4; i++) {
                while (!((seen >> i) & 1u)) seen = __ballot_sync(0xffffffffu, ld_relaxed(hp) == want);
                if (i) spin_until(t3 + B_GAP);
                t3 = clk();
                if (i >= 2) mbar_spin(sb + B_EMPTY + 8 * (2 + i), 0);
                tma2d_pair_elect(bdst + (2 + i) * REGION, &p.mAB, 0, rows[i], sb + B_BL + 8 * (2 + i));
            }
            mbar_wait(sb + B_FREE, 0);
            unsigned char* gdst = p.s->ab + (blk * 32 + own + 16) * 16384;
            t3 = clk();
#pragma unroll 1
            for (int i = 0; i < 16; i++) {
                sleep_until<20>(t3);
                t3 += LATE_GAP;
                asm volatile(ELECT "cp.async.bulk.global.shared::cta.bulk_group [%0], [%1], 1024;}"
                             ::"l"(gdst + i * 1024), "r"(sb + 6 * REGION + i * 1024) : "memory");
            }
            bulk_wait_read();
            mbar_arrive_elect(sb + B_FREE + 8);
            mbar_wait(sb + B_PUB, 0);
            if (lane == 0) {
                asm volatile("fence.proxy.async.global;" ::: "memory");
                asm volatile("red.release.gpu.global.add.u32 [%0], 1;" ::"l"(p.s->ready + (cta >> 3) * 32) : "memory");
            }
            __syncwarp();
            __nanosleep(INIT_NS);
            wait_counter(p.s->ready + own * 32, want * 2u);
            mbar_arrive_elect(sb + B_INIT);
        } else {
            mbar_arrive_elect(sb + B_BL + 8 * (warp & 1));
            uint32_t k = warp == 3 ? 0 : 12;
#define PREFETCH_W() {                                                                                          \
                const char* src = (k >= 8 ? (const char*)p.wd + ((cta >> 5) * 2 + (k >> 1) - 4) * 229376        \
                                          : (const char*)((cta & 32) ? p.wu : p.wg) + ((cta >> 6) * 4 + (k >> 1)) * 229376) \
                                  + ((cta & 31) * 2 + (k & 1)) * 3584;                                          \
                asm volatile(ELECT "cp.async.bulk.prefetch.L2.global [%0], 3584;}" ::"l"(src) : "memory");      \
                k++; }
#pragma unroll 1
            while (k < PF_N0) {
                sleep_until<50>(tstart + PF_T0 + k * PF_GAP);
                __syncwarp();
                PREFETCH_W();
            }
            mbar_wait(sb + B_EPOCH, 0);
            const uint32_t par = (*(volatile uint32_t*)(smem + M_EPOCH) + 1u) & 1u;
            const uint32_t a0 = sb + 16384 + (lane >> 3) * 1028 + ((lane >> 2) & 1) * 144 + (lane & 3) * 32;
            const uint32_t retry = sb + B_RETRY + (warp & 1) * 240;
            uint32_t slot = warp, ph = 0, rph = 0;
            uint32_t j = ffn ? warp & 1 : 12;
#pragma unroll 1
            for (int step = warp; step < 32 || j < 12;) {
                const bool go = step < (j < 8 ? 32 - NA : 32);
                if (go) {
                    const uint32_t bar = sb + 8 * slot;
                    mbar_wait(bar + B_BL, ph);
#pragma unroll 1
                    while (__any_sync(0xffffffffu, stale_tags(a0 + slot * REGION, par) & 1u)) {
                        const int row = blk * 4096 + __shfl_sync(0xffffffffu, tab, step) * 128;
                        mbar_expect_tx_elect(retry, 16384);
                        tma2d_elect(sb + slot * REGION + 16384, &p.mAB, 0, row, retry);
                        tma2d_elect(sb + slot * REGION + 24576, &p.mAB, 0, row + 64, retry);
                        mbar_spin(retry, rph);
                        rph ^= 1u;
                    }
                    mbar_arrive_elect<4>(bar + B_FULL);
                }
                if (j < 12 && step >= FFN_S0 + j * FFN_W / 4 && __any_sync(0xffffffffu, mbar_test(sb + B_FREE + 2 * (j & 12), 0))) {
                    const uint32_t fb = sb + B_FFN + 4 * (j & 6);
                    if (!(j & 1)) mbar_expect_tx_elect(fb, 8192);
                    tma2d_elect(sb + 6 * REGION + ((j + 4) & 7) * 4096, j < 8 ? &p.mWg + (j & 1) : &p.mWd,
                                j < 8 ? (cta >> 1) * 32 : rank * 256, j < 8 ? rank * 256 + (j >> 1) * 64 : (cta >> 1) * 32 + j * 8 - 64, fb);
                    j += 2;
                }
                if (k < 12) PREFETCH_W();
                if (go) {
                    step += 2;
                    slot += 2;
                    if (slot >= NSTAGE) { slot -= NSTAGE; ph ^= 1; }
                }
            }
        }
    } else if (warp < 8) {
        const int t = tid - 128, w = warp - 4;
        if (t == 0) {
            *(volatile uint32_t*)(smem + M_EPOCH) = epoch;
            *(volatile unsigned int*)&p.s->epoch[cta] = epoch + 1;
        }
        mbar_arrive_if(sb + B_EPOCH, t == 0);
        const uint4 gw0 = ldg_nc<0>(p.gate_w + lane * 8), gw1 = ldg_nc<512>(p.gate_w + lane * 8);
        const uint4 rw0 = ldg_nc<0>(p.w_r + lane * 8), rw1 = ldg_nc<512>(p.w_r + lane * 8);
        mbar_wait(sb + B_EPOCH, 0);
        const uint32_t par = (*(volatile uint32_t*)(smem + M_EPOCH) + 1u) & 1u;
        mbar_wait(sb + B_F + 8 * ROUTER_C, 0);
        const int row0 = cta * 16 + w * 4;
        uint4 xr[8];
        {
            const char* xp = (const char*)p.x + (uint32_t)row0 * (D_ * 2) + lane * 16;
            xr[0] = ldg_nc<0>(xp);    xr[1] = ldg_nc<512>(xp);  xr[2] = ldg_nc<1024>(xp); xr[3] = ldg_nc<1536>(xp);
            xr[4] = ldg_nc<2048>(xp); xr[5] = ldg_nc<2560>(xp); xr[6] = ldg_nc<3072>(xp); xr[7] = ldg_nc<3584>(xp);
            float a[8];
#pragma unroll
            for (int i = 0; i < 4; i++) {
                const uint32_t xv[8] = {xr[2 * i].x, xr[2 * i].y, xr[2 * i].z, xr[2 * i].w,
                                        xr[2 * i + 1].x, xr[2 * i + 1].y, xr[2 * i + 1].z, xr[2 * i + 1].w};
                const uint32_t gv[8] = {gw0.x, gw0.y, gw0.z, gw0.w, gw1.x, gw1.y, gw1.z, gw1.w};
                const uint32_t rv[8] = {rw0.x, rw0.y, rw0.z, rw0.w, rw1.x, rw1.y, rw1.z, rw1.w};
                float u = 0.f, v = 0.f;
#pragma unroll
                for (int j = 0; j < 8; j++) {
                    const uint32_t pr = hmul2_bf16(xv[j], gv[j]);
                    u += bflo(pr); u += bfhi(pr);
                    v = fmaf(bflo(xv[j]), bflo(rv[j]), v); v = fmaf(bfhi(xv[j]), bfhi(rv[j]), v);
                }
                a[i] = u; a[4 + i] = v;
            }
            mbar_wait(sb + B_EARLY, 0);
            halve<4, 16>(a); halve<2, 8>(a); halve<1, 4>(a);
            a[0] += __shfl_xor_sync(0xffffffffu, a[0], 1);
            a[0] += __shfl_xor_sync(0xffffffffu, a[0], 2);
            const int row = row0 + ((lane >> 2) & 3);
            const float gate = rbf(sigmoidf_(rbf(a[0])));
            if (lane < 16 && (lane & 3) == 0)
                asm volatile("st.relaxed.gpu.global.u32 [%0], %1;" ::"l"(&p.s->gate[row]), "r"(tagf(gate, par)) : "memory");
            const uint32_t best = __reduce_max_sync(0xffffffffu, lane >= 16 ? router_key(a[0], row) : 0u);
            if (lane == 0) *(volatile uint32_t*)(smem + M_KEY + w * 4) = best;
            side_bar();
            if (t < 8) {
                const uint4 k = *(const uint4*)(smem + M_KEY);
                asm volatile("{.reg .b32 old; atom.relaxed.gpu.global.exch.b32 old, [%0], %1;}" ::"l"(&p.s->keys[t * NCTA + cta]),
                             "r"(max(max(k.x, k.y), max(k.z, k.w)) | (par << 15)) : "memory");
            }
            const uint32_t og = pack_bf16(1.f - gate, 1.f - gate);
#pragma unroll
            for (int i = 0; i < 8; i++) {
                const uint32_t o = __shfl_sync(0xffffffffu, og, 4 * (i >> 1));
                xr[i] = make_uint4(hmul2_bf16(o, xr[i].x), hmul2_bf16(o, xr[i].y), hmul2_bf16(o, xr[i].z), hmul2_bf16(o, xr[i].w));
            }
        }
        mbar_wait(sb + B_FREE, 0);
        __nanosleep(KEY_NS);
        if (w == 0) {
            const uint4 k4 = wait_tags(p.s->keys + gpc * NCTA + lane * 4, 15, par);
            const uint32_t k = __reduce_max_sync(0xffffffffu, max(max(k4.x, k4.y), max(k4.z, k4.w)));
            sts128<M_XS>(sb + lane * 16, ldg_nc<0>(p.x + (0x7fff - (k & 0x7fffu)) * D_ + rank * 256 + lane * 8));
        } else if (w == 1) {
            const uint4 g4 = wait_tags(p.s->gate + own * 128 + lane * 4, 0, par);
            const uint32_t sg = comp ? 0x80000000u : 0u;
            sts128<M_G>(sb + lane * 16, make_uint4((g4.x & ~1u) ^ sg, (g4.y & ~1u) ^ sg, (g4.z & ~1u) ^ sg, (g4.w & ~1u) ^ sg));
            mbar_arrive_warp(sb + B_GATE);
        }
        side_bar();
        char* op = (char*)p.out + (uint32_t)row0 * (D_ * 2) + lane * 16;
        float a[16];
#pragma unroll
        for (int i = 0; i < 16; i++) a[i] = 0.f;
#pragma unroll 1
        for (int i = 0; i < 4; i++) {
            if (i == 2) {
                mbar_wait(sb + B_FREE + 8, 0);
                const uint32_t t2 = clk() + w * (INIT_GAP / 4);
#pragma unroll
                for (int j = 0; j < 8; j++) {
                    sleep_until<20>(t2 + j * INIT_GAP);
                    *(uint4*)(op + j * 512) = xr[j];
                }
                mbar_arrive_warp(sb + B_PUB);
            }
            if (ffn) {
                const float xs0 = __bfloat162float(((const bf16*)(smem + M_XS))[64 * i + (t >> 2)]);
                const float xs1 = __bfloat162float(((const bf16*)(smem + M_XS))[64 * i + 32 + (t >> 2)]);
                const uint32_t wa = sb + 6 * REGION + (i ^ 2) * 8192 + t * 16;
                mbar_wait(sb + B_FFN + 8 * i, 0);
                const uint4 v0 = lds128(wa), v1 = lds128(wa + 4096), v2 = lds128(wa + 2048), v3 = lds128(wa + 6144);
                const uint32_t w0[8] = {v0.x, v0.y, v0.z, v0.w, v1.x, v1.y, v1.z, v1.w};
                const uint32_t w1[8] = {v2.x, v2.y, v2.z, v2.w, v3.x, v3.y, v3.z, v3.w};
#pragma unroll
                for (int k = 0; k < 8; k++) {
                    a[2 * k] = fmaf(xs1, bflo(w1[k]), fmaf(xs0, bflo(w0[k]), a[2 * k]));
                    a[2 * k + 1] = fmaf(xs1, bfhi(w1[k]), fmaf(xs0, bfhi(w0[k]), a[2 * k + 1]));
                }
                if (i == 1) {
                    side_bar();
                    mbar_arrive_if(sb + B_FREE + 16, t == 0);
                }
            }
        }
        if (!ffn) {
            mbar_arrive_warp(sb + B_LOW);
            return;
        }
        halve<8, 16>(a); halve<4, 8>(a); halve<2, 4>(a);
        const uint32_t ho = (lane >> 4) * 128 + (lane & 3) * 32 + ((lane >> 2) & 3) * 8;
        cluster_wait();
#pragma unroll
        for (int k = 0; k < 2; k++)
            asm volatile("st.async.weak.shared::cluster.mbarrier::complete_tx::bytes.v2.f32 [%0], {%1,%2}, [%3];"
                         ::"r"(mapa(sb + (k ? 6 * REGION + w * 512 : M_HX + w * 256) + ho, rank ^ k ^ 1)), "f"(a[0]), "f"(a[1]),
                           "r"(mapa(sb + B_HX, rank ^ k ^ 1)) : "memory");
        mbar_wait_cluster(sb + B_HX, 0);
        const float *hx = (const float*)(smem + M_HX) + lane, *hy = (const float*)(smem + 6 * REGION) + lane;
        const float gs = rbf(((hx[0] + hy[0]) + (hx[64] + hy[128])) + ((hx[128] + hy[256]) + (hx[192] + hy[384])));
        const float us = rbf(((hx[32] + hy[32]) + (hx[96] + hy[160])) + ((hx[160] + hy[288]) + (hx[224] + hy[416])));
        float* hrow = (float*)(smem + M_XS) + w * 32;
        hrow[lane] = rbf(rbf(gs * sigmoidf_(gs)) * us);
        fence_proxy_async_smem();
        mbar_arrive_warp(sb + B_LOW);
        float o0 = 0.f, o1 = 0.f;
#pragma unroll 1
        for (int i = 0; i < 2; i++) {
            float4 hv[4];
            uint32_t vd[16];
#pragma unroll
            for (int k = 0; k < 4; k++) hv[k] = *(const float4*)&hrow[i * 16 + k * 4];
            mbar_wait(sb + B_FFN + 8 * i, 1);
#pragma unroll
            for (int k = 0; k < 16; k++) vd[k] = *(const volatile uint32_t*)(smem + 6 * REGION + 16384 + i * 8192 + k * 512 + t * 4);
#pragma unroll
            for (int k = 0; k < 4; k++) {
                o0 = fmaf(hv[k].x, bflo(vd[4 * k]), o0);     o1 = fmaf(hv[k].x, bfhi(vd[4 * k]), o1);
                o0 = fmaf(hv[k].y, bflo(vd[4 * k + 1]), o0); o1 = fmaf(hv[k].y, bfhi(vd[4 * k + 1]), o1);
                o0 = fmaf(hv[k].z, bflo(vd[4 * k + 2]), o0); o1 = fmaf(hv[k].z, bfhi(vd[4 * k + 2]), o1);
                o0 = fmaf(hv[k].w, bflo(vd[4 * k + 3]), o0); o1 = fmaf(hv[k].w, bfhi(vd[4 * k + 3]), o1);
            }
        }
        asm volatile("st.relaxed.gpu.global.v2.u32 [%0], {%1,%2};" ::"l"(&p.s->part[(cta >> 1) * D_ + rank * 256 + t * 2]),
                     "r"(tagf(o0, par)), "r"(tagf(o1, par)) : "memory");
        red_inc_if(p.s->phint + ((rank * 2 + (w >> 1)) * 16 + (cta >> 3)) * 8 + lane, lane == 0);
    } else {
        const int wg = (warp >> 2) - 2, wq = warp & 3;
        const uint32_t sbd = ((sb & 0x3FFFF) >> 4) + 0x10000;
        const bool lead = (tid & 127) == 0;
        const bool lead0 = lead && !wg, lead1 = lead && wg;
        const int q = lane & 3;
        float acc[64];
        const uint32_t rE = mapa(sb + B_EMPTY, rank ^ 1);
#define RELEASE(n, slot, pred) release_pair<n>(sb + B_EMPTY + 8 * (slot), rE + 8 * (slot), pred)
        const uint32_t ioff = wq * 4096 + (lane >> 2) * 64 + ((q ^ (lane >> 3)) << 4);
        const uint32_t sdst = pin(sb + 6 * REGION + (wg ? 0 : 16384) + ioff);
        unsigned char* gdst = pin(p.s->ab + (blk * 32 + own) * 16384 + ioff);
        unsigned int* hint = pin(p.s->hint + (blk * 4 + ((own >> 1) & 3)) * 32 + rank + lane);
        uint32_t par = 0;
#define GET_PAR() mbar_spin(sb + B_EPOCH, 0); par = (*(volatile uint32_t*)(smem + M_EPOCH) + 1u) & 1u
        cluster_wait();
        if (wg) mbar_spin(sb + B_G0, 0);
#pragma unroll
        for (int c = 0; c < 8; c++) {
            if (c == 1 && wg) {
                wg_wait<0>();
                RELEASE(1, 1, lead);
                GET_PAR();
                mbar_spin(sb + B_G1, 0);
            }
            if (!wg || c < 3 || c == 4) mbar_spin(sb + (!wg || c == 0 ? B_F + 8 * c : c == 1 ? B_GO1 : c == 2 ? B_G2 : B_G4), 0);
            const uint32_t xa = sbd + wg * ((off_xl(c) - off_xe(c)) / 16);
            wg_fence();
#pragma unroll
            for (int kk = 0; kk < 4; kk++) {
                wgmma128<0>(acc, desc128(xa + off_xe(c) / 16 + 2 * kk), desc128(sbd + off_d(c) / 16 + 2 * kk), (c | kk) != 0);
                if (c == 7 && kk == 0) wg_commit();
            }
            wg_commit();
            if (c == 3 && !wg) { GET_PAR(); }
            if (c == 7) {
                if (wg) mbar_spin(sb + B_FULL, 0);
                wg_wait<2>();
                mbar_arrive_if(sb + B_GO1, lead0);
            }
            if (c == 4 || c >= 6) wg_wait<1>();
            if (c == 4) { mbar_arrive_if(sb + B_XE, lead0); RELEASE(1, 1, lead0); RELEASE(2, 2, lead1); RELEASE(2, 3, lead1); }
            if (c == 6) RELEASE(2, 4 * wg, lead);
            if (c == 7) mbar_arrive_if(sb + B_GO0, lead1);
        }
        const int rh = wg ^ comp;
        const uint32_t da0 = sbd + rh * 512, db0 = sbd - 0x10000 + 0x400000 + 1024;
        const uint32_t dbe = db0 + 6 * (REGION / 16), dbl = dbe - 1024;
#define STEP(da, db, first) wg_fence();                                                                     \
        _Pragma("unroll") for (int kk = 0; kk < 4; kk++)                                                    \
            wgmma128<1>(acc, desc128((da) + kk * 2), desc64((db) + kk * 256), !((first) && kk == 0));       \
        wg_commit()
#define ACC(i, j) (16 * ((i) >> 1) + 2 * ((i) & 1) + 4 * (j))
#define PW(i, j) pack_bf16(acc[ACC(i, j)], acc[ACC(i, j) + 1])
#define PT(i, j) ((j) == ((i) >> 1) ? (PW(i, j) & ~1u) | par : PW(i, j))
#define PIECE(i) make_uint4(PT(i, 0), PT(i, 1), PT(i, 2), PT(i, 3))
#define PIECES(F) F(0); F(1); sched_cut(); F(2); F(3); F(4); F(5); F(6); F(7)
        if (wg) {
            wg_wait<0>();
            fence_regs(acc);
#define STS1(i) sts128<(i) * 512>(sdst, PIECE(i))
            PIECES(STS1);
            STEP(da0, dbe, true);
            fence_proxy_async_smem();
            mbar_arrive_warp(sb + B_FULL + 8);
            RELEASE(1, 5, lead);
        } else {
            wg_wait<0>();
            fence_regs(acc);
            uint4 v[8];
#define STG0(i) v[i] = PIECE(i); stg128<(i) * 512>(gdst, v[i]); if (HINT_AT == (i) + 1) red_inc_if(hint, own < 6 && lane == 0)
            PIECES(STG0);
            mbar_spin(sb + B_EPOCH, 0);
            asm volatile("bar.sync 2, 128;" ::: "memory");
#define STS0(i) if ((i) % 2 == 0) mbar_spin(sb + B_EPOCH, 0); sts128<(i) * 512>(sdst, v[i])
            STS0(0); STS0(1); STS0(2); STS0(3); STS0(4); STS0(5); STS0(6); STS0(7);
            fence_proxy_async_smem();
            mbar_arrive_warp(sb + B_FULL);
            RELEASE(1, 5, lead);
            mbar_arrive_if(sb + B_EARLY, lead);
            mbar_spin(sb + B_FULL, 0);
            mbar_spin(sb + B_GO0, 0);
            STEP(da0, dbe, true);
        }
#pragma unroll
        for (int step = 1; step < 3; step++) {
            mbar_spin(sb + B_FULL + 8 * step, 0);
            STEP(da0 + step * (REGION / 16), step == 1 ? dbl : db0 + step * (REGION / 16), false);
            wg_wait<1>();
            RELEASE(1, step - 1, lead);
            mbar_arrive_if(sb + B_FREE + 8 * (step - 1), lead);
        }
        int slot = 3, ph = 0, pslot = 2;
        float g0 = 0.f, g1 = 0.f;
        uint32_t oa = 0;
#pragma unroll 1
        for (int step = 3; step < 26; step++) {
            mbar_wait(sb + B_FULL + 8 * slot, ph);
            STEP(da0 + slot * (REGION / 16), db0 + slot * (REGION / 16), false);
            if (step == 22 + wg) {
                const int r0 = rh * 64 + wq * 16 + (lane >> 2), sr = ((lane >> 2) & 1) * 4 + (lane >> 3);
                mbar_wait(sb + B_GATE, 0);
                g0 = ((const volatile float*)(smem + M_G))[r0];
                g1 = ((const volatile float*)(smem + M_G))[r0 + 8];
                oa = pin(wg ? ((own * 128 + (r0 & ~1)) * D_ + tn * 128 + (lane & 7) * 8) * 2u
                            : sb + rh * 8192 + wq * 2048 + sr * 128 + ((q ^ sr) << 4));
            }
            wg_wait<1>();
            RELEASE(1, pslot, lead);
            pslot = slot;
            if (++slot == NSTAGE) { slot = 0; ph ^= 1; }
        }
        mbar_wait(sb + B_FULL + 8 * 2, 0);
        wg_fence();
#pragma unroll
        for (int kk = 0; kk < 4; kk++) {
            if (kk == HSK) {
                wg_commit();
                if (wg) {
                    wg_wait<1>();
                    RELEASE(1, 1, lead);
                    mbar_wait(sb + B_INIT, 0);
                    mbar_wait(sb + B_TAIL, 0);
                }
                wg_fence();
            }
            wgmma128<1>(acc, desc128(da0 + 2 * (REGION / 16) + kk * 2), desc64(db0 + 2 * (REGION / 16) + kk * 256), 1);
        }
        wg_commit();
        if (!wg) {
            wg_wait<2>();
            RELEASE(1, 1, lead);
        }
        slot = 3;
#pragma unroll 1
        for (int step = 27; step < 32; step++) {
            if (!wg) mbar_wait(sb + B_FULL + 8 * slot, ph);
            STEP(da0 + (step < 32 - NA ? slot : step == 32 - NA ? 6 : pslot) * (REGION / 16), db0 + slot * (REGION / 16), false);
            pslot = slot;
            if (++slot == NSTAGE) { slot = 0; ph ^= 1; }
        }
#define OW(i, j) pack_bf16((((i) & 1) ? g1 : g0) * acc[ACC(i, j)], (((i) & 1) ? g1 : g0) * acc[ACC(i, j) + 1])
        if (!wg) {
            wg_wait<1>();
            mbar_arrive_if(sb + B_TAIL, lead);
            const uint32_t st0 = sb + rh * 8192 + wq * 2048;
            mbar_wait(sb + B_INIT, 0);
            wg_wait<0>();
            fence_regs(acc);
#define OSTS(i) sts128<((i) >> 2) * REGION + ((i) & 1) * 1024>(((i) & 2) ? oa ^ 64 : oa, make_uint4(OW(i, 0), OW(i, 1), OW(i, 2), OW(i, 3)))
#define ORED(h) fence_proxy_async_smem(); __syncwarp();                                                     \
            asm volatile(ELECT "cp.reduce.async.bulk.tensor.4d.global.shared::cta.add.tile.bulk_group [%0, {%2,%3,%3,%4}], [%1];}" \
                         ::"l"(&p.mOut), "r"(st0 + (h) * REGION), "r"(tn * 128 + (h) * 64), "r"(0), "r"(own * 16 + rh * 8 + wq * 2) : "memory")
            OSTS(0); OSTS(1); OSTS(2); OSTS(3);
            ORED(0);
            sched_cut();
            OSTS(4); OSTS(5); OSTS(6); OSTS(7);
            ORED(1);
            bulk_wait_read();
        } else {
            const bool odd = lane & 4;
            char *op = pin((char*)p.out + oa), *opb = pin((char*)p.out + (oa ^ 64) + 1024);
            sched_cut();
            wg_wait<0>();
            fence_regs(acc);
#define REDLINE(i) {                                                                                        \
                uint32_t k[4], r[4];                                                                        \
                _Pragma("unroll") for (int j = 0; j < 4; j++) {                                             \
                    r[j] = __shfl_xor_sync(0xffffffffu, OW((i) + 2, j), 4);                                 \
                    k[j] = OW(i, j);                                                                        \
                }                                                                                           \
                red_bf16x8<((i) & 1) * 8192 + ((i) >> 2) * 128>(op, odd ? r[0] : k[0], odd ? r[1] : k[1], odd ? r[2] : k[2], odd ? r[3] : k[3]);  \
                red_bf16x8<((i) & 1) * 8192 + ((i) >> 2) * 128>(opb, odd ? k[0] : r[0], odd ? k[1] : r[1], odd ? k[2] : r[2], odd ? k[3] : r[3]); }
            REDLINE(0)
            sched_cut();
            REDLINE(4) REDLINE(1) REDLINE(5)
        }
    }
}

typedef CUresult (*EncodeTiledFn)(CUtensorMap*, CUtensorMapDataType, cuuint32_t, void*, const cuuint64_t*, const cuuint64_t*,
                                  const cuuint32_t*, const cuuint32_t*, CUtensorMapInterleave, CUtensorMapSwizzle,
                                  CUtensorMapL2promotion, CUtensorMapFloatOOBfill);

static void make_map(EncodeTiledFn enc, CUtensorMap* m, const void* base, uint64_t cols, uint64_t rows, uint32_t box_rows,
                     CUtensorMapSwizzle sw = CU_TENSOR_MAP_SWIZZLE_128B, uint32_t box_cols = 64) {
    cuuint64_t dims[2] = {cols, rows};
    cuuint64_t str[1] = {cols * 2};
    cuuint32_t box[2] = {box_cols, box_rows};
    cuuint32_t es[2] = {1, 1};
    enc(m, CU_TENSOR_MAP_DATA_TYPE_BFLOAT16, 2, (void*)base, dims, str, box, es, CU_TENSOR_MAP_INTERLEAVE_NONE,
        sw, CU_TENSOR_MAP_L2_PROMOTION_L2_128B, CU_TENSOR_MAP_FLOAT_OOB_FILL_NONE);
}

static void make_map_chunks(EncodeTiledFn enc, CUtensorMap* m, const void* base, uint64_t rows, uint32_t box_rows, uint32_t n = 1) {
    cuuint64_t dims[3] = {64, rows, 8};
    cuuint64_t str[2] = {D_ * 2, 128};
    cuuint32_t box[3] = {64, box_rows, n};
    cuuint32_t es[3] = {1, 1, 1};
    enc(m, CU_TENSOR_MAP_DATA_TYPE_BFLOAT16, 3, (void*)base, dims, str, box, es, CU_TENSOR_MAP_INTERLEAVE_NONE,
        CU_TENSOR_MAP_SWIZZLE_128B, CU_TENSOR_MAP_L2_PROMOTION_L2_128B, CU_TENSOR_MAP_FLOAT_OOB_FILL_NONE);
}

static void make_map_out(EncodeTiledFn enc, CUtensorMap* m, const void* base) {
    cuuint64_t dims[4] = {D_, 4, 2, S_ / 8};
    cuuint64_t str[3] = {2 * D_ * 2, D_ * 2, 8 * D_ * 2};
    cuuint32_t box[4] = {64, 4, 2, 2};
    cuuint32_t es[4] = {1, 1, 1, 1};
    enc(m, CU_TENSOR_MAP_DATA_TYPE_BFLOAT16, 4, (void*)base, dims, str, box, es, CU_TENSOR_MAP_INTERLEAVE_NONE,
        CU_TENSOR_MAP_SWIZZLE_128B, CU_TENSOR_MAP_L2_PROMOTION_NONE, CU_TENSOR_MAP_FLOAT_OOB_FILL_NONE);
}

extern "C" void kernel_launch(void* const* d_in, const int* in_sizes, int n_in, void* d_out, int out_size) {
    (void)in_sizes; (void)n_in; (void)out_size;
    static EncodeTiledFn enc = nullptr;
    static bool fused_ok = false;
    static void* scratch = nullptr;
    if (!enc) {
        void* fn = nullptr;
        cudaDriverEntryPointQueryResult q;
        cudaGetDriverEntryPoint("cuTensorMapEncodeTiled", &fn, cudaEnableDefault, &q);
        enc = (EncodeTiledFn)fn;
        cudaGetSymbolAddress(&scratch, g_s);
        cudaFuncSetAttribute(fused_kernel, cudaFuncAttributeMaxDynamicSharedMemorySize, SMEM_BYTES);
        int dev = 0, nsm = 0, ncl = 0;
        cudaGetDevice(&dev);
        cudaDeviceGetAttribute(&nsm, cudaDevAttrMultiProcessorCount, dev);
        cudaLaunchConfig_t cfg = {};
        cfg.gridDim = dim3(132); cfg.blockDim = dim3(NTHREADS); cfg.dynamicSmemBytes = SMEM_BYTES;
        cudaLaunchAttribute at;
        at.id = cudaLaunchAttributeClusterDimension;
        at.val.clusterDim.x = 2; at.val.clusterDim.y = 1; at.val.clusterDim.z = 1;
        cfg.attrs = &at; cfg.numAttrs = 1;
        fused_ok = cudaOccupancyMaxActiveClusters(&ncl, fused_kernel, &cfg) == cudaSuccess && nsm == 132 && ncl == 66;
        (void)cudaGetLastError();
    }
    if (!fused_ok) {
        const bf16* const* in = (const bf16* const*)d_in;
        fb_hidden<<<S_, D_, 0, cudaStreamPerThread>>>(in[0], in[3], in[4], in[10], in[6]);
        fb_ffn1<<<F_ / 128, 128, 0, cudaStreamPerThread>>>(in[0], in[7], in[8]);
        fb_ffn2<<<D_ / 64, 64, 0, cudaStreamPerThread>>>(in[9]);
        fb_seq<<<S_, D_, 0, cudaStreamPerThread>>>(in[0], in[1], in[2], (bf16*)d_out);
        return;
    }
    Params p;
    p.s = (Scratch*)scratch;
    p.x = (const bf16*)d_in[0];
    p.w_r = (const bf16*)d_in[6];
    p.wg = (const bf16*)d_in[7];
    p.wu = (const bf16*)d_in[8];
    p.wd = (const bf16*)d_in[9];
    p.gate_w = (const bf16*)d_in[10];
    p.out = (bf16*)d_out;
    make_map_chunks(enc, &p.mX1, d_in[0], S_, 64);
    make_map_chunks(enc, &p.mX2, d_in[0], S_, 64, 2);
    make_map(enc, &p.mCre, d_in[1], S_, S_, 128);
    make_map(enc, &p.mCim, d_in[2], S_, S_, 128);
    make_map_chunks(enc, &p.mDre, d_in[3], D_, 128);
    make_map_chunks(enc, &p.mDim, d_in[4], D_, 128);
    make_map(enc, &p.mAB, scratch, 64, 8 * 32 * 128, 64, CU_TENSOR_MAP_SWIZZLE_NONE);
    make_map_out(enc, &p.mOut, d_out);
    make_map(enc, &p.mWg, d_in[7], F_, D_, 64, CU_TENSOR_MAP_SWIZZLE_NONE, 32);
    make_map(enc, &p.mWu, d_in[8], F_, D_, 64, CU_TENSOR_MAP_SWIZZLE_NONE, 32);
    make_map(enc, &p.mWd, d_in[9], D_, F_, 8, CU_TENSOR_MAP_SWIZZLE_NONE, 256);
    fused_kernel<<<132, NTHREADS, SMEM_BYTES, cudaStreamPerThread>>>(p);
}
```

```cpp
#include <cuda_runtime.h>
#include <cuda.h>
#include <cuda_bf16.h>
#include <stdint.h>

typedef __nv_bfloat16 bf16;

constexpr int S_ = 2048, D_ = 512, F_ = 1792;
constexpr int NCTA = 128;
constexpr int NTHREADS = 512;
constexpr int NSTAGE = 6;
constexpr int REGION = 32768;
constexpr int FFN_CTAS = F_ / 16;
constexpr uint32_t SPIN_LIMIT = 1u << 22;
constexpr int PACE = 260;
constexpr int PACE0 = 100;
constexpr int A_GAP = 260;
constexpr int B_GAP = 280;
constexpr int LATE_GAP = 240;
constexpr int INIT_GAP = 360;
constexpr int INIT_NS = 300;
constexpr int PF_T0 = 3000;
constexpr int PF_GAP = 850;
constexpr int PF_N0 = 4;
constexpr int FFN_S0 = 4;
constexpr int FFN_W = 7;
constexpr int ROUTER_C = 4;
constexpr int HINT_AT = 5;
constexpr int SUM_T0 = 15000;
constexpr int PS1 = 24;
constexpr int NA = 3;
constexpr int KEY_NS = 300;
constexpr int HSK = 2;

constexpr int OFF_MISC = 7 * REGION;
constexpr int B_F = OFF_MISC;
constexpr int B_G1 = B_F + 64;
constexpr int B_G4 = B_G1 + 8;
constexpr int B_XE = B_G4 + 8;
constexpr int B_GO1 = B_XE + 8;
constexpr int B_GO0 = B_GO1 + 8;
constexpr int B_EPOCH = B_GO0 + 8;
constexpr int B_RETRY = B_EPOCH + 8;
constexpr int B_INIT = B_RETRY + 8;
constexpr int B_FULL = B_INIT + 8;
constexpr int B_EMPTY = B_FULL + 48;
constexpr int B_PUB = B_EMPTY + 48;
constexpr int B_FREE = B_PUB + 8;
constexpr int B_BL = B_FREE + 24;
constexpr int B_TAIL = B_BL + 48;
constexpr int B_HX = B_TAIL + 8;
constexpr int B_FFN = B_HX + 8;
constexpr int B_ROLE = B_FFN + 40;
constexpr int B_EARLY = B_ROLE + 8;
constexpr int B_GATE = B_EARLY + 8;
constexpr int B_G2 = B_GATE + 8;
constexpr int B_LOW = B_G2 + 8;
constexpr int B_G0 = B_LOW + 8;
constexpr int M_EPOCH = B_G0 + 8;
constexpr int M_ROLE = M_EPOCH + 4;
constexpr int M_KEY = OFF_MISC + 416;
constexpr int M_HX = OFF_MISC + 512;
constexpr int M_G = M_HX + 1024;
constexpr int M_XS = M_G + 512;
constexpr int SMEM_BYTES = 232448;
static_assert(M_ROLE + 4 <= M_KEY && M_XS + 512 <= SMEM_BYTES, "smem");

struct Scratch {
    unsigned char ab[8 * 32 * 16384];
    unsigned int pair[65 * 32];
    unsigned int ready[16 * 32];
    unsigned int gate[S_];
    unsigned int part[FFN_CTAS / 2 * D_];
    unsigned int phint[4 * 16 * 8];
    unsigned int keys[8 * NCTA];
};
__device__ __align__(1024) Scratch g_s;

struct Params {
    Scratch* s;
    bf16* out;
    const bf16 *x, *gate_w, *w_r, *wg, *wu, *wd;
    CUtensorMap mDre, mDim, mX1, mX2, mCre, mCim, mAB, mOut, mWg, mWu, mWd;
};

#define ELECT "{.reg .pred p; elect.sync _|p, 0xffffffff; @p "
__device__ __forceinline__ uint32_t smem_u32(const void* p) { return (uint32_t)__cvta_generic_to_shared(p); }
__device__ __forceinline__ uint32_t clk() { return (uint32_t)clock64(); }
__device__ __forceinline__ void spin_until(uint32_t t) { while ((int)(clk() - t) < 0) {} }
template <int NS>
__device__ __forceinline__ void sleep_until(uint32_t t) { while ((int)(clk() - t) < 0) __nanosleep(NS); }
__device__ __forceinline__ void mbar_init_elect(uint32_t bar, uint32_t cnt) {
    asm volatile(ELECT "mbarrier.init.shared::cta.b64 [%0], %1;}" ::"r"(bar), "r"(cnt) : "memory");
}
__device__ __forceinline__ void mbar_expect_tx_elect(uint32_t bar, uint32_t bytes) {
    asm volatile(ELECT "mbarrier.arrive.expect_tx.shared::cta.b64 _, [%0], %1;}" ::"r"(bar), "r"(bytes) : "memory");
}
template <int N = 1>
__device__ __forceinline__ void mbar_arrive_elect(uint32_t bar) {
    asm volatile(ELECT "mbarrier.arrive.shared::cta.b64 _, [%0], %1;}" ::"r"(bar), "n"(N) : "memory");
}
__device__ __forceinline__ void mbar_arrive_if(uint32_t bar, bool pred) {
    asm volatile("{.reg .pred p; setp.ne.b32 p, %1, 0; @p mbarrier.arrive.shared::cta.b64 _, [%0];}" ::"r"(bar), "r"((int)pred) : "memory");
}
__device__ __forceinline__ void mbar_arrive_warp(uint32_t bar) {
    __syncwarp();
    mbar_arrive_if(bar, (threadIdx.x & 31) == 0);
}
template <int N>
__device__ __forceinline__ void release_pair(uint32_t bar, uint32_t rbar, bool pred) {
    asm volatile("{.reg .pred p; setp.ne.b32 p, %2, 0; @p mbarrier.arrive.shared::cta.b64 _, [%0], %3;"
                 " @p mbarrier.arrive.shared::cluster.b64 _, [%1], %3;}" ::"r"(bar), "r"(rbar), "r"((int)pred), "n"(N) : "memory");
}
__device__ __forceinline__ uint32_t mapa(uint32_t a, uint32_t cta) {
    uint32_t r;
    asm volatile("mapa.shared::cluster.u32 %0, %1, %2;" : "=r"(r) : "r"(a), "r"(cta));
    return r;
}
__device__ __forceinline__ bool mbar_test(uint32_t bar, uint32_t parity) {
    uint32_t ok;
    asm volatile("{.reg .pred p; mbarrier.test_wait.parity.shared::cta.b64 p, [%1], %2; selp.u32 %0,1,0,p;}"
                 : "=r"(ok) : "r"(bar), "r"(parity) : "memory");
    return ok;
}
__device__ __forceinline__ void mbar_wait(uint32_t bar, uint32_t parity) {
    asm volatile("{.reg .pred p, q; .reg .u32 n; mov.u32 n, 0;\n"
                 "W%=: mbarrier.try_wait.parity.shared::cta.b64 p, [%0], %1;\n"
                 "add.u32 n, n, 1; setp.lt.and.u32 q, n, %2, !p; @q bra W%=; @!p trap;}" ::"r"(bar), "r"(parity), "n"(SPIN_LIMIT) : "memory");
}
__device__ __forceinline__ void mbar_wait_cluster(uint32_t bar, uint32_t parity) {
    asm volatile("{.reg .pred p, q; .reg .u32 n; mov.u32 n, 0;\n"
                 "W%=: mbarrier.try_wait.parity.acquire.cluster.shared::cta.b64 p, [%0], %1;\n"
                 "add.u32 n, n, 1; setp.lt.and.u32 q, n, %2, !p; @q bra W%=; @!p trap;}" ::"r"(bar), "r"(parity), "n"(SPIN_LIMIT) : "memory");
}
__device__ __forceinline__ void mbar_spin(uint32_t bar, uint32_t parity) {
    asm volatile("{.reg .pred p;\nW%=: mbarrier.try_wait.parity.shared::cta.b64 p, [%0], %1; @!p bra W%=;}" ::"r"(bar), "r"(parity) : "memory");
}
__device__ __forceinline__ void cluster_arrive() { asm volatile("barrier.cluster.arrive.relaxed.aligned;" ::: "memory"); }
__device__ __forceinline__ void cluster_wait() { asm volatile("barrier.cluster.wait.acquire.aligned;" ::: "memory"); }
__device__ __forceinline__ void side_bar() { asm volatile("bar.sync 1, 128;" ::: "memory"); }
__device__ __forceinline__ void tma2d_elect(uint32_t dst, const CUtensorMap* m, int c0, int c1, uint32_t bar) {
    asm volatile(ELECT "cp.async.bulk.tensor.2d.shared::cluster.global.mbarrier::complete_tx::bytes [%0], [%1, {%3,%4}], [%2];}"
                 ::"r"(dst), "l"(m), "r"(bar), "r"(c0), "r"(c1) : "memory");
}
__device__ __forceinline__ void tma2d_pair_elect(uint32_t dst, const CUtensorMap* m, int c0, int c1, uint32_t bar) {
    asm volatile(ELECT "cp.async.bulk.tensor.2d.shared::cluster.global.mbarrier::complete_tx::bytes.multicast::cluster"
                 " [%0], [%1, {%3,%4}], [%2], %5;}" ::"r"(dst), "l"(m), "r"(bar), "r"(c0), "r"(c1), "h"((uint16_t)3) : "memory");
}
__device__ __forceinline__ void tma3d_elect(uint32_t dst, const CUtensorMap* m, int row, int chunk, uint32_t bar) {
    asm volatile(ELECT "cp.async.bulk.tensor.3d.shared::cluster.global.mbarrier::complete_tx::bytes [%0], [%1, {%3,%4,%5}], [%2];}"
                 ::"r"(dst), "l"(m), "r"(bar), "r"(0), "r"(row), "r"(chunk) : "memory");
}
__device__ __forceinline__ void bulk_wait_read() {
    asm volatile("cp.async.bulk.commit_group; cp.async.bulk.wait_group.read 0;" ::: "memory");
    __syncwarp();
}
__device__ __forceinline__ void fence_proxy_async_smem() { asm volatile("fence.proxy.async.shared::cta;" ::: "memory"); }
__device__ __forceinline__ uint32_t ld_relaxed(const void* p) {
    uint32_t v;
    asm volatile("ld.relaxed.gpu.global.u32 %0, [%1];" : "=r"(v) : "l"(p) : "memory");
    return v;
}
__device__ __forceinline__ uint4 ld_relaxed4(const void* p) {
    uint4 v;
    asm volatile("ld.relaxed.gpu.global.v4.u32 {%0,%1,%2,%3}, [%4];" : "=r"(v.x), "=r"(v.y), "=r"(v.z), "=r"(v.w) : "l"(p) : "memory");
    return v;
}
__device__ __forceinline__ void red_inc_if(unsigned int* p, bool pred) {
    asm volatile("{.reg .pred p; setp.ne.b32 p, %1, 0; @p red.relaxed.gpu.global.add.u32 [%0], 1;}" ::"l"(p), "r"((int)pred) : "memory");
}
__device__ __forceinline__ uint32_t tagf(float v, uint32_t par) { return (__float_as_uint(v) & ~1u) | par; }
__device__ __forceinline__ uint4 wait_tags(const unsigned int* p, int bit, uint32_t par) {
    uint32_t n = 0;
    while (true) {
        const uint4 v = ld_relaxed4(p);
        const uint32_t m = par ? (v.x & v.y & v.z & v.w) : ~(v.x | v.y | v.z | v.w);
        if (__all_sync(0xffffffffu, (m >> bit) & 1u)) return v;
        __nanosleep(100);
        if (++n > SPIN_LIMIT) __trap();
    }
}
__device__ __forceinline__ void wait_counter(const unsigned int* p, uint32_t want) {
    uint32_t n = 0;
    while (!__all_sync(0xffffffffu, (int)(ld_relaxed(p) - want) >= 0)) {
        __nanosleep(200);
        if (++n > SPIN_LIMIT) __trap();
    }
    asm volatile("fence.acquire.gpu;" ::: "memory");
}
__device__ __forceinline__ uint32_t stale_tags(uint32_t a, uint32_t par) {
    uint32_t r;
    asm volatile("{.reg .b32 v<16>;\n"
                 "ld.shared.u32 v0, [%1]; ld.shared.u32 v1, [%1+256]; ld.shared.u32 v2, [%1+512]; ld.shared.u32 v3, [%1+768];\n"
                 "ld.shared.u32 v4, [%1+4096]; ld.shared.u32 v5, [%1+4352]; ld.shared.u32 v6, [%1+4608]; ld.shared.u32 v7, [%1+4864];\n"
                 "ld.shared.u32 v8, [%1+8192]; ld.shared.u32 v9, [%1+8448]; ld.shared.u32 v10, [%1+8704]; ld.shared.u32 v11, [%1+8960];\n"
                 "ld.shared.u32 v12, [%1+12288]; ld.shared.u32 v13, [%1+12544]; ld.shared.u32 v14, [%1+12800]; ld.shared.u32 v15, [%1+13056];\n"
                 "lop3.b32 v0, v0, v1, %2, 0x7e; lop3.b32 v2, v2, v3, %2, 0x7e; lop3.b32 v4, v4, v5, %2, 0x7e; lop3.b32 v6, v6, v7, %2, 0x7e;\n"
                 "lop3.b32 v8, v8, v9, %2, 0x7e; lop3.b32 v10, v10, v11, %2, 0x7e; lop3.b32 v12, v12, v13, %2, 0x7e; lop3.b32 v14, v14, v15, %2, 0x7e;\n"
                 "lop3.b32 v0, v0, v2, v4, 0xfe; lop3.b32 v6, v6, v8, v10, 0xfe; lop3.b32 v0, v0, v6, v12, 0xfe; or.b32 %0, v0, v14;}"
                 : "=r"(r) : "r"(a), "r"(par) : "memory");
    return r;
}
template <int OFF>
__device__ __forceinline__ uint4 ldg_nc(const void* p) {
    uint4 v;
    asm volatile("ld.global.nc.v4.u32 {%0,%1,%2,%3}, [%4+%5];" : "=r"(v.x), "=r"(v.y), "=r"(v.z), "=r"(v.w) : "l"(p), "n"(OFF));
    return v;
}
template <int OFF>
__device__ __forceinline__ void stg128(void* p, const uint4& v) {
    asm volatile("st.global.v4.u32 [%0+%5], {%1,%2,%3,%4};" ::"l"(p), "r"(v.x), "r"(v.y), "r"(v.z), "r"(v.w), "n"(OFF) : "memory");
}
template <int OFF>
__device__ __forceinline__ void sts128(uint32_t a, const uint4& v) {
    asm volatile("st.shared.v4.u32 [%0+%5], {%1,%2,%3,%4};" ::"r"(a), "r"(v.x), "r"(v.y), "r"(v.z), "r"(v.w), "n"(OFF) : "memory");
}
__device__ __forceinline__ uint4 lds128(uint32_t a) {
    uint4 v;
    asm volatile("ld.shared.v4.u32 {%0,%1,%2,%3}, [%4];" : "=r"(v.x), "=r"(v.y), "=r"(v.z), "=r"(v.w) : "r"(a) : "memory");
    return v;
}
template <int OFF>
__device__ __forceinline__ void red_bf16x8(void* p, uint32_t x, uint32_t y, uint32_t z, uint32_t w) {
    asm volatile("red.relaxed.gpu.global.add.noftz.v4.bf16x2 [%0+%5], {%1,%2,%3,%4};"
                 ::"l"(p), "r"(x), "r"(y), "r"(z), "r"(w), "n"(OFF) : "memory");
}
__device__ __forceinline__ void sched_cut() {
    asm volatile("{.reg .pred p; .reg .u64 t; .reg .u32 a, b;\n"
                 "C%=: mov.u64 t, %%clock64; mov.b64 {a, b}, t; setp.eq.u32 p, a, %0; @p bra C%=;}" ::"n"(0) : "memory");
}
__device__ __forceinline__ uint32_t pin(uint32_t v) { return __shfl_xor_sync(0xffffffffu, v, 0); }
template <class T>
__device__ __forceinline__ T* pin(T* p) { return (T*)__shfl_xor_sync(0xffffffffu, (unsigned long long)p, 0); }
__device__ __forceinline__ float selpf(float a, float b, bool p) {
    float r;
    asm("{.reg .pred q; setp.ne.b32 q, %3, 0; selp.f32 %0, %1, %2, q;}" : "=f"(r) : "f"(a), "f"(b), "r"((int)p));
    return r;
}
template <int N, int MASK, int SZ>
__device__ __forceinline__ void halve(float (&a)[SZ]) {
    const bool up = threadIdx.x & MASK;
#pragma unroll
    for (int j = 0; j < N; j++) a[j] = selpf(a[N + j], a[j], up) + __shfl_xor_sync(0xffffffffu, selpf(a[j], a[N + j], up), MASK);
}
__device__ __forceinline__ float bflo(uint32_t u) { return __uint_as_float(u << 16); }
__device__ __forceinline__ float bfhi(uint32_t u) { return __uint_as_float(u & 0xffff0000u); }
__device__ __forceinline__ uint32_t pack_bf16(float lo, float hi) {
    uint32_t r;
    asm("cvt.rn.bf16x2.f32 %0, %1, %2;" : "=r"(r) : "f"(hi), "f"(lo));
    return r;
}
__device__ __forceinline__ uint32_t hmul2_bf16(uint32_t a, uint32_t b) {
    uint32_t r;
    asm("mul.rn.bf16x2 %0, %1, %2;" : "=r"(r) : "r"(a), "r"(b));
    return r;
}
__device__ __forceinline__ float rbf(float v) { return bflo(pack_bf16(v, 0.f)); }
__device__ __forceinline__ float sigmoidf_(float v) { return __fdividef(1.0f, 1.0f + __expf(-v)); }

__device__ __forceinline__ void wg_fence() { asm volatile("wgmma.fence.sync.aligned;" ::: "memory"); }
__device__ __forceinline__ void wg_commit() { asm volatile("wgmma.commit_group.sync.aligned;" ::: "memory"); }
template <int N> __device__ __forceinline__ void wg_wait() { asm volatile("wgmma.wait_group.sync.aligned %0;" ::"n"(N) : "memory"); }
__device__ __forceinline__ uint64_t desc128(uint32_t lo) { return (uint64_t)lo | (0x40000040ull << 32); }
__device__ __forceinline__ uint64_t desc64(uint32_t lo) { return (uint64_t)lo | (0x80000020ull << 32); }
__device__ __forceinline__ void fence_regs(float (&d)[64]) {
#pragma unroll
    for (int i = 0; i < 64; i++) asm volatile("" : "+f"(d[i])::"memory");
}
template <int TB>
__device__ __forceinline__ void wgmma128(float (&d)[64], uint64_t da, uint64_t db, int scaleD) {
    asm volatile(
        "{ .reg .pred p; setp.ne.b32 p, %66, 0;\n"
        "wgmma.mma_async.sync.aligned.m64n128k16.f32.bf16.bf16 "
        "{%0,%1,%2,%3,%4,%5,%6,%7,%8,%9,%10,%11,%12,%13,%14,%15,%16,%17,%18,%19,%20,%21,%22,%23,%24,%25,%26,%27,%28,%29,%30,%31,"
        "%32,%33,%34,%35,%36,%37,%38,%39,%40,%41,%42,%43,%44,%45,%46,%47,%48,%49,%50,%51,%52,%53,%54,%55,%56,%57,%58,%59,%60,%61,%62,%63}, "
        "%64, %65, p, 1, 1, 0, %67;\n}"
        : "+f"(d[0]), "+f"(d[1]), "+f"(d[2]), "+f"(d[3]), "+f"(d[4]), "+f"(d[5]), "+f"(d[6]), "+f"(d[7]),
          "+f"(d[8]), "+f"(d[9]), "+f"(d[10]), "+f"(d[11]), "+f"(d[12]), "+f"(d[13]), "+f"(d[14]), "+f"(d[15]),
          "+f"(d[16]), "+f"(d[17]), "+f"(d[18]), "+f"(d[19]), "+f"(d[20]), "+f"(d[21]), "+f"(d[22]), "+f"(d[23]),
          "+f"(d[24]), "+f"(d[25]), "+f"(d[26]), "+f"(d[27]), "+f"(d[28]), "+f"(d[29]), "+f"(d[30]), "+f"(d[31]),
          "+f"(d[32]), "+f"(d[33]), "+f"(d[34]), "+f"(d[35]), "+f"(d[36]), "+f"(d[37]), "+f"(d[38]), "+f"(d[39]),
          "+f"(d[40]), "+f"(d[41]), "+f"(d[42]), "+f"(d[43]), "+f"(d[44]), "+f"(d[45]), "+f"(d[46]), "+f"(d[47]),
          "+f"(d[48]), "+f"(d[49]), "+f"(d[50]), "+f"(d[51]), "+f"(d[52]), "+f"(d[53]), "+f"(d[54]), "+f"(d[55]),
          "+f"(d[56]), "+f"(d[57]), "+f"(d[58]), "+f"(d[59]), "+f"(d[60]), "+f"(d[61]), "+f"(d[62]), "+f"(d[63])
        : "l"(da), "l"(db), "r"(scaleD), "n"(TB));
}

__device__ __forceinline__ uint32_t get_role(uint32_t& smid) {
    uint32_t role;
    asm volatile("mov.u32 %0, %%smid;" : "=r"(smid));
    asm("{.reg .pred p, q; .reg .u32 t, a, b; shr.u32 t, %1, 1; mad.lo.u32 a, t, 293, -928; shr.u32 a, a, 8; mad.lo.u32 b, t, 8, -464;"
        " setp.lt.u32 p, t, 32; setp.lt.u32 q, t, 62; selp.u32 a, a, b, q; selp.u32 %0, t, a, p;}" : "=r"(role) : "r"(smid));
    return role;
}
__device__ __forceinline__ int tile_of_step(int step, int own) {
    const int u = step >= 17 ? step - 17 - (step > PS1) : step - 2;
    int e = u + (u >= (own & 14) ? 2 : 0);
    if (step == 16 || step == PS1) e = own ^ 1;
    if (step < 2) e = own;
    return e + (step >= 17 || step == 1 ? 16 : 0);
}
__device__ __forceinline__ uint32_t router_key(float score, int row) {
    const float r = score + 0.0f;
    uint32_t u = pack_bf16(r, 0.f) & 0xffffu;
    u = (u & 0x8000u) ? (~u & 0xffffu) : (u | 0x8000u);
    if (r != r) u = 0;
    return (u << 16) | (uint32_t)(0x7fff - row);
}

#define g_fb_h ((float*)g_s.part)
#define g_fb_upd (g_fb_h + 2048)
#define g_fb_gate (g_fb_h + 4096)
#define g_fb_keys (g_s.part + 8192)
__global__ void fb_hidden(const bf16* x, const bf16* dre, const bf16* dim, const bf16* gw, const bf16* wr) {
    __shared__ float xs[D_];
    const int s = blockIdx.x, t = threadIdx.x;
    xs[t] = __bfloat162float(x[s * D_ + t]);
    __syncthreads();
    float a = 0.f, b = 0.f;
    for (int d = 0; d < D_; d++) { a = fmaf(xs[d], __bfloat162float(dre[t * D_ + d]), a); b = fmaf(xs[d], __bfloat162float(dim[t * D_ + d]), b); }
    ((bf16*)g_s.ab)[s * 1024 + t] = __float2bfloat16(a);
    ((bf16*)g_s.ab)[s * 1024 + 512 + t] = __float2bfloat16(b);
    if (t == 0) {
        float u = 0.f, v = 0.f;
        for (int d = 0; d < D_; d++) { u = fmaf(xs[d], __bfloat162float(gw[d]), u); v = fmaf(xs[d], __bfloat162float(wr[d]), v); }
        g_fb_gate[s] = sigmoidf_(u);
        g_fb_keys[s] = router_key(v, s);
    }
}
__device__ uint32_t fb_best() {
    uint32_t k = 0;
    for (int i = 0; i < S_; i++) k = max(k, g_fb_keys[i]);
    return k;
}
__global__ void fb_ffn1(const bf16* x, const bf16* wg, const bf16* wu) {
    const int f = blockIdx.x * blockDim.x + threadIdx.x, idx = 0x7fff - (int)(fb_best() & 0x7fffu);
    float a = 0.f, b = 0.f;
    for (int d = 0; d < D_; d++) {
        const float xv = __bfloat162float(x[idx * D_ + d]);
        a = fmaf(xv, __bfloat162float(wg[d * F_ + f]), a); b = fmaf(xv, __bfloat162float(wu[d * F_ + f]), b);
    }
    g_fb_h[f] = a * sigmoidf_(a) * b;
}
__global__ void fb_ffn2(const bf16* wd) {
    const int e = blockIdx.x * blockDim.x + threadIdx.x;
    const uint32_t u = fb_best() >> 16, rb = (u & 0x8000u) ? (u & 0x7fffu) : (~u & 0xffffu);
    float a = 0.f;
    for (int f = 0; f < F_; f++) a = fmaf(g_fb_h[f], __bfloat162float(wd[f * D_ + e]), a);
    g_fb_upd[e] = a * sigmoidf_(__uint_as_float(rb << 16));
}
__global__ void fb_seq(const bf16* x, const bf16* cre, const bf16* cim, bf16* out) {
    __shared__ float c[2][S_];
    __shared__ int idx;
    const int t = blockIdx.x, e = threadIdx.x;
    for (int i = e; i < S_; i += D_) { c[0][i] = __bfloat162float(cre[t * S_ + i]); c[1][i] = __bfloat162float(cim[t * S_ + i]); }
    if (e == 0) idx = 0x7fff - (int)(fb_best() & 0x7fffu);
    __syncthreads();
    float y = 0.f;
    for (int s = 0; s < S_; s++)
        y += c[0][s] * __bfloat162float(((const bf16*)g_s.ab)[s * 1024 + e]) - c[1][s] * __bfloat162float(((const bf16*)g_s.ab)[s * 1024 + 512 + e]);
    const float g = g_fb_gate[t];
    out[t * D_ + e] = __float2bfloat16(g * y + (1.f - g) * (__bfloat162float(x[t * D_ + e]) + (t == idx ? g_fb_upd[e] : 0.f)));
}

__device__ __forceinline__ void spare_job(const Params& p, unsigned char* smem, int sp, uint32_t tstart) {
    const int tid = threadIdx.x, warp = tid >> 5, lane = tid & 31;
    const uint32_t e1 = *(volatile unsigned int*)&p.s->pair[64 * 32 + sp] + 1u;
    const uint32_t par = e1 & 1u;
    uint32_t* sel = (uint32_t*)smem;
    float* acc = (float*)(smem + 1024);
    __syncthreads();
    if (tid == 0) *(volatile unsigned int*)&p.s->pair[64 * 32 + sp] = e1;
    sleep_until<500>(tstart + SUM_T0);
    if (warp < 14) {
        uint32_t n = 0;
        while ((int)(ld_relaxed(p.s->phint + (sp * 16 + warp) * 8) - e1 * 8u) < 0) {
            __nanosleep(100);
            if (++n > SPIN_LIMIT) __trap();
        }
        const unsigned int* src = p.s->part + warp * 4 * D_ + sp * 128 + lane * 4;
        uint4 v[4];
        while (true) {
            uint32_t bad = 0;
#pragma unroll
            for (int i = 0; i < 4; i++) v[i] = ld_relaxed4(src + i * D_);
#pragma unroll
            for (int i = 0; i < 4; i++) bad |= (v[i].x ^ par) | (v[i].y ^ par) | (v[i].z ^ par) | (v[i].w ^ par);
            if (!__any_sync(0xffffffffu, bad & 1u)) break;
            if (++n > SPIN_LIMIT) __trap();
        }
        float4 s = make_float4(0.f, 0.f, 0.f, 0.f);
#pragma unroll
        for (int i = 0; i < 4; i++) {
            s.x += __uint_as_float(v[i].x); s.y += __uint_as_float(v[i].y);
            s.z += __uint_as_float(v[i].z); s.w += __uint_as_float(v[i].w);
        }
        *(float4*)&acc[warp * 128 + lane * 4] = s;
    } else if (warp == 14) {
        const uint4 k4 = wait_tags(p.s->keys + lane * 4, 15, par);
        const uint32_t k = __reduce_max_sync(0xffffffffu, max(max(k4.x, k4.y), max(k4.z, k4.w)));
        const int idx = 0x7fff - (int)(k & 0x7fffu);
        const uint4 g4 = wait_tags(p.s->gate + (idx & ~3), 0, par);
        const uint32_t gw = (idx & 2) ? ((idx & 1) ? g4.w : g4.z) : ((idx & 1) ? g4.y : g4.x);
        const uint32_t u = k >> 16;
        const uint32_t rb = (u & 0x8000u) ? (u & 0x7fffu) : (~u & 0xffffu);
        const float og = 1.f - __uint_as_float(gw & ~1u), rs = sigmoidf_(__uint_as_float(rb << 16));
        if (lane == 0) { sel[0] = idx; sel[1] = pack_bf16(og, og); sel[2] = pack_bf16(rs, rs); }
        sleep_until<500>(tstart + SUM_T0 + 3000);
        wait_counter(p.s->ready + (idx >> 7) * 32, e1 * 8u);
    }
    __syncthreads();
    if (tid < 64) {
        float t0 = 0.f, t1 = 0.f;
#pragma unroll
        for (int i = 0; i < 14; i++) {
            const float2 z = *(const float2*)&acc[i * 128 + tid * 2];
            t0 += z.x; t1 += z.y;
        }
        asm volatile("red.relaxed.gpu.global.add.noftz.bf16x2 [%0], %1;" ::"l"(p.out + sel[0] * D_ + sp * 128 + tid * 2),
                     "r"(hmul2_bf16(sel[1], hmul2_bf16(sel[2], pack_bf16(t0, t1)))) : "memory");
    }
}

__host__ __device__ constexpr int off_d(int c) { return (c < 2 ? 1 : c / 2 + 2) * REGION + (c & 1) * 16384; }
__host__ __device__ constexpr int off_xe(int c) { return (c < 2 ? 6 * REGION : c < 4 ? 16384 : c < 6 ? 0 : 6 * REGION + 16384) + (c & 1) * 8192; }
__host__ __device__ constexpr int off_xl(int c) { return c < 4 ? 2 * REGION + c * 8192 : off_xe(c - 4); }

__global__ void __cluster_dims__(2, 1, 1) __launch_bounds__(NTHREADS, 1)
fused_kernel(const __grid_constant__ Params p) {
    extern __shared__ __align__(1024) unsigned char smem[];
    const uint32_t tstart = clk();
    const uint32_t sb = smem_u32(smem);
    const int tid = threadIdx.x, lane = tid & 31;
    const int rank = blockIdx.x & 1;
    uint32_t t1 = 0;
    if (__any_sync(0xffffffffu, tid == 0)) {
        uint32_t s0;
        const uint32_t r0 = get_role(s0);
        mbar_init_elect(sb + B_F, 1);
        if (r0 < 64) {
#pragma unroll
            for (int c = 0; c < 2; c++) {
                if (c) {
                    spin_until(t1 + PACE);
                    mbar_init_elect(sb + B_F + 8, 1);
                }
                tma3d_elect(sb + off_d(c), &p.mDre + ((r0 >> 2) & 1), (r0 & 24) * 16, c, sb + B_F + 8 * c);
                tma3d_elect(sb + off_xe(c), &p.mX1, (r0 & 3) * 256 + (r0 & 32) * 4 + rank * 64, c, sb + B_F + 8 * c);
                mbar_expect_tx_elect(sb + B_F + 8 * c, 24576);
                if (!c) {
                    t1 = clk() + PACE0;
                    mbar_init_elect(sb + B_G0, 1);
                    tma3d_elect(sb + off_xl(0), &p.mX1, (r0 & 3) * 256 + (r0 & 32) * 4 + rank * 64 + 1024, 0, sb + B_G0);
                    mbar_expect_tx_elect(sb + B_G0, 8192);
                }
            }
        }
    }
    const int warp = __shfl_sync(0xffffffffu, tid >> 5, 0);
    uint32_t smid;
    const uint32_t role = get_role(smid);
    const int gpc = role & 7;
    const int tn = (role >> 3) & 3;
    const int comp = gpc >> 2;
    const int own = (gpc & 3) * 4 + ((role >> 5) & 1) * 2 + rank;
    const int blk = comp * 4 + tn;
    const int cta = gpc * 16 + (role >> 3) * 2 + rank;
    const bool ffn = cta < FFN_CTAS;
    uint32_t epoch = 0;
    if (warp != 0) {
        const uint32_t b1 = sb + B_F + 8 * warp;
        mbar_init_elect(warp < 2 ? b1 + 360 : b1, 1);
        if (warp >= 2 && warp < 5) mbar_init_elect(b1 + 360, warp < 4 ? 1 : 4);
        mbar_init_elect(b1 + 120, warp < 7 ? 5 : warp < 14 ? 4 : warp - 12);
        mbar_init_elect(b1 + 240, 1);
        if (warp == 9 || warp == 15) mbar_expect_tx_elect(b1 + 240, warp == 9 ? 2048 : 4);
        asm volatile("fence.mbarrier_init.release.cluster;" ::: "memory");
        if (tid == 128 && role < 64) epoch = *(volatile unsigned int*)&p.s->pair[(blk * 8 + (own >> 1)) * 32 + rank];
    }
    if (role >= 64) {
        spare_job(p, smem, smid & 3, tstart);
        return;
    }
    __syncthreads();
    cluster_arrive();
    if (warp == 0) {
#pragma unroll
        for (int c = 2; c < 8; c++) {
            spin_until(t1 + c * PACE);
            tma3d_elect(sb + off_d(c), &p.mDre + comp, tn * 128, c, sb + B_F + 8 * c);
            tma3d_elect(sb + off_xe(c), &p.mX1, own * 64, c, sb + B_F + 8 * c);
            mbar_expect_tx_elect(sb + B_F + 8 * c, 24576);
        }
        tma3d_elect(sb + off_xl(1), &p.mX1, own * 64 + 1024, 1, sb + B_G1);
        mbar_expect_tx_elect(sb + B_G1, 8192);
        spin_until(t1 + 8 * PACE);
        tma3d_elect(sb + off_xl(2), &p.mX2, own * 64 + 1024, 2, sb + B_G2);
        mbar_expect_tx_elect(sb + B_G2, 16384);
        if (tn < 2)
            asm volatile(ELECT "cp.async.bulk.prefetch.tensor.3d.L2.global [%0, {%1,%2,%3}];}"
                         ::"l"(&p.mX2), "r"(0), "r"(own * 64 + 1024), "r"(4 + 2 * tn) : "memory");
    }

    if (warp < 4) {
        const int tab = tile_of_step(lane, own);
        const uint32_t bdst = sb + 16384 + rank * 8192;
        const int brow = blk * 4096 + rank * 64;
        if (warp == 0) {
            mbar_spin(sb + B_XE, 0);
            tma3d_elect(sb + off_xl(4), &p.mX2, own * 64 + 1024, 4, sb + B_G4);
            tma3d_elect(sb + off_xl(6), &p.mX2, own * 64 + 1024, 6, sb + B_G4);
            mbar_expect_tx_elect(sb + B_G4, 32768);
#define LOAD_A() const int e = __shfl_sync(0xffffffffu, tab, step);                                             \
                 const uint32_t bar = sb + 8 * slot;                                                            \
                 mbar_spin(bar + B_EMPTY, ph);                                                                  \
                 tma2d_elect(sb + slot * REGION, &p.mCre + comp, e * 64, own * 128, bar + B_FULL);              \
                 mbar_expect_tx_elect(bar + B_FULL, 16384)
            uint32_t slot = 0, ph = 0;
            int step = 0;
#pragma unroll 1
            for (int i = 0; i < NSTAGE; i++) {
                step = slot = i < 2 ? i ^ 1 : i;
                LOAD_A();
                if (i == 2 || i == 3) spin_until(clk() + A_GAP);
            }
            step = NSTAGE;
            slot = 0; ph = 1;
#pragma unroll 1
            for (int h = 0; h < 3; h++) {
                const int last = h == 0 ? 16 : h == 1 ? PS1 : 32 - NA;
#pragma unroll 1
                for (; step < last; step++) {
                    LOAD_A();
                    tma2d_pair_elect(bdst + slot * REGION, &p.mAB, 0, brow + e * 128, bar + B_BL);
                    mbar_expect_tx_elect(bar + B_BL, 16384);
                    if (++slot == NSTAGE) { slot = 0; ph ^= 1; }
                }
                if (h == 2) break;
                LOAD_A();
                tma2d_elect(bdst + slot * REGION, &p.mAB, 0, brow + e * 128, bar + B_BL);
                tma2d_elect((bdst ^ 8192) + slot * REGION, &p.mAB, 0, (brow ^ 64) + e * 128, bar + B_BL);
                mbar_expect_tx_elect(bar + B_BL, 16384);
                step++;
                if (++slot == NSTAGE) { slot = 0; ph ^= 1; }
            }
            mbar_spin(sb + B_LOW, 0);
            uint32_t aslot = 6;
#pragma unroll 1
            for (; step < 32; step++) {
                const int e = __shfl_sync(0xffffffffu, tab, step);
                const uint32_t bar = sb + 8 * slot;
                tma2d_elect(sb + aslot * REGION, &p.mCre + comp, e * 64, own * 128, bar + B_FULL);
                mbar_expect_tx_elect(bar + B_FULL, 16384);
                mbar_expect_tx_elect(bar + B_BL, 16384);
                mbar_spin(bar + B_EMPTY, ph);
                tma2d_pair_elect(bdst + slot * REGION, &p.mAB, 0, brow + e * 128, bar + B_BL);
                aslot = slot;
                if (++slot == NSTAGE) { slot = 0; ph ^= 1; }
            }
        } else if (warp == 1) {
            if (lane < 4) asm volatile("prefetch.tensormap [%0];" ::"l"(&p.mCre + lane) : "memory");
            __syncwarp();
            cluster_wait();
            if (lane == 0)
                asm volatile("st.async.weak.shared::cluster.mbarrier::complete_tx::bytes.u32 [%0], %1, [%2];"
                             ::"r"(mapa(sb + M_ROLE, rank ^ 1)), "r"(role), "r"(mapa(sb + B_ROLE, rank ^ 1)) : "memory");
            mbar_wait_cluster(sb + B_ROLE, 0);
            if (*(volatile uint32_t*)(smem + M_ROLE) != role) __trap();
            mbar_wait(sb + B_EPOCH, 0);
            const uint32_t want = (*(volatile uint32_t*)(smem + M_EPOCH) + 1u) * 4u;
            const int eh = __shfl_sync(0xffffffffu, tab, 2 + (lane & 3));
            const unsigned int* hp = p.s->pair + (blk * 8 + (eh >> 1)) * 32 + 2 + (eh & 1);
            uint32_t seen = 0;
            int rows[4];
#pragma unroll
            for (int i = 0; i < 4; i++) {
                rows[i] = brow + __shfl_sync(0xffffffffu, tab, 2 + i) * 128;
                mbar_expect_tx_elect(sb + B_BL + 8 * (2 + i), 16384);
            }
            mbar_wait(sb + B_EMPTY + 8 * 3, 0);
            mbar_spin(sb + B_EMPTY + 8 * 2, 0);
            uint32_t t3 = 0;
#pragma unroll
            for (int i = 0; i < 4; i++) {
                while (!((seen >> i) & 1u)) seen = __ballot_sync(0xffffffffu, ld_relaxed(hp) == want);
                if (i) spin_until(t3 + B_GAP);
                t3 = clk();
                if (i >= 2) mbar_spin(sb + B_EMPTY + 8 * (2 + i), 0);
                tma2d_pair_elect(bdst + (2 + i) * REGION, &p.mAB, 0, rows[i], sb + B_BL + 8 * (2 + i));
            }
            mbar_wait(sb + B_FREE, 0);
            unsigned char* gdst = p.s->ab + (blk * 32 + own + 16) * 16384;
            t3 = clk();
#pragma unroll 1
            for (int i = 0; i < 16; i++) {
                sleep_until<20>(t3);
                t3 += LATE_GAP;
                asm volatile(ELECT "cp.async.bulk.global.shared::cta.bulk_group [%0], [%1], 1024;}"
                             ::"l"(gdst + i * 1024), "r"(sb + 6 * REGION + i * 1024) : "memory");
            }
            bulk_wait_read();
            mbar_arrive_elect(sb + B_FREE + 8);
            mbar_wait(sb + B_PUB, 0);
            if (lane == 0) {
                asm volatile("fence.proxy.async.global;" ::: "memory");
                asm volatile("red.release.gpu.global.add.u32 [%0], 1;" ::"l"(p.s->ready + (cta >> 3) * 32) : "memory");
            }
            __syncwarp();
            __nanosleep(INIT_NS);
            wait_counter(p.s->ready + own * 32, want * 2u);
            mbar_arrive_elect(sb + B_INIT);
        } else {
            mbar_arrive_elect(sb + B_BL + 8 * (warp & 1));
            uint32_t k = warp == 3 ? 0 : 12;
#define PREFETCH_W() {                                                                                          \
                const char* src = (k >= 8 ? (const char*)p.wd + ((cta >> 5) * 2 + (k >> 1) - 4) * 229376        \
                                          : (const char*)((cta & 32) ? p.wu : p.wg) + ((cta >> 6) * 4 + (k >> 1)) * 229376) \
                                  + ((cta & 31) * 2 + (k & 1)) * 3584;                                          \
                asm volatile(ELECT "cp.async.bulk.prefetch.L2.global [%0], 3584;}" ::"l"(src) : "memory");      \
                k++; }
#pragma unroll 1
            while (k < PF_N0) {
                sleep_until<50>(tstart + PF_T0 + k * PF_GAP);
                __syncwarp();
                PREFETCH_W();
            }
            mbar_wait(sb + B_EPOCH, 0);
            const uint32_t par = (*(volatile uint32_t*)(smem + M_EPOCH) + 1u) & 1u;
            const uint32_t a0 = sb + 16384 + (lane >> 3) * 1028 + ((lane >> 2) & 1) * 144 + (lane & 3) * 32;
            const uint32_t retry = sb + B_RETRY + (warp & 1) * 240;
            uint32_t slot = warp, ph = 0, rph = 0;
            uint32_t j = ffn ? warp & 1 : 12;
#pragma unroll 1
            for (int step = warp; step < 32 || j < 12;) {
                const bool go = step < (j < 8 ? 32 - NA : 32);
                if (go) {
                    const uint32_t bar = sb + 8 * slot;
                    mbar_wait(bar + B_BL, ph);
#pragma unroll 1
                    while (__any_sync(0xffffffffu, stale_tags(a0 + slot * REGION, par) & 1u)) {
                        const int row = blk * 4096 + __shfl_sync(0xffffffffu, tab, step) * 128;
                        mbar_expect_tx_elect(retry, 16384);
                        tma2d_elect(sb + slot * REGION + 16384, &p.mAB, 0, row, retry);
                        tma2d_elect(sb + slot * REGION + 24576, &p.mAB, 0, row + 64, retry);
                        mbar_spin(retry, rph);
                        rph ^= 1u;
                    }
                    mbar_arrive_elect<4>(bar + B_FULL);
                }
                if (j < 12 && step >= FFN_S0 + j * FFN_W / 4 && __any_sync(0xffffffffu, mbar_test(sb + B_FREE + 2 * (j & 12), 0))) {
                    const uint32_t fb = sb + B_FFN + 4 * (j & 6);
                    if (!(j & 1)) mbar_expect_tx_elect(fb, 8192);
                    tma2d_elect(sb + 6 * REGION + ((j + 4) & 7) * 4096, j < 8 ? &p.mWg + (j & 1) : &p.mWd,
                                j < 8 ? (cta >> 1) * 32 : rank * 256, j < 8 ? rank * 256 + (j >> 1) * 64 : (cta >> 1) * 32 + j * 8 - 64, fb);
                    j += 2;
                }
                if (k < 12) PREFETCH_W();
                if (go) {
                    step += 2;
                    slot += 2;
                    if (slot >= NSTAGE) { slot -= NSTAGE; ph ^= 1; }
                }
            }
        }
    } else if (warp < 8) {
        const int t = tid - 128, w = warp - 4;
        if (t == 0) {
            *(volatile uint32_t*)(smem + M_EPOCH) = epoch;
            *(volatile unsigned int*)&p.s->pair[(blk * 8 + (own >> 1)) * 32 + rank] = epoch + 1;
        }
        mbar_arrive_if(sb + B_EPOCH, t == 0);
        const uint4 gw0 = ldg_nc<0>(p.gate_w + lane * 8), gw1 = ldg_nc<512>(p.gate_w + lane * 8);
        const uint4 rw0 = ldg_nc<0>(p.w_r + lane * 8), rw1 = ldg_nc<512>(p.w_r + lane * 8);
        mbar_wait(sb + B_EPOCH, 0);
        const uint32_t par = (*(volatile uint32_t*)(smem + M_EPOCH) + 1u) & 1u;
        mbar_wait(sb + B_F + 8 * ROUTER_C, 0);
        const int row0 = cta * 16 + w * 4;
        uint4 xr[8];
        {
            const char* xp = (const char*)p.x + (uint32_t)row0 * (D_ * 2) + lane * 16;
            xr[0] = ldg_nc<0>(xp);    xr[1] = ldg_nc<512>(xp);  xr[2] = ldg_nc<1024>(xp); xr[3] = ldg_nc<1536>(xp);
            xr[4] = ldg_nc<2048>(xp); xr[5] = ldg_nc<2560>(xp); xr[6] = ldg_nc<3072>(xp); xr[7] = ldg_nc<3584>(xp);
            float a[8];
#pragma unroll
            for (int i = 0; i < 4; i++) {
                const uint32_t xv[8] = {xr[2 * i].x, xr[2 * i].y, xr[2 * i].z, xr[2 * i].w,
                                        xr[2 * i + 1].x, xr[2 * i + 1].y, xr[2 * i + 1].z, xr[2 * i + 1].w};
                const uint32_t gv[8] = {gw0.x, gw0.y, gw0.z, gw0.w, gw1.x, gw1.y, gw1.z, gw1.w};
                const uint32_t rv[8] = {rw0.x, rw0.y, rw0.z, rw0.w, rw1.x, rw1.y, rw1.z, rw1.w};
                float u = 0.f, v = 0.f;
#pragma unroll
                for (int j = 0; j < 8; j++) {
                    const uint32_t pr = hmul2_bf16(xv[j], gv[j]);
                    u += bflo(pr); u += bfhi(pr);
                    v = fmaf(bflo(xv[j]), bflo(rv[j]), v); v = fmaf(bfhi(xv[j]), bfhi(rv[j]), v);
                }
                a[i] = u; a[4 + i] = v;
            }
            mbar_wait(sb + B_EARLY, 0);
            halve<4, 16>(a); halve<2, 8>(a); halve<1, 4>(a);
            a[0] += __shfl_xor_sync(0xffffffffu, a[0], 1);
            a[0] += __shfl_xor_sync(0xffffffffu, a[0], 2);
            const int row = row0 + ((lane >> 2) & 3);
            const float gate = rbf(sigmoidf_(rbf(a[0])));
            if (lane < 16 && (lane & 3) == 0)
                asm volatile("st.relaxed.gpu.global.u32 [%0], %1;" ::"l"(&p.s->gate[row]), "r"(tagf(gate, par)) : "memory");
            const uint32_t best = __reduce_max_sync(0xffffffffu, lane >= 16 ? router_key(a[0], row) : 0u);
            if (lane == 0) *(volatile uint32_t*)(smem + M_KEY + w * 4) = best;
            side_bar();
            if (t < 8) {
                const uint4 k = *(const uint4*)(smem + M_KEY);
                asm volatile("{.reg .b32 old; atom.relaxed.gpu.global.exch.b32 old, [%0], %1;}" ::"l"(&p.s->keys[t * NCTA + cta]),
                             "r"(max(max(k.x, k.y), max(k.z, k.w)) | (par << 15)) : "memory");
            }
            const uint32_t og = pack_bf16(1.f - gate, 1.f - gate);
#pragma unroll
            for (int i = 0; i < 8; i++) {
                const uint32_t o = __shfl_sync(0xffffffffu, og, 4 * (i >> 1));
                xr[i] = make_uint4(hmul2_bf16(o, xr[i].x), hmul2_bf16(o, xr[i].y), hmul2_bf16(o, xr[i].z), hmul2_bf16(o, xr[i].w));
            }
        }
        mbar_wait(sb + B_FREE, 0);
        __nanosleep(KEY_NS);
        if (w == 0) {
            const uint4 k4 = wait_tags(p.s->keys + gpc * NCTA + lane * 4, 15, par);
            const uint32_t k = __reduce_max_sync(0xffffffffu, max(max(k4.x, k4.y), max(k4.z, k4.w)));
            sts128<M_XS>(sb + lane * 16, ldg_nc<0>(p.x + (0x7fff - (k & 0x7fffu)) * D_ + rank * 256 + lane * 8));
        } else if (w == 1) {
            const uint4 g4 = wait_tags(p.s->gate + own * 128 + lane * 4, 0, par);
            const uint32_t sg = comp ? 0x80000000u : 0u;
            sts128<M_G>(sb + lane * 16, make_uint4((g4.x & ~1u) ^ sg, (g4.y & ~1u) ^ sg, (g4.z & ~1u) ^ sg, (g4.w & ~1u) ^ sg));
            mbar_arrive_warp(sb + B_GATE);
        }
        side_bar();
        char* op = (char*)p.out + (uint32_t)row0 * (D_ * 2) + lane * 16;
        float a[16];
#pragma unroll
        for (int i = 0; i < 16; i++) a[i] = 0.f;
#pragma unroll 1
        for (int i = 0; i < 4; i++) {
            if (i == 2) {
                mbar_wait(sb + B_FREE + 8, 0);
                const uint32_t t2 = clk() + w * (INIT_GAP / 4);
#pragma unroll
                for (int j = 0; j < 8; j++) {
                    sleep_until<20>(t2 + j * INIT_GAP);
                    *(uint4*)(op + j * 512) = xr[j];
                }
                mbar_arrive_warp(sb + B_PUB);
            }
            if (ffn) {
                const float xs0 = __bfloat162float(((const bf16*)(smem + M_XS))[64 * i + (t >> 2)]);
                const float xs1 = __bfloat162float(((const bf16*)(smem + M_XS))[64 * i + 32 + (t >> 2)]);
                const uint32_t wa = sb + 6 * REGION + (i ^ 2) * 8192 + t * 16;
                mbar_wait(sb + B_FFN + 8 * i, 0);
                const uint4 v0 = lds128(wa), v1 = lds128(wa + 4096), v2 = lds128(wa + 2048), v3 = lds128(wa + 6144);
                const uint32_t w0[8] = {v0.x, v0.y, v0.z, v0.w, v1.x, v1.y, v1.z, v1.w};
                const uint32_t w1[8] = {v2.x, v2.y, v2.z, v2.w, v3.x, v3.y, v3.z, v3.w};
#pragma unroll
                for (int k = 0; k < 8; k++) {
                    a[2 * k] = fmaf(xs1, bflo(w1[k]), fmaf(xs0, bflo(w0[k]), a[2 * k]));
                    a[2 * k + 1] = fmaf(xs1, bfhi(w1[k]), fmaf(xs0, bfhi(w0[k]), a[2 * k + 1]));
                }
                if (i == 1) {
                    side_bar();
                    mbar_arrive_if(sb + B_FREE + 16, t == 0);
                }
            }
        }
        if (!ffn) {
            mbar_arrive_warp(sb + B_LOW);
            return;
        }
        halve<8, 16>(a); halve<4, 8>(a); halve<2, 4>(a);
        const uint32_t ho = (lane >> 4) * 128 + (lane & 3) * 32 + ((lane >> 2) & 3) * 8;
        cluster_wait();
#pragma unroll
        for (int k = 0; k < 2; k++)
            asm volatile("st.async.weak.shared::cluster.mbarrier::complete_tx::bytes.v2.f32 [%0], {%1,%2}, [%3];"
                         ::"r"(mapa(sb + (k ? 6 * REGION + w * 512 : M_HX + w * 256) + ho, rank ^ k ^ 1)), "f"(a[0]), "f"(a[1]),
                           "r"(mapa(sb + B_HX, rank ^ k ^ 1)) : "memory");
        mbar_wait_cluster(sb + B_HX, 0);
        const float *hx = (const float*)(smem + M_HX) + lane, *hy = (const float*)(smem + 6 * REGION) + lane;
        const float gs = rbf(((hx[0] + hy[0]) + (hx[64] + hy[128])) + ((hx[128] + hy[256]) + (hx[192] + hy[384])));
        const float us = rbf(((hx[32] + hy[32]) + (hx[96] + hy[160])) + ((hx[160] + hy[288]) + (hx[224] + hy[416])));
        float* hrow = (float*)(smem + M_XS) + w * 32;
        hrow[lane] = rbf(rbf(gs * sigmoidf_(gs)) * us);
        fence_proxy_async_smem();
        mbar_arrive_warp(sb + B_LOW);
        float o0 = 0.f, o1 = 0.f;
#pragma unroll 1
        for (int i = 0; i < 2; i++) {
            float4 hv[4];
            uint32_t vd[16];
#pragma unroll
            for (int k = 0; k < 4; k++) hv[k] = *(const float4*)&hrow[i * 16 + k * 4];
            mbar_wait(sb + B_FFN + 8 * i, 1);
#pragma unroll
            for (int k = 0; k < 16; k++) vd[k] = *(const volatile uint32_t*)(smem + 6 * REGION + 16384 + i * 8192 + k * 512 + t * 4);
#pragma unroll
            for (int k = 0; k < 4; k++) {
                o0 = fmaf(hv[k].x, bflo(vd[4 * k]), o0);     o1 = fmaf(hv[k].x, bfhi(vd[4 * k]), o1);
                o0 = fmaf(hv[k].y, bflo(vd[4 * k + 1]), o0); o1 = fmaf(hv[k].y, bfhi(vd[4 * k + 1]), o1);
                o0 = fmaf(hv[k].z, bflo(vd[4 * k + 2]), o0); o1 = fmaf(hv[k].z, bfhi(vd[4 * k + 2]), o1);
                o0 = fmaf(hv[k].w, bflo(vd[4 * k + 3]), o0); o1 = fmaf(hv[k].w, bfhi(vd[4 * k + 3]), o1);
            }
        }
        asm volatile("st.relaxed.gpu.global.v2.u32 [%0], {%1,%2};" ::"l"(&p.s->part[(cta >> 1) * D_ + rank * 256 + t * 2]),
                     "r"(tagf(o0, par)), "r"(tagf(o1, par)) : "memory");
        red_inc_if(p.s->phint + ((rank * 2 + (w >> 1)) * 16 + (cta >> 3)) * 8 + lane, lane == 0);
    } else {
        const int wg = (warp >> 2) - 2, wq = warp & 3;
        const uint32_t sbd = ((sb & 0x3FFFF) >> 4) + 0x10000;
        const bool lead = (tid & 127) == 0;
        const bool lead0 = lead && !wg, lead1 = lead && wg;
        const int q = lane & 3;
        float acc[64];
        const uint32_t rE = mapa(sb + B_EMPTY, rank ^ 1);
#define RELEASE(n, slot, pred) release_pair<n>(sb + B_EMPTY + 8 * (slot), rE + 8 * (slot), pred)
        const uint32_t ioff = wq * 4096 + (lane >> 2) * 64 + ((q ^ (lane >> 3)) << 4);
        const uint32_t sdst = pin(sb + 6 * REGION + (wg ? 0 : 16384) + ioff);
        unsigned char* gdst = pin(p.s->ab + (blk * 32 + own) * 16384 + ioff);
        unsigned int* hint = pin(p.s->pair + (blk * 8 + (own >> 1)) * 32 + 2 + rank + lane);
        uint32_t par = 0;
#define GET_PAR() mbar_spin(sb + B_EPOCH, 0); par = (*(volatile uint32_t*)(smem + M_EPOCH) + 1u) & 1u
        cluster_wait();
        if (wg) mbar_spin(sb + B_G0, 0);
#pragma unroll
        for (int c = 0; c < 8; c++) {
            if (c == 1 && wg) {
                wg_wait<0>();
                RELEASE(1, 1, lead);
                GET_PAR();
                mbar_spin(sb + B_G1, 0);
            }
            if (!wg || c < 3 || c == 4) mbar_spin(sb + (!wg || c == 0 ? B_F + 8 * c : c == 1 ? B_GO1 : c == 2 ? B_G2 : B_G4), 0);
            const uint32_t xa = sbd + wg * ((off_xl(c) - off_xe(c)) / 16);
            wg_fence();
#pragma unroll
            for (int kk = 0; kk < 4; kk++) {
                wgmma128<0>(acc, desc128(xa + off_xe(c) / 16 + 2 * kk), desc128(sbd + off_d(c) / 16 + 2 * kk), (c | kk) != 0);
                if (c == 7 && kk == 0) wg_commit();
            }
            wg_commit();
            if (c == 3 && !wg) { GET_PAR(); }
            if (c == 7) {
                if (wg) mbar_spin(sb + B_FULL, 0);
                wg_wait<2>();
                mbar_arrive_if(sb + B_GO1, lead0);
            }
            if (c == 4 || c >= 6) wg_wait<1>();
            if (c == 4) { mbar_arrive_if(sb + B_XE, lead0); RELEASE(1, 1, lead0); RELEASE(2, 2, lead1); RELEASE(2, 3, lead1); }
            if (c == 6) RELEASE(2, 4 * wg, lead);
            if (c == 7) mbar_arrive_if(sb + B_GO0, lead1);
        }
        const int rh = wg ^ comp;
        const uint32_t da0 = sbd + rh * 512, db0 = sbd - 0x10000 + 0x400000 + 1024;
        const uint32_t dbe = db0 + 6 * (REGION / 16), dbl = dbe - 1024;
#define STEP(da, db, first) wg_fence();                                                                     \
        _Pragma("unroll") for (int kk = 0; kk < 4; kk++)                                                    \
            wgmma128<1>(acc, desc128((da) + kk * 2), desc64((db) + kk * 256), !((first) && kk == 0));       \
        wg_commit()
#define ACC(i, j) (16 * ((i) >> 1) + 2 * ((i) & 1) + 4 * (j))
#define PW(i, j) pack_bf16(acc[ACC(i, j)], acc[ACC(i, j) + 1])
#define PT(i, j) ((j) == ((i) >> 1) ? (PW(i, j) & ~1u) | par : PW(i, j))
#define PIECE(i) make_uint4(PT(i, 0), PT(i, 1), PT(i, 2), PT(i, 3))
#define PIECES(F) F(0); F(1); sched_cut(); F(2); F(3); F(4); F(5); F(6); F(7)
        if (wg) {
            wg_wait<0>();
            fence_regs(acc);
#define STS1(i) sts128<(i) * 512>(sdst, PIECE(i))
            PIECES(STS1);
            STEP(da0, dbe, true);
            fence_proxy_async_smem();
            mbar_arrive_warp(sb + B_FULL + 8);
            RELEASE(1, 5, lead);
        } else {
            wg_wait<0>();
            fence_regs(acc);
            uint4 v[8];
#define STG0(i) v[i] = PIECE(i); stg128<(i) * 512>(gdst, v[i]); if (HINT_AT == (i) + 1) red_inc_if(hint, own < 6 && lane == 0)
            PIECES(STG0);
            mbar_spin(sb + B_EPOCH, 0);
            asm volatile("bar.sync 2, 128;" ::: "memory");
#define STS0(i) if ((i) % 2 == 0) mbar_spin(sb + B_EPOCH, 0); sts128<(i) * 512>(sdst, v[i])
            STS0(0); STS0(1); STS0(2); STS0(3); STS0(4); STS0(5); STS0(6); STS0(7);
            fence_proxy_async_smem();
            mbar_arrive_warp(sb + B_FULL);
            RELEASE(1, 5, lead);
            mbar_arrive_if(sb + B_EARLY, lead);
            mbar_spin(sb + B_FULL, 0);
            mbar_spin(sb + B_GO0, 0);
            STEP(da0, dbe, true);
        }
#pragma unroll
        for (int step = 1; step < 3; step++) {
            mbar_spin(sb + B_FULL + 8 * step, 0);
            STEP(da0 + step * (REGION / 16), step == 1 ? dbl : db0 + step * (REGION / 16), false);
            wg_wait<1>();
            RELEASE(1, step - 1, lead);
            mbar_arrive_if(sb + B_FREE + 8 * (step - 1), lead);
        }
        int slot = 3, ph = 0, pslot = 2;
        float g0 = 0.f, g1 = 0.f;
        uint32_t oa = 0;
#pragma unroll 1
        for (int step = 3; step < 26; step++) {
            mbar_wait(sb + B_FULL + 8 * slot, ph);
            STEP(da0 + slot * (REGION / 16), db0 + slot * (REGION / 16), false);
            if (step == 22 + wg) {
                const int r0 = rh * 64 + wq * 16 + (lane >> 2), sr = ((lane >> 2) & 1) * 4 + (lane >> 3);
                mbar_wait(sb + B_GATE, 0);
                g0 = ((const volatile float*)(smem + M_G))[r0];
                g1 = ((const volatile float*)(smem + M_G))[r0 + 8];
                oa = pin(wg ? ((own * 128 + (r0 & ~1)) * D_ + tn * 128 + (lane & 7) * 8) * 2u
                            : sb + rh * 8192 + wq * 2048 + sr * 128 + ((q ^ sr) << 4));
            }
            wg_wait<1>();
            RELEASE(1, pslot, lead);
            pslot = slot;
            if (++slot == NSTAGE) { slot = 0; ph ^= 1; }
        }
        mbar_wait(sb + B_FULL + 8 * 2, 0);
        wg_fence();
#pragma unroll
        for (int kk = 0; kk < 4; kk++) {
            if (kk == HSK) {
                wg_commit();
                if (wg) {
                    wg_wait<1>();
                    RELEASE(1, 1, lead);
                    mbar_wait(sb + B_INIT, 0);
                    mbar_wait(sb + B_TAIL, 0);
                }
                wg_fence();
            }
            wgmma128<1>(acc, desc128(da0 + 2 * (REGION / 16) + kk * 2), desc64(db0 + 2 * (REGION / 16) + kk * 256), 1);
        }
        wg_commit();
        if (!wg) {
            wg_wait<2>();
            RELEASE(1, 1, lead);
        }
        slot = 3;
#pragma unroll 1
        for (int step = 27; step < 32; step++) {
            if (!wg) mbar_wait(sb + B_FULL + 8 * slot, ph);
            STEP(da0 + (step < 32 - NA ? slot : step == 32 - NA ? 6 : pslot) * (REGION / 16), db0 + slot * (REGION / 16), false);
            pslot = slot;
            if (++slot == NSTAGE) { slot = 0; ph ^= 1; }
        }
#define OW(i, j) pack_bf16((((i) & 1) ? g1 : g0) * acc[ACC(i, j)], (((i) & 1) ? g1 : g0) * acc[ACC(i, j) + 1])
        if (!wg) {
            wg_wait<1>();
            mbar_arrive_if(sb + B_TAIL, lead);
            const uint32_t st0 = sb + rh * 8192 + wq * 2048;
            mbar_wait(sb + B_INIT, 0);
            wg_wait<0>();
            fence_regs(acc);
#define OSTS(i) sts128<((i) >> 2) * REGION + ((i) & 1) * 1024>(((i) & 2) ? oa ^ 64 : oa, make_uint4(OW(i, 0), OW(i, 1), OW(i, 2), OW(i, 3)))
#define ORED(h) fence_proxy_async_smem(); __syncwarp();                                                     \
            asm volatile(ELECT "cp.reduce.async.bulk.tensor.4d.global.shared::cta.add.tile.bulk_group [%0, {%2,%3,%3,%4}], [%1];}" \
                         ::"l"(&p.mOut), "r"(st0 + (h) * REGION), "r"(tn * 128 + (h) * 64), "r"(0), "r"(own * 16 + rh * 8 + wq * 2) : "memory")
            OSTS(0); OSTS(1); OSTS(2); OSTS(3);
            ORED(0);
            sched_cut();
            OSTS(4); OSTS(5); OSTS(6); OSTS(7);
            ORED(1);
            bulk_wait_read();
        } else {
            const bool odd = lane & 4;
            char *op = pin((char*)p.out + oa), *opb = pin((char*)p.out + (oa ^ 64) + 1024);
            sched_cut();
            wg_wait<0>();
            fence_regs(acc);
#define REDLINE(i) {                                                                                        \
                uint32_t k[4], r[4];                                                                        \
                _Pragma("unroll") for (int j = 0; j < 4; j++) {                                             \
                    r[j] = __shfl_xor_sync(0xffffffffu, OW((i) + 2, j), 4);                                 \
                    k[j] = OW(i, j);                                                                        \
                }                                                                                           \
                red_bf16x8<((i) & 1) * 8192 + ((i) >> 2) * 128>(op, odd ? r[0] : k[0], odd ? r[1] : k[1], odd ? r[2] : k[2], odd ? r[3] : k[3]);  \
                red_bf16x8<((i) & 1) * 8192 + ((i) >> 2) * 128>(opb, odd ? k[0] : r[0], odd ? k[1] : r[1], odd ? k[2] : r[2], odd ? k[3] : r[3]); }
            REDLINE(0)
            sched_cut();
            REDLINE(4) REDLINE(1) REDLINE(5)
        }
    }
}

typedef CUresult (*EncodeTiledFn)(CUtensorMap*, CUtensorMapDataType, cuuint32_t, void*, const cuuint64_t*, const cuuint64_t*,
                                  const cuuint32_t*, const cuuint32_t*, CUtensorMapInterleave, CUtensorMapSwizzle,
                                  CUtensorMapL2promotion, CUtensorMapFloatOOBfill);

static void make_map(EncodeTiledFn enc, CUtensorMap* m, const void* base, uint64_t cols, uint64_t rows, uint32_t box_rows,
                     CUtensorMapSwizzle sw = CU_TENSOR_MAP_SWIZZLE_128B, uint32_t box_cols = 64) {
    cuuint64_t dims[2] = {cols, rows};
    cuuint64_t str[1] = {cols * 2};
    cuuint32_t box[2] = {box_cols, box_rows};
    cuuint32_t es[2] = {1, 1};
    enc(m, CU_TENSOR_MAP_DATA_TYPE_BFLOAT16, 2, (void*)base, dims, str, box, es, CU_TENSOR_MAP_INTERLEAVE_NONE,
        sw, CU_TENSOR_MAP_L2_PROMOTION_L2_128B, CU_TENSOR_MAP_FLOAT_OOB_FILL_NONE);
}

static void make_map_chunks(EncodeTiledFn enc, CUtensorMap* m, const void* base, uint64_t rows, uint32_t box_rows, uint32_t n = 1) {
    cuuint64_t dims[3] = {64, rows, 8};
    cuuint64_t str[2] = {D_ * 2, 128};
    cuuint32_t box[3] = {64, box_rows, n};
    cuuint32_t es[3] = {1, 1, 1};
    enc(m, CU_TENSOR_MAP_DATA_TYPE_BFLOAT16, 3, (void*)base, dims, str, box, es, CU_TENSOR_MAP_INTERLEAVE_NONE,
        CU_TENSOR_MAP_SWIZZLE_128B, CU_TENSOR_MAP_L2_PROMOTION_L2_128B, CU_TENSOR_MAP_FLOAT_OOB_FILL_NONE);
}

static void make_map_out(EncodeTiledFn enc, CUtensorMap* m, const void* base) {
    cuuint64_t dims[4] = {D_, 4, 2, S_ / 8};
    cuuint64_t str[3] = {2 * D_ * 2, D_ * 2, 8 * D_ * 2};
    cuuint32_t box[4] = {64, 4, 2, 2};
    cuuint32_t es[4] = {1, 1, 1, 1};
    enc(m, CU_TENSOR_MAP_DATA_TYPE_BFLOAT16, 4, (void*)base, dims, str, box, es, CU_TENSOR_MAP_INTERLEAVE_NONE,
        CU_TENSOR_MAP_SWIZZLE_128B, CU_TENSOR_MAP_L2_PROMOTION_NONE, CU_TENSOR_MAP_FLOAT_OOB_FILL_NONE);
}

extern "C" void kernel_launch(void* const* d_in, const int* in_sizes, int n_in, void* d_out, int out_size) {
    (void)in_sizes; (void)n_in; (void)out_size;
    static EncodeTiledFn enc = nullptr;
    static bool fused_ok = false;
    static void* scratch = nullptr;
    if (!enc) {
        void* fn = nullptr;
        cudaDriverEntryPointQueryResult q;
        cudaGetDriverEntryPoint("cuTensorMapEncodeTiled", &fn, cudaEnableDefault, &q);
        enc = (EncodeTiledFn)fn;
        cudaGetSymbolAddress(&scratch, g_s);
        cudaFuncSetAttribute(fused_kernel, cudaFuncAttributeMaxDynamicSharedMemorySize, SMEM_BYTES);
        int dev = 0, nsm = 0, ncl = 0;
        cudaGetDevice(&dev);
        cudaDeviceGetAttribute(&nsm, cudaDevAttrMultiProcessorCount, dev);
        cudaLaunchConfig_t cfg = {};
        cfg.gridDim = dim3(132); cfg.blockDim = dim3(NTHREADS); cfg.dynamicSmemBytes = SMEM_BYTES;
        cudaLaunchAttribute at;
        at.id = cudaLaunchAttributeClusterDimension;
        at.val.clusterDim.x = 2; at.val.clusterDim.y = 1; at.val.clusterDim.z = 1;
        cfg.attrs = &at; cfg.numAttrs = 1;
        fused_ok = cudaOccupancyMaxActiveClusters(&ncl, fused_kernel, &cfg) == cudaSuccess && nsm == 132 && ncl == 66;
        (void)cudaGetLastError();
    }
    if (!fused_ok) {
        const bf16* const* in = (const bf16* const*)d_in;
        fb_hidden<<<S_, D_, 0, cudaStreamPerThread>>>(in[0], in[3], in[4], in[10], in[6]);
        fb_ffn1<<<F_ / 128, 128, 0, cudaStreamPerThread>>>(in[0], in[7], in[8]);
        fb_ffn2<<<D_ / 64, 64, 0, cudaStreamPerThread>>>(in[9]);
        fb_seq<<<S_, D_, 0, cudaStreamPerThread>>>(in[0], in[1], in[2], (bf16*)d_out);
        return;
    }
    Params p;
    p.s = (Scratch*)scratch;
    p.x = (const bf16*)d_in[0];
    p.w_r = (const bf16*)d_in[6];
    p.wg = (const bf16*)d_in[7];
    p.wu = (const bf16*)d_in[8];
    p.wd = (const bf16*)d_in[9];
    p.gate_w = (const bf16*)d_in[10];
    p.out = (bf16*)d_out;
    make_map_chunks(enc, &p.mX1, d_in[0], S_, 64);
    make_map_chunks(enc, &p.mX2, d_in[0], S_, 64, 2);
    make_map(enc, &p.mCre, d_in[1], S_, S_, 128);
    make_map(enc, &p.mCim, d_in[2], S_, S_, 128);
    make_map_chunks(enc, &p.mDre, d_in[3], D_, 128);
    make_map_chunks(enc, &p.mDim, d_in[4], D_, 128);
    make_map(enc, &p.mAB, scratch, 64, 8 * 32 * 128, 64, CU_TENSOR_MAP_SWIZZLE_NONE);
    make_map_out(enc, &p.mOut, d_out);
    make_map(enc, &p.mWg, d_in[7], F_, D_, 64, CU_TENSOR_MAP_SWIZZLE_NONE, 32);
    make_map(enc, &p.mWu, d_in[8], F_, D_, 64, CU_TENSOR_MAP_SWIZZLE_NONE, 32);
    make_map(enc, &p.mWd, d_in[9], D_, F_, 8, CU_TENSOR_MAP_SWIZZLE_NONE, 256);
    fused_kernel<<<132, NTHREADS, SMEM_BYTES, cudaStreamPerThread>>>(p);
}
```

```cpp
#include <cuda_runtime.h>
#include <cuda.h>
#include <cuda_bf16.h>
#include <stdint.h>

typedef __nv_bfloat16 bf16;

constexpr int S_ = 2048, D_ = 512, F_ = 1792;
constexpr int NCTA = 128;
constexpr int NTHREADS = 512;
constexpr int NSTAGE = 6;
constexpr int REGION = 32768;
constexpr int FFN_CTAS = F_ / 16;
constexpr uint32_t SPIN_LIMIT = 1u << 22;
constexpr int HOLD = 320;
constexpr int PACE = 270;
constexpr int PACE0 = 100;
constexpr int A_GAP = 260;
constexpr int B_GAP = 280;
constexpr int LATE_GAP = 240;
constexpr int INIT_GAP = 360;
constexpr int INIT_NS = 300;
constexpr int PF_T0 = 3000;
constexpr int PF_GAP = 850;
constexpr int PF_N0 = 4;
constexpr int FFN_S0 = 4;
constexpr int FFN_W = 7;
constexpr int ROUTER_C = 4;
constexpr int HINT_AT = 5;
constexpr int SUM_T0 = 15000;
constexpr int PS1 = 24;
constexpr int NA = 3;
constexpr int KEY_NS = 300;
constexpr int HSK = 2;

constexpr int OFF_MISC = 7 * REGION;
constexpr int B_F = OFF_MISC;
constexpr int B_G1 = B_F + 64;
constexpr int B_G4 = B_G1 + 8;
constexpr int B_XE = B_G4 + 8;
constexpr int B_GO1 = B_XE + 8;
constexpr int B_GO0 = B_GO1 + 8;
constexpr int B_EPOCH = B_GO0 + 8;
constexpr int B_RETRY = B_EPOCH + 8;
constexpr int B_INIT = B_RETRY + 8;
constexpr int B_FULL = B_INIT + 8;
constexpr int B_EMPTY = B_FULL + 48;
constexpr int B_PUB = B_EMPTY + 48;
constexpr int B_FREE = B_PUB + 8;
constexpr int B_BL = B_FREE + 24;
constexpr int B_TAIL = B_BL + 48;
constexpr int B_HX = B_TAIL + 8;
constexpr int B_FFN = B_HX + 8;
constexpr int B_ROLE = B_FFN + 40;
constexpr int B_EARLY = B_ROLE + 8;
constexpr int B_GATE = B_EARLY + 8;
constexpr int B_G2 = B_GATE + 8;
constexpr int B_LOW = B_G2 + 8;
constexpr int B_G0 = B_LOW + 8;
constexpr int M_EPOCH = B_G0 + 8;
constexpr int M_ROLE = M_EPOCH + 4;
constexpr int M_KEY = OFF_MISC + 416;
constexpr int M_HX = OFF_MISC + 512;
constexpr int M_G = M_HX + 1024;
constexpr int M_XS = M_G + 512;
constexpr int SMEM_BYTES = 232448;
static_assert(M_ROLE + 4 <= M_KEY && M_XS + 512 <= SMEM_BYTES, "smem");

struct Scratch {
    unsigned char ab[8 * 32 * 16384];
    unsigned int pair[65 * 32];
    unsigned int ready[16 * 32];
    unsigned int gate[S_];
    unsigned int part[FFN_CTAS / 2 * D_];
    unsigned int phint[4 * 16 * 8];
    unsigned int keys[8 * NCTA];
};
__device__ __align__(1024) Scratch g_s;

struct Params {
    Scratch* s;
    bf16* out;
    const bf16 *x, *gate_w, *w_r, *wg, *wu, *wd;
    CUtensorMap mDre, mDim, mX1, mX2, mCre, mCim, mAB, mOut, mWg, mWu, mWd;
};

#define ELECT "{.reg .pred p; elect.sync _|p, 0xffffffff; @p "
__device__ __forceinline__ uint32_t smem_u32(const void* p) { return (uint32_t)__cvta_generic_to_shared(p); }
__device__ __forceinline__ uint32_t clk() { return (uint32_t)clock64(); }
__device__ __forceinline__ void spin_until(uint32_t t) { while ((int)(clk() - t) < 0) {} }
template <int NS>
__device__ __forceinline__ void sleep_until(uint32_t t) { while ((int)(clk() - t) < 0) __nanosleep(NS); }
__device__ __forceinline__ void mbar_init_elect(uint32_t bar, uint32_t cnt) {
    asm volatile(ELECT "mbarrier.init.shared::cta.b64 [%0], %1;}" ::"r"(bar), "r"(cnt) : "memory");
}
__device__ __forceinline__ void mbar_expect_tx_elect(uint32_t bar, uint32_t bytes) {
    asm volatile(ELECT "mbarrier.arrive.expect_tx.shared::cta.b64 _, [%0], %1;}" ::"r"(bar), "r"(bytes) : "memory");
}
template <int N = 1>
__device__ __forceinline__ void mbar_arrive_elect(uint32_t bar) {
    asm volatile(ELECT "mbarrier.arrive.shared::cta.b64 _, [%0], %1;}" ::"r"(bar), "n"(N) : "memory");
}
__device__ __forceinline__ void mbar_arrive_if(uint32_t bar, bool pred) {
    asm volatile("{.reg .pred p; setp.ne.b32 p, %1, 0; @p mbarrier.arrive.shared::cta.b64 _, [%0];}" ::"r"(bar), "r"((int)pred) : "memory");
}
__device__ __forceinline__ void mbar_arrive_warp(uint32_t bar) {
    __syncwarp();
    mbar_arrive_if(bar, (threadIdx.x & 31) == 0);
}
template <int N>
__device__ __forceinline__ void release_pair(uint32_t bar, uint32_t rbar, bool pred) {
    asm volatile("{.reg .pred p; setp.ne.b32 p, %2, 0; @p mbarrier.arrive.shared::cta.b64 _, [%0], %3;"
                 " @p mbarrier.arrive.shared::cluster.b64 _, [%1], %3;}" ::"r"(bar), "r"(rbar), "r"((int)pred), "n"(N) : "memory");
}
__device__ __forceinline__ uint32_t mapa(uint32_t a, uint32_t cta) {
    uint32_t r;
    asm volatile("mapa.shared::cluster.u32 %0, %1, %2;" : "=r"(r) : "r"(a), "r"(cta));
    return r;
}
__device__ __forceinline__ bool mbar_test(uint32_t bar, uint32_t parity) {
    uint32_t ok;
    asm volatile("{.reg .pred p; mbarrier.test_wait.parity.shared::cta.b64 p, [%1], %2; selp.u32 %0,1,0,p;}"
                 : "=r"(ok) : "r"(bar), "r"(parity) : "memory");
    return ok;
}
__device__ __forceinline__ void mbar_wait(uint32_t bar, uint32_t parity) {
    asm volatile("{.reg .pred p, q; .reg .u32 n; mov.u32 n, 0;\n"
                 "W%=: mbarrier.try_wait.parity.shared::cta.b64 p, [%0], %1;\n"
                 "add.u32 n, n, 1; setp.lt.and.u32 q, n, %2, !p; @q bra W%=; @!p trap;}" ::"r"(bar), "r"(parity), "n"(SPIN_LIMIT) : "memory");
}
__device__ __forceinline__ void mbar_wait_cluster(uint32_t bar, uint32_t parity) {
    asm volatile("{.reg .pred p, q; .reg .u32 n; mov.u32 n, 0;\n"
                 "W%=: mbarrier.try_wait.parity.acquire.cluster.shared::cta.b64 p, [%0], %1;\n"
                 "add.u32 n, n, 1; setp.lt.and.u32 q, n, %2, !p; @q bra W%=; @!p trap;}" ::"r"(bar), "r"(parity), "n"(SPIN_LIMIT) : "memory");
}
__device__ __forceinline__ void mbar_spin(uint32_t bar, uint32_t parity) {
    asm volatile("{.reg .pred p;\nW%=: mbarrier.try_wait.parity.shared::cta.b64 p, [%0], %1; @!p bra W%=;}" ::"r"(bar), "r"(parity) : "memory");
}
__device__ __forceinline__ void cluster_arrive() { asm volatile("barrier.cluster.arrive.relaxed.aligned;" ::: "memory"); }
__device__ __forceinline__ void cluster_wait() { asm volatile("barrier.cluster.wait.acquire.aligned;" ::: "memory"); }
__device__ __forceinline__ void cta_bar() { asm volatile("bar.sync 0, 512;" ::: "memory"); }
__device__ __forceinline__ void side_bar() { asm volatile("bar.sync 1, 128;" ::: "memory"); }
__device__ __forceinline__ void tma2d_elect(uint32_t dst, const CUtensorMap* m, int c0, int c1, uint32_t bar) {
    asm volatile(ELECT "cp.async.bulk.tensor.2d.shared::cluster.global.mbarrier::complete_tx::bytes [%0], [%1, {%3,%4}], [%2];}"
                 ::"r"(dst), "l"(m), "r"(bar), "r"(c0), "r"(c1) : "memory");
}
__device__ __forceinline__ void tma2d_pair_elect(uint32_t dst, const CUtensorMap* m, int c0, int c1, uint32_t bar) {
    asm volatile(ELECT "cp.async.bulk.tensor.2d.shared::cluster.global.mbarrier::complete_tx::bytes.multicast::cluster"
                 " [%0], [%1, {%3,%4}], [%2], %5;}" ::"r"(dst), "l"(m), "r"(bar), "r"(c0), "r"(c1), "h"((uint16_t)3) : "memory");
}
__device__ __forceinline__ void tma3d_elect(uint32_t dst, const CUtensorMap* m, int row, int chunk, uint32_t bar) {
    asm volatile(ELECT "cp.async.bulk.tensor.3d.shared::cluster.global.mbarrier::complete_tx::bytes [%0], [%1, {%3,%4,%5}], [%2];}"
                 ::"r"(dst), "l"(m), "r"(bar), "r"(0), "r"(row), "r"(chunk) : "memory");
}
__device__ __forceinline__ void bulk_wait_read() {
    asm volatile("cp.async.bulk.commit_group; cp.async.bulk.wait_group.read 0;" ::: "memory");
    __syncwarp();
}
__device__ __forceinline__ void fence_proxy_async_smem() { asm volatile("fence.proxy.async.shared::cta;" ::: "memory"); }
__device__ __forceinline__ uint32_t ld_relaxed(const void* p) {
    uint32_t v;
    asm volatile("ld.relaxed.gpu.global.u32 %0, [%1];" : "=r"(v) : "l"(p) : "memory");
    return v;
}
__device__ __forceinline__ uint4 ld_relaxed4(const void* p) {
    uint4 v;
    asm volatile("ld.relaxed.gpu.global.v4.u32 {%0,%1,%2,%3}, [%4];" : "=r"(v.x), "=r"(v.y), "=r"(v.z), "=r"(v.w) : "l"(p) : "memory");
    return v;
}
__device__ __forceinline__ void red_inc_if(unsigned int* p, bool pred) {
    asm volatile("{.reg .pred p; setp.ne.b32 p, %1, 0; @p red.relaxed.gpu.global.add.u32 [%0], 1;}" ::"l"(p), "r"((int)pred) : "memory");
}
__device__ __forceinline__ uint32_t tagf(float v, uint32_t par) { return (__float_as_uint(v) & ~1u) | par; }
__device__ __forceinline__ uint4 wait_tags(const unsigned int* p, int bit, uint32_t par) {
    uint32_t n = 0;
    while (true) {
        const uint4 v = ld_relaxed4(p);
        const uint32_t m = par ? (v.x & v.y & v.z & v.w) : ~(v.x | v.y | v.z | v.w);
        if (__all_sync(0xffffffffu, (m >> bit) & 1u)) return v;
        __nanosleep(100);
        if (++n > SPIN_LIMIT) __trap();
    }
}
__device__ __forceinline__ void wait_counter(const unsigned int* p, uint32_t want) {
    uint32_t n = 0;
    while (!__all_sync(0xffffffffu, (int)(ld_relaxed(p) - want) >= 0)) {
        __nanosleep(200);
        if (++n > SPIN_LIMIT) __trap();
    }
    asm volatile("fence.acquire.gpu;" ::: "memory");
}
__device__ __forceinline__ uint32_t stale_tags(uint32_t a, uint32_t par) {
    uint32_t r;
    asm volatile("{.reg .b32 v<16>;\n"
                 "ld.shared.u32 v0, [%1]; ld.shared.u32 v1, [%1+256]; ld.shared.u32 v2, [%1+512]; ld.shared.u32 v3, [%1+768];\n"
                 "ld.shared.u32 v4, [%1+4096]; ld.shared.u32 v5, [%1+4352]; ld.shared.u32 v6, [%1+4608]; ld.shared.u32 v7, [%1+4864];\n"
                 "ld.shared.u32 v8, [%1+8192]; ld.shared.u32 v9, [%1+8448]; ld.shared.u32 v10, [%1+8704]; ld.shared.u32 v11, [%1+8960];\n"
                 "ld.shared.u32 v12, [%1+12288]; ld.shared.u32 v13, [%1+12544]; ld.shared.u32 v14, [%1+12800]; ld.shared.u32 v15, [%1+13056];\n"
                 "lop3.b32 v0, v0, v1, %2, 0x7e; lop3.b32 v2, v2, v3, %2, 0x7e; lop3.b32 v4, v4, v5, %2, 0x7e; lop3.b32 v6, v6, v7, %2, 0x7e;\n"
                 "lop3.b32 v8, v8, v9, %2, 0x7e; lop3.b32 v10, v10, v11, %2, 0x7e; lop3.b32 v12, v12, v13, %2, 0x7e; lop3.b32 v14, v14, v15, %2, 0x7e;\n"
                 "lop3.b32 v0, v0, v2, v4, 0xfe; lop3.b32 v6, v6, v8, v10, 0xfe; lop3.b32 v0, v0, v6, v12, 0xfe; or.b32 %0, v0, v14;}"
                 : "=r"(r) : "r"(a), "r"(par) : "memory");
    return r;
}
template <int OFF>
__device__ __forceinline__ uint4 ldg_nc(const void* p) {
    uint4 v;
    asm volatile("ld.global.nc.v4.u32 {%0,%1,%2,%3}, [%4+%5];" : "=r"(v.x), "=r"(v.y), "=r"(v.z), "=r"(v.w) : "l"(p), "n"(OFF));
    return v;
}
template <int OFF>
__device__ __forceinline__ void stg128(void* p, const uint4& v) {
    asm volatile("st.global.v4.u32 [%0+%5], {%1,%2,%3,%4};" ::"l"(p), "r"(v.x), "r"(v.y), "r"(v.z), "r"(v.w), "n"(OFF) : "memory");
}
template <int OFF>
__device__ __forceinline__ void sts128(uint32_t a, const uint4& v) {
    asm volatile("st.shared.v4.u32 [%0+%5], {%1,%2,%3,%4};" ::"r"(a), "r"(v.x), "r"(v.y), "r"(v.z), "r"(v.w), "n"(OFF) : "memory");
}
__device__ __forceinline__ uint4 lds128(uint32_t a) {
    uint4 v;
    asm volatile("ld.shared.v4.u32 {%0,%1,%2,%3}, [%4];" : "=r"(v.x), "=r"(v.y), "=r"(v.z), "=r"(v.w) : "r"(a) : "memory");
    return v;
}
template <int OFF>
__device__ __forceinline__ void red_bf16x8(void* p, uint32_t x, uint32_t y, uint32_t z, uint32_t w) {
    asm volatile("red.relaxed.gpu.global.add.noftz.v4.bf16x2 [%0+%5], {%1,%2,%3,%4};"
                 ::"l"(p), "r"(x), "r"(y), "r"(z), "r"(w), "n"(OFF) : "memory");
}
__device__ __forceinline__ void sched_cut() {
    asm volatile("{.reg .pred p; .reg .u64 t; .reg .u32 a, b;\n"
                 "C%=: mov.u64 t, %%clock64; mov.b64 {a, b}, t; setp.eq.u32 p, a, %0; @p bra C%=;}" ::"n"(0) : "memory");
}
__device__ __forceinline__ uint32_t pin(uint32_t v) { return __shfl_xor_sync(0xffffffffu, v, 0); }
template <class T>
__device__ __forceinline__ T* pin(T* p) { return (T*)__shfl_xor_sync(0xffffffffu, (unsigned long long)p, 0); }
__device__ __forceinline__ float selpf(float a, float b, bool p) {
    float r;
    asm("{.reg .pred q; setp.ne.b32 q, %3, 0; selp.f32 %0, %1, %2, q;}" : "=f"(r) : "f"(a), "f"(b), "r"((int)p));
    return r;
}
template <int N, int MASK, int SZ>
__device__ __forceinline__ void halve(float (&a)[SZ]) {
    const bool up = threadIdx.x & MASK;
#pragma unroll
    for (int j = 0; j < N; j++) a[j] = selpf(a[N + j], a[j], up) + __shfl_xor_sync(0xffffffffu, selpf(a[j], a[N + j], up), MASK);
}
__device__ __forceinline__ float bflo(uint32_t u) { return __uint_as_float(u << 16); }
__device__ __forceinline__ float bfhi(uint32_t u) { return __uint_as_float(u & 0xffff0000u); }
__device__ __forceinline__ uint32_t pack_bf16(float lo, float hi) {
    uint32_t r;
    asm("cvt.rn.bf16x2.f32 %0, %1, %2;" : "=r"(r) : "f"(hi), "f"(lo));
    return r;
}
__device__ __forceinline__ uint32_t hmul2_bf16(uint32_t a, uint32_t b) {
    uint32_t r;
    asm("mul.rn.bf16x2 %0, %1, %2;" : "=r"(r) : "r"(a), "r"(b));
    return r;
}
__device__ __forceinline__ float rbf(float v) { return bflo(pack_bf16(v, 0.f)); }
__device__ __forceinline__ float sigmoidf_(float v) { return __fdividef(1.0f, 1.0f + __expf(-v)); }

__device__ __forceinline__ void wg_fence() { asm volatile("wgmma.fence.sync.aligned;" ::: "memory"); }
__device__ __forceinline__ void wg_commit() { asm volatile("wgmma.commit_group.sync.aligned;" ::: "memory"); }
template <int N> __device__ __forceinline__ void wg_wait() { asm volatile("wgmma.wait_group.sync.aligned %0;" ::"n"(N) : "memory"); }
__device__ __forceinline__ uint64_t desc128(uint32_t lo) { return (uint64_t)lo | (0x40000040ull << 32); }
__device__ __forceinline__ uint64_t desc64(uint32_t lo) { return (uint64_t)lo | (0x80000020ull << 32); }
__device__ __forceinline__ void fence_regs(float (&d)[64]) {
#pragma unroll
    for (int i = 0; i < 64; i++) asm volatile("" : "+f"(d[i])::"memory");
}
template <int TB>
__device__ __forceinline__ void wgmma128(float (&d)[64], uint64_t da, uint64_t db, int scaleD) {
    asm volatile(
        "{ .reg .pred p; setp.ne.b32 p, %66, 0;\n"
        "wgmma.mma_async.sync.aligned.m64n128k16.f32.bf16.bf16 "
        "{%0,%1,%2,%3,%4,%5,%6,%7,%8,%9,%10,%11,%12,%13,%14,%15,%16,%17,%18,%19,%20,%21,%22,%23,%24,%25,%26,%27,%28,%29,%30,%31,"
        "%32,%33,%34,%35,%36,%37,%38,%39,%40,%41,%42,%43,%44,%45,%46,%47,%48,%49,%50,%51,%52,%53,%54,%55,%56,%57,%58,%59,%60,%61,%62,%63}, "
        "%64, %65, p, 1, 1, 0, %67;\n}"
        : "+f"(d[0]), "+f"(d[1]), "+f"(d[2]), "+f"(d[3]), "+f"(d[4]), "+f"(d[5]), "+f"(d[6]), "+f"(d[7]),
          "+f"(d[8]), "+f"(d[9]), "+f"(d[10]), "+f"(d[11]), "+f"(d[12]), "+f"(d[13]), "+f"(d[14]), "+f"(d[15]),
          "+f"(d[16]), "+f"(d[17]), "+f"(d[18]), "+f"(d[19]), "+f"(d[20]), "+f"(d[21]), "+f"(d[22]), "+f"(d[23]),
          "+f"(d[24]), "+f"(d[25]), "+f"(d[26]), "+f"(d[27]), "+f"(d[28]), "+f"(d[29]), "+f"(d[30]), "+f"(d[31]),
          "+f"(d[32]), "+f"(d[33]), "+f"(d[34]), "+f"(d[35]), "+f"(d[36]), "+f"(d[37]), "+f"(d[38]), "+f"(d[39]),
          "+f"(d[40]), "+f"(d[41]), "+f"(d[42]), "+f"(d[43]), "+f"(d[44]), "+f"(d[45]), "+f"(d[46]), "+f"(d[47]),
          "+f"(d[48]), "+f"(d[49]), "+f"(d[50]), "+f"(d[51]), "+f"(d[52]), "+f"(d[53]), "+f"(d[54]), "+f"(d[55]),
          "+f"(d[56]), "+f"(d[57]), "+f"(d[58]), "+f"(d[59]), "+f"(d[60]), "+f"(d[61]), "+f"(d[62]), "+f"(d[63])
        : "l"(da), "l"(db), "r"(scaleD), "n"(TB));
}

__device__ __forceinline__ uint32_t get_role(uint32_t& smid) {
    uint32_t role;
    asm volatile("mov.u32 %0, %%smid;" : "=r"(smid));
    asm("{.reg .pred p, q; .reg .u32 t, a, b; shr.u32 t, %1, 1; mad.lo.u32 a, t, 293, -928; shr.u32 a, a, 8; mad.lo.u32 b, t, 8, -464;"
        " setp.lt.u32 p, t, 32; setp.lt.u32 q, t, 62; selp.u32 a, a, b, q; selp.u32 %0, t, a, p;}" : "=r"(role) : "r"(smid));
    return role;
}
__device__ __forceinline__ int tile_of_step(int step, int own) {
    const int u = step >= 17 ? step - 17 - (step > PS1) : step - 2;
    int e = u + (u >= (own & 14) ? 2 : 0);
    if (step == 16 || step == PS1) e = own ^ 1;
    if (step < 2) e = own;
    return e + (step >= 17 || step == 1 ? 16 : 0);
}
__device__ __forceinline__ uint32_t router_key(float score, int row) {
    const float r = score + 0.0f;
    uint32_t u = pack_bf16(r, 0.f) & 0xffffu;
    u = (u & 0x8000u) ? (~u & 0xffffu) : (u | 0x8000u);
    if (r != r) u = 0;
    return (u << 16) | (uint32_t)(0x7fff - row);
}

#define g_fb_h ((float*)g_s.part)
#define g_fb_upd (g_fb_h + 2048)
#define g_fb_gate (g_fb_h + 4096)
#define g_fb_keys (g_s.part + 8192)
__global__ void fb_hidden(const bf16* x, const bf16* dre, const bf16* dim, const bf16* gw, const bf16* wr) {
    __shared__ float xs[D_];
    const int s = blockIdx.x, t = threadIdx.x;
    xs[t] = __bfloat162float(x[s * D_ + t]);
    __syncthreads();
    float a = 0.f, b = 0.f;
    for (int d = 0; d < D_; d++) { a = fmaf(xs[d], __bfloat162float(dre[t * D_ + d]), a); b = fmaf(xs[d], __bfloat162float(dim[t * D_ + d]), b); }
    ((bf16*)g_s.ab)[s * 1024 + t] = __float2bfloat16(a);
    ((bf16*)g_s.ab)[s * 1024 + 512 + t] = __float2bfloat16(b);
    if (t == 0) {
        float u = 0.f, v = 0.f;
        for (int d = 0; d < D_; d++) { u = fmaf(xs[d], __bfloat162float(gw[d]), u); v = fmaf(xs[d], __bfloat162float(wr[d]), v); }
        g_fb_gate[s] = sigmoidf_(u);
        g_fb_keys[s] = router_key(v, s);
    }
}
__device__ uint32_t fb_best() {
    uint32_t k = 0;
    for (int i = 0; i < S_; i++) k = max(k, g_fb_keys[i]);
    return k;
}
__global__ void fb_ffn1(const bf16* x, const bf16* wg, const bf16* wu) {
    const int f = blockIdx.x * blockDim.x + threadIdx.x, idx = 0x7fff - (int)(fb_best() & 0x7fffu);
    float a = 0.f, b = 0.f;
    for (int d = 0; d < D_; d++) {
        const float xv = __bfloat162float(x[idx * D_ + d]);
        a = fmaf(xv, __bfloat162float(wg[d * F_ + f]), a); b = fmaf(xv, __bfloat162float(wu[d * F_ + f]), b);
    }
    g_fb_h[f] = a * sigmoidf_(a) * b;
}
__global__ void fb_ffn2(const bf16* wd) {
    const int e = blockIdx.x * blockDim.x + threadIdx.x;
    const uint32_t u = fb_best() >> 16, rb = (u & 0x8000u) ? (u & 0x7fffu) : (~u & 0xffffu);
    float a = 0.f;
    for (int f = 0; f < F_; f++) a = fmaf(g_fb_h[f], __bfloat162float(wd[f * D_ + e]), a);
    g_fb_upd[e] = a * sigmoidf_(__uint_as_float(rb << 16));
}
__global__ void fb_seq(const bf16* x, const bf16* cre, const bf16* cim, bf16* out) {
    __shared__ float c[2][S_];
    __shared__ int idx;
    const int t = blockIdx.x, e = threadIdx.x;
    for (int i = e; i < S_; i += D_) { c[0][i] = __bfloat162float(cre[t * S_ + i]); c[1][i] = __bfloat162float(cim[t * S_ + i]); }
    if (e == 0) idx = 0x7fff - (int)(fb_best() & 0x7fffu);
    __syncthreads();
    float y = 0.f;
    for (int s = 0; s < S_; s++)
        y += c[0][s] * __bfloat162float(((const bf16*)g_s.ab)[s * 1024 + e]) - c[1][s] * __bfloat162float(((const bf16*)g_s.ab)[s * 1024 + 512 + e]);
    const float g = g_fb_gate[t];
    out[t * D_ + e] = __float2bfloat16(g * y + (1.f - g) * (__bfloat162float(x[t * D_ + e]) + (t == idx ? g_fb_upd[e] : 0.f)));
}

__device__ __forceinline__ void spare_job(const Params& p, unsigned char* smem, int sp, uint32_t tstart) {
    const int tid = threadIdx.x, warp = tid >> 5, lane = tid & 31;
    const uint32_t e1 = *(volatile unsigned int*)&p.s->pair[64 * 32 + sp] + 1u;
    const uint32_t par = e1 & 1u;
    uint32_t* sel = (uint32_t*)smem;
    float* acc = (float*)(smem + 1024);
    __syncthreads();
    if (tid == 0) *(volatile unsigned int*)&p.s->pair[64 * 32 + sp] = e1;
    sleep_until<500>(tstart + SUM_T0);
    if (warp < 14) {
        uint32_t n = 0;
        while ((int)(ld_relaxed(p.s->phint + (sp * 16 + warp) * 8) - e1 * 8u) < 0) {
            __nanosleep(100);
            if (++n > SPIN_LIMIT) __trap();
        }
        const unsigned int* src = p.s->part + warp * 4 * D_ + sp * 128 + lane * 4;
        uint4 v[4];
        while (true) {
            uint32_t bad = 0;
#pragma unroll
            for (int i = 0; i < 4; i++) v[i] = ld_relaxed4(src + i * D_);
#pragma unroll
            for (int i = 0; i < 4; i++) bad |= (v[i].x ^ par) | (v[i].y ^ par) | (v[i].z ^ par) | (v[i].w ^ par);
            if (!__any_sync(0xffffffffu, bad & 1u)) break;
            if (++n > SPIN_LIMIT) __trap();
        }
        float4 s = make_float4(0.f, 0.f, 0.f, 0.f);
#pragma unroll
        for (int i = 0; i < 4; i++) {
            s.x += __uint_as_float(v[i].x); s.y += __uint_as_float(v[i].y);
            s.z += __uint_as_float(v[i].z); s.w += __uint_as_float(v[i].w);
        }
        *(float4*)&acc[warp * 128 + lane * 4] = s;
    } else if (warp == 14) {
        const uint4 k4 = wait_tags(p.s->keys + lane * 4, 15, par);
        const uint32_t k = __reduce_max_sync(0xffffffffu, max(max(k4.x, k4.y), max(k4.z, k4.w)));
        const int idx = 0x7fff - (int)(k & 0x7fffu);
        const uint4 g4 = wait_tags(p.s->gate + (idx & ~3), 0, par);
        const uint32_t gw = (idx & 2) ? ((idx & 1) ? g4.w : g4.z) : ((idx & 1) ? g4.y : g4.x);
        const uint32_t u = k >> 16;
        const uint32_t rb = (u & 0x8000u) ? (u & 0x7fffu) : (~u & 0xffffu);
        const float og = 1.f - __uint_as_float(gw & ~1u), rs = sigmoidf_(__uint_as_float(rb << 16));
        if (lane == 0) { sel[0] = idx; sel[1] = pack_bf16(og, og); sel[2] = pack_bf16(rs, rs); }
        sleep_until<500>(tstart + SUM_T0 + 3000);
        wait_counter(p.s->ready + (idx >> 7) * 32, e1 * 8u);
    }
    __syncthreads();
    if (tid < 64) {
        float t0 = 0.f, t1 = 0.f;
#pragma unroll
        for (int i = 0; i < 14; i++) {
            const float2 z = *(const float2*)&acc[i * 128 + tid * 2];
            t0 += z.x; t1 += z.y;
        }
        asm volatile("red.relaxed.gpu.global.add.noftz.bf16x2 [%0], %1;" ::"l"(p.out + sel[0] * D_ + sp * 128 + tid * 2),
                     "r"(hmul2_bf16(sel[1], hmul2_bf16(sel[2], pack_bf16(t0, t1)))) : "memory");
    }
}

__host__ __device__ constexpr int off_d(int c) { return (c < 2 ? 1 : c / 2 + 2) * REGION + (c & 1) * 16384; }
__host__ __device__ constexpr int off_xe(int c) { return (c < 2 ? 6 * REGION : c < 4 ? 16384 : c < 6 ? 0 : 6 * REGION + 16384) + (c & 1) * 8192; }
__host__ __device__ constexpr int off_xl(int c) { return c < 4 ? 2 * REGION + c * 8192 : off_xe(c - 4); }

__global__ void __cluster_dims__(2, 1, 1) __launch_bounds__(NTHREADS, 1)
fused_kernel(const __grid_constant__ Params p) {
    extern __shared__ __align__(1024) unsigned char smem[];
    const uint32_t tstart = clk();
    const uint32_t sb = smem_u32(smem);
    const int tid = threadIdx.x, lane = tid & 31;
    const int rank = blockIdx.x & 1;
    if (__all_sync(0xffffffffu, tid != 0)) {
        spin_until(tstart + HOLD);
        const int w = __shfl_sync(0xffffffffu, tid >> 5, 0);
        const uint32_t b1 = sb + B_F + 8 * w;
        if (w >= 2) mbar_init_elect(b1, 1);
        if (w < 5) mbar_init_elect(b1 + 360, w < 4 ? 1 : 4);
        mbar_init_elect(b1 + 120, w < 7 ? 5 : w < 14 ? 4 : w - 12);
        mbar_init_elect(b1 + 240, 1);
        if (w == 9 || w == 15) mbar_expect_tx_elect(b1 + 240, w == 9 ? 2048 : 4);
        asm volatile("fence.mbarrier_init.release.cluster;" ::: "memory");
        cta_bar();
        cluster_arrive();
    } else {
        uint32_t s0, t1 = 0;
        const uint32_t r0 = get_role(s0);
        const int xrow = (r0 & 3) * 256 + (r0 & 32) * 4 + rank * 64;
        mbar_init_elect(sb + B_F, 1);
        if (r0 >= 64) {
            cta_bar();
            cluster_arrive();
        } else {
#pragma unroll
            for (int c = 0; c < 8; c++) {
                if (c == 2) { cta_bar(); cluster_arrive(); }
                if (c) spin_until(t1 + c * PACE);
                if (c == 1) mbar_init_elect(sb + B_F + 8, 1);
                tma3d_elect(sb + off_d(c), &p.mDre + ((r0 >> 2) & 1), (r0 & 24) * 16, c, sb + B_F + 8 * c);
                tma3d_elect(sb + off_xe(c), &p.mX1, xrow, c, sb + B_F + 8 * c);
                mbar_expect_tx_elect(sb + B_F + 8 * c, 24576);
                if (!c) {
                    t1 = clk() + PACE0;
                    sched_cut();
                    mbar_init_elect(sb + B_G0, 1);
                    tma3d_elect(sb + off_xl(0), &p.mX1, xrow + 1024, 0, sb + B_G0);
                    mbar_expect_tx_elect(sb + B_G0, 8192);
                }
            }
            tma3d_elect(sb + off_xl(1), &p.mX1, xrow + 1024, 1, sb + B_G1);
            mbar_expect_tx_elect(sb + B_G1, 8192);
            spin_until(t1 + 8 * PACE);
            tma3d_elect(sb + off_xl(2), &p.mX2, xrow + 1024, 2, sb + B_G2);
            mbar_expect_tx_elect(sb + B_G2, 16384);
            if (!(r0 & 16))
                asm volatile(ELECT "cp.async.bulk.prefetch.tensor.3d.L2.global [%0, {%1,%2,%3}];}"
                             ::"l"(&p.mX2), "r"(0), "r"(xrow + 1024), "r"(4 + ((r0 >> 2) & 2)) : "memory");
        }
    }
    const int warp = __shfl_sync(0xffffffffu, tid >> 5, 0);
    uint32_t smid;
    const uint32_t role = get_role(smid);
    if (role >= 64) {
        spare_job(p, smem, smid & 3, tstart);
        return;
    }
    const int gpc = role & 7;
    const int tn = (role >> 3) & 3;
    const int comp = gpc >> 2;
    const int own = (gpc & 3) * 4 + ((role >> 5) & 1) * 2 + rank;
    const int blk = comp * 4 + tn;
    const int cta = gpc * 16 + (role >> 3) * 2 + rank;
    constexpr unsigned long long FFN_PAIRS = 0xffff3f3f7fffff1full;
    const bool ffn = (FFN_PAIRS >> (cta >> 1)) & 1;
    const int fp = __popcll(FFN_PAIRS & ((1ull << (cta >> 1)) - 1));

    if (warp < 4) {
        const int tab = tile_of_step(lane, own);
        const uint32_t bdst = sb + 16384 + rank * 8192;
        const int brow = blk * 4096 + rank * 64;
        if (warp == 0) {
            mbar_spin(sb + B_XE, 0);
            tma3d_elect(sb + off_xl(4), &p.mX2, own * 64 + 1024, 4, sb + B_G4);
            tma3d_elect(sb + off_xl(6), &p.mX2, own * 64 + 1024, 6, sb + B_G4);
            mbar_expect_tx_elect(sb + B_G4, 32768);
#define LOAD_A() const int e = __shfl_sync(0xffffffffu, tab, step);                                             \
                 const uint32_t bar = sb + 8 * slot;                                                            \
                 mbar_spin(bar + B_EMPTY, ph);                                                                  \
                 tma2d_elect(sb + slot * REGION, &p.mCre + comp, e * 64, own * 128, bar + B_FULL);              \
                 mbar_expect_tx_elect(bar + B_FULL, 16384)
            uint32_t slot = 0, ph = 0;
            int step = 0;
#pragma unroll 1
            for (int i = 0; i < NSTAGE; i++) {
                step = slot = i < 2 ? i ^ 1 : i;
                LOAD_A();
                if (i == 2 || i == 3) spin_until(clk() + A_GAP);
            }
            step = NSTAGE;
            slot = 0; ph = 1;
#pragma unroll 1
            for (int h = 0; h < 3; h++) {
                const int last = h == 0 ? 16 : h == 1 ? PS1 : 32 - NA;
#pragma unroll 1
                for (; step < last; step++) {
                    LOAD_A();
                    tma2d_pair_elect(bdst + slot * REGION, &p.mAB, 0, brow + e * 128, bar + B_BL);
                    mbar_expect_tx_elect(bar + B_BL, 16384);
                    if (++slot == NSTAGE) { slot = 0; ph ^= 1; }
                }
                if (h == 2) break;
                LOAD_A();
                tma2d_elect(bdst + slot * REGION, &p.mAB, 0, brow + e * 128, bar + B_BL);
                tma2d_elect((bdst ^ 8192) + slot * REGION, &p.mAB, 0, (brow ^ 64) + e * 128, bar + B_BL);
                mbar_expect_tx_elect(bar + B_BL, 16384);
                step++;
                if (++slot == NSTAGE) { slot = 0; ph ^= 1; }
            }
            mbar_spin(sb + B_LOW, 0);
            uint32_t aslot = 6;
#pragma unroll 1
            for (; step < 32; step++) {
                const int e = __shfl_sync(0xffffffffu, tab, step);
                const uint32_t bar = sb + 8 * slot;
                tma2d_elect(sb + aslot * REGION, &p.mCre + comp, e * 64, own * 128, bar + B_FULL);
                mbar_expect_tx_elect(bar + B_FULL, 16384);
                mbar_expect_tx_elect(bar + B_BL, 16384);
                mbar_spin(bar + B_EMPTY, ph);
                tma2d_pair_elect(bdst + slot * REGION, &p.mAB, 0, brow + e * 128, bar + B_BL);
                aslot = slot;
                if (++slot == NSTAGE) { slot = 0; ph ^= 1; }
            }
        } else if (warp == 1) {
            cluster_wait();
            if (lane == 0)
                asm volatile("st.async.weak.shared::cluster.mbarrier::complete_tx::bytes.u32 [%0], %1, [%2];"
                             ::"r"(mapa(sb + M_ROLE, rank ^ 1)), "r"(role), "r"(mapa(sb + B_ROLE, rank ^ 1)) : "memory");
            mbar_wait_cluster(sb + B_ROLE, 0);
            if (*(volatile uint32_t*)(smem + M_ROLE) != role) __trap();
            mbar_wait(sb + B_EPOCH, 0);
            const uint32_t want = (*(volatile uint32_t*)(smem + M_EPOCH) + 1u) * 4u;
            const int eh = __shfl_sync(0xffffffffu, tab, 2 + (lane & 3));
            const unsigned int* hp = p.s->pair + (blk * 8 + (eh >> 1)) * 32 + 2 + (eh & 1);
            uint32_t seen = 0;
            int rows[4];
#pragma unroll
            for (int i = 0; i < 4; i++) {
                rows[i] = brow + __shfl_sync(0xffffffffu, tab, 2 + i) * 128;
                mbar_expect_tx_elect(sb + B_BL + 8 * (2 + i), 16384);
            }
            mbar_wait(sb + B_GO1, 0);
            asm volatile(ELECT "prefetch.tensormap [%0];}" ::"l"(&p.mAB) : "memory");
            mbar_wait(sb + B_EMPTY + 8 * 3, 0);
            mbar_spin(sb + B_EMPTY + 8 * 2, 0);
            uint32_t t3 = 0;
#pragma unroll
            for (int i = 0; i < 4; i++) {
                while (!((seen >> i) & 1u)) seen = __ballot_sync(0xffffffffu, ld_relaxed(hp) == want);
                if (i) spin_until(t3 + B_GAP);
                t3 = clk();
                if (i >= 2) mbar_spin(sb + B_EMPTY + 8 * (2 + i), 0);
                tma2d_pair_elect(bdst + (2 + i) * REGION, &p.mAB, 0, rows[i], sb + B_BL + 8 * (2 + i));
            }
            mbar_wait(sb + B_FREE, 0);
            unsigned char* gdst = p.s->ab + (blk * 32 + own + 16) * 16384;
            t3 = clk();
#pragma unroll 1
            for (int i = 0; i < 16; i++) {
                sleep_until<20>(t3);
                t3 += LATE_GAP;
                asm volatile(ELECT "cp.async.bulk.global.shared::cta.bulk_group [%0], [%1], 1024;}"
                             ::"l"(gdst + i * 1024), "r"(sb + 6 * REGION + i * 1024) : "memory");
            }
            bulk_wait_read();
            mbar_arrive_elect(sb + B_FREE + 8);
            mbar_wait(sb + B_PUB, 0);
            if (lane == 0) {
                asm volatile("fence.proxy.async.global;" ::: "memory");
                asm volatile("red.release.gpu.global.add.u32 [%0], 1;" ::"l"(p.s->ready + (cta >> 3) * 32) : "memory");
            }
            __syncwarp();
            __nanosleep(INIT_NS);
            wait_counter(p.s->ready + own * 32, want * 2u);
            mbar_arrive_elect(sb + B_INIT);
            asm volatile(ELECT "prefetch.tensormap [%0];}" ::"l"(&p.mOut) : "memory");
        } else {
            mbar_arrive_elect(sb + B_BL + 8 * (warp & 1));
            uint32_t k = warp == 3 ? 0 : 12;
#define PREFETCH_W() {                                                                                          \
                const char* src = (k >= 8 ? (const char*)p.wd + ((cta >> 5) * 2 + (k >> 1) - 4) * 229376        \
                                          : (const char*)((cta & 32) ? p.wu : p.wg) + ((cta >> 6) * 4 + (k >> 1)) * 229376) \
                                  + ((cta & 31) * 2 + (k & 1)) * 3584;                                          \
                asm volatile(ELECT "cp.async.bulk.prefetch.L2.global [%0], 3584;}" ::"l"(src) : "memory");      \
                k++; }
#pragma unroll 1
            while (k < PF_N0) {
                sleep_until<50>(tstart + PF_T0 + k * PF_GAP);
                __syncwarp();
                PREFETCH_W();
            }
            mbar_wait(sb + B_EPOCH, 0);
            const uint32_t par = (*(volatile uint32_t*)(smem + M_EPOCH) + 1u) & 1u;
            const uint32_t a0 = sb + 16384 + (lane >> 3) * 1028 + ((lane >> 2) & 1) * 144 + (lane & 3) * 32;
            const uint32_t retry = sb + B_RETRY + (warp & 1) * 240;
            uint32_t slot = warp, ph = 0, rph = 0;
            uint32_t j = ffn ? warp & 1 : 12;
#pragma unroll 1
            for (int step = warp; step < 32 || j < 12;) {
                const bool go = step < (j < 8 ? 32 - NA : 32);
                if (go) {
                    const uint32_t bar = sb + 8 * slot;
                    mbar_wait(bar + B_BL, ph);
#pragma unroll 1
                    while (__any_sync(0xffffffffu, stale_tags(a0 + slot * REGION, par) & 1u)) {
                        const int row = blk * 4096 + __shfl_sync(0xffffffffu, tab, step) * 128;
                        mbar_expect_tx_elect(retry, 16384);
                        tma2d_elect(sb + slot * REGION + 16384, &p.mAB, 0, row, retry);
                        tma2d_elect(sb + slot * REGION + 24576, &p.mAB, 0, row + 64, retry);
                        mbar_spin(retry, rph);
                        rph ^= 1u;
                    }
                    mbar_arrive_elect<4>(bar + B_FULL);
                }
                if (j < 12 && step >= FFN_S0 + j * FFN_W / 4 && __any_sync(0xffffffffu, mbar_test(sb + B_FREE + 2 * (j & 12), 0))) {
                    const uint32_t fb = sb + B_FFN + 4 * (j & 6);
                    if (!(j & 1)) mbar_expect_tx_elect(fb, 8192);
                    tma2d_elect(sb + 6 * REGION + ((j + 4) & 7) * 4096, j < 8 ? &p.mWg + (j & 1) : &p.mWd,
                                j < 8 ? fp * 32 : rank * 256, j < 8 ? rank * 256 + (j >> 1) * 64 : fp * 32 + j * 8 - 64, fb);
                    j += 2;
                }
                if (k < 12) PREFETCH_W();
                if (go) {
                    step += 2;
                    slot += 2;
                    if (slot >= NSTAGE) { slot -= NSTAGE; ph ^= 1; }
                }
            }
        }
    } else if (warp < 8) {
        const int t = tid - 128, w = warp - 4;
        if (t == 0) {
            volatile unsigned int* ep = &p.s->pair[(blk * 8 + (own >> 1)) * 32 + rank];
            const uint32_t epoch = *ep;
            *(volatile uint32_t*)(smem + M_EPOCH) = epoch;
            *ep = epoch + 1;
        }
        mbar_arrive_if(sb + B_EPOCH, t == 0);
        const uint4 gw0 = ldg_nc<0>(p.gate_w + lane * 8), gw1 = ldg_nc<512>(p.gate_w + lane * 8);
        const uint4 rw0 = ldg_nc<0>(p.w_r + lane * 8), rw1 = ldg_nc<512>(p.w_r + lane * 8);
        mbar_wait(sb + B_EPOCH, 0);
        const uint32_t par = (*(volatile uint32_t*)(smem + M_EPOCH) + 1u) & 1u;
        mbar_wait(sb + B_F + 8 * ROUTER_C, 0);
        const int row0 = cta * 16 + w * 4;
        uint4 xr[8];
        {
            const char* xp = (const char*)p.x + (uint32_t)row0 * (D_ * 2) + lane * 16;
            xr[0] = ldg_nc<0>(xp);    xr[1] = ldg_nc<512>(xp);  xr[2] = ldg_nc<1024>(xp); xr[3] = ldg_nc<1536>(xp);
            xr[4] = ldg_nc<2048>(xp); xr[5] = ldg_nc<2560>(xp); xr[6] = ldg_nc<3072>(xp); xr[7] = ldg_nc<3584>(xp);
            float a[8];
#pragma unroll
            for (int i = 0; i < 4; i++) {
                const uint32_t xv[8] = {xr[2 * i].x, xr[2 * i].y, xr[2 * i].z, xr[2 * i].w,
                                        xr[2 * i + 1].x, xr[2 * i + 1].y, xr[2 * i + 1].z, xr[2 * i + 1].w};
                const uint32_t gv[8] = {gw0.x, gw0.y, gw0.z, gw0.w, gw1.x, gw1.y, gw1.z, gw1.w};
                const uint32_t rv[8] = {rw0.x, rw0.y, rw0.z, rw0.w, rw1.x, rw1.y, rw1.z, rw1.w};
                float u = 0.f, v = 0.f;
#pragma unroll
                for (int j = 0; j < 8; j++) {
                    const uint32_t pr = hmul2_bf16(xv[j], gv[j]);
                    u += bflo(pr); u += bfhi(pr);
                    v = fmaf(bflo(xv[j]), bflo(rv[j]), v); v = fmaf(bfhi(xv[j]), bfhi(rv[j]), v);
                }
                a[i] = u; a[4 + i] = v;
            }
            mbar_wait(sb + B_EARLY, 0);
            halve<4, 16>(a); halve<2, 8>(a); halve<1, 4>(a);
            a[0] += __shfl_xor_sync(0xffffffffu, a[0], 1);
            a[0] += __shfl_xor_sync(0xffffffffu, a[0], 2);
            const int row = row0 + ((lane >> 2) & 3);
            const float gate = rbf(sigmoidf_(rbf(a[0])));
            if (lane < 16 && (lane & 3) == 0)
                asm volatile("st.relaxed.gpu.global.u32 [%0], %1;" ::"l"(&p.s->gate[row]), "r"(tagf(gate, par)) : "memory");
            const uint32_t best = __reduce_max_sync(0xffffffffu, lane >= 16 ? router_key(a[0], row) : 0u);
            if (lane == 0) *(volatile uint32_t*)(smem + M_KEY + w * 4) = best;
            side_bar();
            if (t < 8) {
                const uint4 k = *(const uint4*)(smem + M_KEY);
                asm volatile("{.reg .b32 old; atom.relaxed.gpu.global.exch.b32 old, [%0], %1;}" ::"l"(&p.s->keys[t * NCTA + cta]),
                             "r"(max(max(k.x, k.y), max(k.z, k.w)) | (par << 15)) : "memory");
            }
            const uint32_t og = pack_bf16(1.f - gate, 1.f - gate);
#pragma unroll
            for (int i = 0; i < 8; i++) {
                const uint32_t o = __shfl_sync(0xffffffffu, og, 4 * (i >> 1));
                xr[i] = make_uint4(hmul2_bf16(o, xr[i].x), hmul2_bf16(o, xr[i].y), hmul2_bf16(o, xr[i].z), hmul2_bf16(o, xr[i].w));
            }
        }
        mbar_wait(sb + B_FREE, 0);
        __nanosleep(KEY_NS);
        if (w == 0) {
            const uint4 k4 = wait_tags(p.s->keys + gpc * NCTA + lane * 4, 15, par);
            const uint32_t k = __reduce_max_sync(0xffffffffu, max(max(k4.x, k4.y), max(k4.z, k4.w)));
            sts128<M_XS>(sb + lane * 16, ldg_nc<0>(p.x + (0x7fff - (k & 0x7fffu)) * D_ + rank * 256 + lane * 8));
        } else if (w == 1) {
            const uint4 g4 = wait_tags(p.s->gate + own * 128 + lane * 4, 0, par);
            const uint32_t sg = comp ? 0x80000000u : 0u;
            sts128<M_G>(sb + lane * 16, make_uint4((g4.x & ~1u) ^ sg, (g4.y & ~1u) ^ sg, (g4.z & ~1u) ^ sg, (g4.w & ~1u) ^ sg));
            mbar_arrive_warp(sb + B_GATE);
        }
        side_bar();
        char* op = (char*)p.out + (uint32_t)row0 * (D_ * 2) + lane * 16;
        float a[16];
#pragma unroll
        for (int i = 0; i < 16; i++) a[i] = 0.f;
#pragma unroll 1
        for (int i = 0; i < 4; i++) {
            if (i == 2) {
                mbar_wait(sb + B_FREE + 8, 0);
                const uint32_t t2 = clk() + w * (INIT_GAP / 4);
#pragma unroll
                for (int j = 0; j < 8; j++) {
                    sleep_until<20>(t2 + j * INIT_GAP);
                    *(uint4*)(op + j * 512) = xr[j];
                }
                mbar_arrive_warp(sb + B_PUB);
            }
            if (ffn) {
                const float xs0 = __bfloat162float(((const bf16*)(smem + M_XS))[64 * i + (t >> 2)]);
                const float xs1 = __bfloat162float(((const bf16*)(smem + M_XS))[64 * i + 32 + (t >> 2)]);
                const uint32_t wa = sb + 6 * REGION + (i ^ 2) * 8192 + t * 16;
                mbar_wait(sb + B_FFN + 8 * i, 0);
                const uint4 v0 = lds128(wa), v1 = lds128(wa + 4096), v2 = lds128(wa + 2048), v3 = lds128(wa + 6144);
                const uint32_t w0[8] = {v0.x, v0.y, v0.z, v0.w, v1.x, v1.y, v1.z, v1.w};
                const uint32_t w1[8] = {v2.x, v2.y, v2.z, v2.w, v3.x, v3.y, v3.z, v3.w};
#pragma unroll
                for (int k = 0; k < 8; k++) {
                    a[2 * k] = fmaf(xs1, bflo(w1[k]), fmaf(xs0, bflo(w0[k]), a[2 * k]));
                    a[2 * k + 1] = fmaf(xs1, bfhi(w1[k]), fmaf(xs0, bfhi(w0[k]), a[2 * k + 1]));
                }
                if (i == 1) {
                    side_bar();
                    mbar_arrive_if(sb + B_FREE + 16, t == 0);
                }
            }
        }
        if (!ffn) {
            mbar_arrive_warp(sb + B_LOW);
            return;
        }
        halve<8, 16>(a); halve<4, 8>(a); halve<2, 4>(a);
        const uint32_t ho = (lane >> 4) * 128 + (lane & 3) * 32 + ((lane >> 2) & 3) * 8;
        cluster_wait();
#pragma unroll
        for (int k = 0; k < 2; k++)
            asm volatile("st.async.weak.shared::cluster.mbarrier::complete_tx::bytes.v2.f32 [%0], {%1,%2}, [%3];"
                         ::"r"(mapa(sb + (k ? 6 * REGION + w * 512 : M_HX + w * 256) + ho, rank ^ k ^ 1)), "f"(a[0]), "f"(a[1]),
                           "r"(mapa(sb + B_HX, rank ^ k ^ 1)) : "memory");
        mbar_wait_cluster(sb + B_HX, 0);
        const float *hx = (const float*)(smem + M_HX) + lane, *hy = (const float*)(smem + 6 * REGION) + lane;
        const float gs = rbf(((hx[0] + hy[0]) + (hx[64] + hy[128])) + ((hx[128] + hy[256]) + (hx[192] + hy[384])));
        const float us = rbf(((hx[32] + hy[32]) + (hx[96] + hy[160])) + ((hx[160] + hy[288]) + (hx[224] + hy[416])));
        float* hrow = (float*)(smem + M_XS) + w * 32;
        hrow[lane] = rbf(rbf(gs * sigmoidf_(gs)) * us);
        fence_proxy_async_smem();
        mbar_arrive_warp(sb + B_LOW);
        float o0 = 0.f, o1 = 0.f;
#pragma unroll 1
        for (int i = 0; i < 2; i++) {
            float4 hv[4];
            uint32_t vd[16];
#pragma unroll
            for (int k = 0; k < 4; k++) hv[k] = *(const float4*)&hrow[i * 16 + k * 4];
            mbar_wait(sb + B_FFN + 8 * i, 1);
#pragma unroll
            for (int k = 0; k < 16; k++) vd[k] = *(const volatile uint32_t*)(smem + 6 * REGION + 16384 + i * 8192 + k * 512 + t * 4);
#pragma unroll
            for (int k = 0; k < 4; k++) {
                o0 = fmaf(hv[k].x, bflo(vd[4 * k]), o0);     o1 = fmaf(hv[k].x, bfhi(vd[4 * k]), o1);
                o0 = fmaf(hv[k].y, bflo(vd[4 * k + 1]), o0); o1 = fmaf(hv[k].y, bfhi(vd[4 * k + 1]), o1);
                o0 = fmaf(hv[k].z, bflo(vd[4 * k + 2]), o0); o1 = fmaf(hv[k].z, bfhi(vd[4 * k + 2]), o1);
                o0 = fmaf(hv[k].w, bflo(vd[4 * k + 3]), o0); o1 = fmaf(hv[k].w, bfhi(vd[4 * k + 3]), o1);
            }
        }
        asm volatile("st.relaxed.gpu.global.v2.u32 [%0], {%1,%2};" ::"l"(&p.s->part[fp * D_ + rank * 256 + t * 2]),
                     "r"(tagf(o0, par)), "r"(tagf(o1, par)) : "memory");
        red_inc_if(p.s->phint + ((rank * 2 + (w >> 1)) * 16 + (fp >> 2)) * 8 + lane, lane == 0);
    } else {
        const int wg = (warp >> 2) - 2, wq = warp & 3;
        const uint32_t sbd = ((sb & 0x3FFFF) >> 4) + 0x10000;
        const bool lead = (tid & 127) == 0;
        const bool lead0 = lead && !wg, lead1 = lead && wg;
        const int q = lane & 3;
        float acc[64];
        const uint32_t rE = mapa(sb + B_EMPTY, rank ^ 1);
#define RELEASE(n, slot, pred) release_pair<n>(sb + B_EMPTY + 8 * (slot), rE + 8 * (slot), pred)
        const uint32_t ioff = wq * 4096 + (lane >> 2) * 64 + ((q ^ (lane >> 3)) << 4);
        const uint32_t sdst = pin(sb + 6 * REGION + (wg ? 0 : 16384) + ioff);
        unsigned char* gdst = pin(p.s->ab + (blk * 32 + own) * 16384 + ioff);
        unsigned int* hint = pin(p.s->pair + (blk * 8 + (own >> 1)) * 32 + 2 + rank + lane);
        uint32_t par = 0;
#define GET_PAR() mbar_spin(sb + B_EPOCH, 0); par = (*(volatile uint32_t*)(smem + M_EPOCH) + 1u) & 1u
        cluster_wait();
        if (wg) mbar_spin(sb + B_G0, 0);
#pragma unroll
        for (int c = 0; c < 8; c++) {
            if (c == 1 && wg) {
                wg_wait<0>();
                RELEASE(1, 1, lead);
                GET_PAR();
                mbar_spin(sb + B_G1, 0);
            }
            if (!wg || c < 3 || c == 4) mbar_spin(sb + (!wg || c == 0 ? B_F + 8 * c : c == 1 ? B_GO1 : c == 2 ? B_G2 : B_G4), 0);
            const uint32_t xa = sbd + wg * ((off_xl(c) - off_xe(c)) / 16);
            wg_fence();
#pragma unroll
            for (int kk = 0; kk < 4; kk++) {
                wgmma128<0>(acc, desc128(xa + off_xe(c) / 16 + 2 * kk), desc128(sbd + off_d(c) / 16 + 2 * kk), (c | kk) != 0);
                if (c == 7 && kk == 0) wg_commit();
            }
            wg_commit();
            if (c == 5 && !wg) { GET_PAR(); }
            if (c == 7) {
                if (wg) mbar_spin(sb + B_FULL, 0);
                wg_wait<2>();
                mbar_arrive_if(sb + B_GO1, lead0);
            }
            if (c == 4 || c >= 6) wg_wait<1>();
            if (c == 4) { mbar_arrive_if(sb + B_XE, lead0); RELEASE(1, 1, lead0); RELEASE(2, 2, lead1); RELEASE(2, 3, lead1); }
            if (c == 6) RELEASE(2, 4 * wg, lead);
            if (c == 7) mbar_arrive_if(sb + B_GO0, lead1);
        }
        const int rh = wg ^ comp;
        const uint32_t da0 = sbd + rh * 512, db0 = sbd - 0x10000 + 0x400000 + 1024;
        const uint32_t dbe = db0 + 6 * (REGION / 16), dbl = dbe - 1024;
#define STEP(da, db, first) wg_fence();                                                                     \
        _Pragma("unroll") for (int kk = 0; kk < 4; kk++)                                                    \
            wgmma128<1>(acc, desc128((da) + kk * 2), desc64((db) + kk * 256), !((first) && kk == 0));       \
        wg_commit()
#define ACC(i, j) (16 * ((i) >> 1) + 2 * ((i) & 1) + 4 * (j))
#define PW(i, j) pack_bf16(acc[ACC(i, j)], acc[ACC(i, j) + 1])
#define PT(i, j) ((j) == ((i) >> 1) ? (PW(i, j) & ~1u) | par : PW(i, j))
#define PIECE(i) make_uint4(PT(i, 0), PT(i, 1), PT(i, 2), PT(i, 3))
#define PIECES(F) F(0); F(1); sched_cut(); F(2); F(3); F(4); F(5); F(6); F(7)
        if (wg) {
            wg_wait<0>();
            fence_regs(acc);
#define STS1(i) sts128<(i) * 512>(sdst, PIECE(i))
            PIECES(STS1);
            STEP(da0, dbe, true);
            fence_proxy_async_smem();
            mbar_arrive_warp(sb + B_FULL + 8);
            RELEASE(1, 5, lead);
        } else {
            wg_wait<0>();
            fence_regs(acc);
            uint4 v[8];
#define STG0(i) v[i] = PIECE(i); stg128<(i) * 512>(gdst, v[i]); if (HINT_AT == (i) + 1) red_inc_if(hint, own < 6 && lane == 0)
            PIECES(STG0);
            mbar_spin(sb + B_EPOCH, 0);
            asm volatile("bar.sync 2, 128;" ::: "memory");
#define STS0(i) if ((i) % 2 == 0) mbar_spin(sb + B_EPOCH, 0); sts128<(i) * 512>(sdst, v[i])
            STS0(0); STS0(1); STS0(2); STS0(3); STS0(4); STS0(5); STS0(6); STS0(7);
            fence_proxy_async_smem();
            mbar_arrive_warp(sb + B_FULL);
            RELEASE(1, 5, lead);
            mbar_arrive_if(sb + B_EARLY, lead);
            mbar_spin(sb + B_FULL, 0);
            mbar_spin(sb + B_GO0, 0);
            STEP(da0, dbe, true);
        }
#pragma unroll
        for (int step = 1; step < 3; step++) {
            mbar_spin(sb + B_FULL + 8 * step, 0);
            STEP(da0 + step * (REGION / 16), step == 1 ? dbl : db0 + step * (REGION / 16), false);
            wg_wait<1>();
            RELEASE(1, step - 1, lead);
            mbar_arrive_if(sb + B_FREE + 8 * (step - 1), lead);
        }
        int slot = 3, ph = 0, pslot = 2;
        float g0 = 0.f, g1 = 0.f;
        uint32_t oa = 0;
#pragma unroll 1
        for (int step = 3; step < 26; step++) {
            mbar_wait(sb + B_FULL + 8 * slot, ph);
            STEP(da0 + slot * (REGION / 16), db0 + slot * (REGION / 16), false);
            if (step == 22 + wg) {
                const int r0 = rh * 64 + wq * 16 + (lane >> 2), sr = ((lane >> 2) & 1) * 4 + (lane >> 3);
                mbar_wait(sb + B_GATE, 0);
                g0 = ((const volatile float*)(smem + M_G))[r0];
                g1 = ((const volatile float*)(smem + M_G))[r0 + 8];
                oa = pin(wg ? ((own * 128 + (r0 & ~1)) * D_ + tn * 128 + (lane & 7) * 8) * 2u
                            : sb + rh * 8192 + wq * 2048 + sr * 128 + ((q ^ sr) << 4));
            }
            wg_wait<1>();
            RELEASE(1, pslot, lead);
            pslot = slot;
            if (++slot == NSTAGE) { slot = 0; ph ^= 1; }
        }
        mbar_wait(sb + B_FULL + 8 * 2, 0);
        wg_fence();
#pragma unroll
        for (int kk = 0; kk < 4; kk++) {
            if (kk == HSK) {
                wg_commit();
                if (wg) {
                    wg_wait<1>();
                    RELEASE(1, 1, lead);
                    mbar_wait(sb + B_INIT, 0);
                    mbar_wait(sb + B_TAIL, 0);
                }
                wg_fence();
            }
            wgmma128<1>(acc, desc128(da0 + 2 * (REGION / 16) + kk * 2), desc64(db0 + 2 * (REGION / 16) + kk * 256), 1);
        }
        wg_commit();
        if (!wg) {
            wg_wait<2>();
            RELEASE(1, 1, lead);
        }
        slot = 3;
#pragma unroll 1
        for (int step = 27; step < 32; step++) {
            if (!wg) mbar_wait(sb + B_FULL + 8 * slot, ph);
            STEP(da0 + (step < 32 - NA ? slot : step == 32 - NA ? 6 : pslot) * (REGION / 16), db0 + slot * (REGION / 16), false);
            pslot = slot;
            if (++slot == NSTAGE) { slot = 0; ph ^= 1; }
        }
#define OW(i, j) pack_bf16((((i) & 1) ? g1 : g0) * acc[ACC(i, j)], (((i) & 1) ? g1 : g0) * acc[ACC(i, j) + 1])
        if (!wg) {
            wg_wait<1>();
            mbar_arrive_if(sb + B_TAIL, lead);
            const uint32_t st0 = sb + rh * 8192 + wq * 2048;
            mbar_wait(sb + B_INIT, 0);
            wg_wait<0>();
            fence_regs(acc);
#define OSTS(i) sts128<((i) >> 2) * REGION + ((i) & 1) * 1024>(((i) & 2) ? oa ^ 64 : oa, make_uint4(OW(i, 0), OW(i, 1), OW(i, 2), OW(i, 3)))
#define ORED(h) fence_proxy_async_smem(); __syncwarp();                                                     \
            asm volatile(ELECT "cp.reduce.async.bulk.tensor.4d.global.shared::cta.add.tile.bulk_group [%0, {%2,%3,%3,%4}], [%1];}" \
                         ::"l"(&p.mOut), "r"(st0 + (h) * REGION), "r"(tn * 128 + (h) * 64), "r"(0), "r"(own * 16 + rh * 8 + wq * 2) : "memory")
            OSTS(0); OSTS(1); OSTS(2); OSTS(3);
            ORED(0);
            sched_cut();
            OSTS(4); OSTS(5); OSTS(6); OSTS(7);
            ORED(1);
            bulk_wait_read();
        } else {
            const bool odd = lane & 4;
            char *op = pin((char*)p.out + oa), *opb = pin((char*)p.out + (oa ^ 64) + 1024);
            sched_cut();
            wg_wait<0>();
            fence_regs(acc);
#define REDLINE(i) {                                                                                        \
                uint32_t k[4], r[4];                                                                        \
                _Pragma("unroll") for (int j = 0; j < 4; j++) {                                             \
                    r[j] = __shfl_xor_sync(0xffffffffu, OW((i) + 2, j), 4);                                 \
                    k[j] = OW(i, j);                                                                        \
                }                                                                                           \
                red_bf16x8<((i) & 1) * 8192 + ((i) >> 2) * 128>(op, odd ? r[0] : k[0], odd ? r[1] : k[1], odd ? r[2] : k[2], odd ? r[3] : k[3]);  \
                red_bf16x8<((i) & 1) * 8192 + ((i) >> 2) * 128>(opb, odd ? k[0] : r[0], odd ? k[1] : r[1], odd ? k[2] : r[2], odd ? k[3] : r[3]); }
            REDLINE(0)
            sched_cut();
            REDLINE(4) REDLINE(1) REDLINE(5)
        }
    }
}

typedef CUresult (*EncodeTiledFn)(CUtensorMap*, CUtensorMapDataType, cuuint32_t, void*, const cuuint64_t*, const cuuint64_t*,
                                  const cuuint32_t*, const cuuint32_t*, CUtensorMapInterleave, CUtensorMapSwizzle,
                                  CUtensorMapL2promotion, CUtensorMapFloatOOBfill);

static void make_map(EncodeTiledFn enc, CUtensorMap* m, const void* base, uint64_t cols, uint64_t rows, uint32_t box_rows,
                     CUtensorMapSwizzle sw = CU_TENSOR_MAP_SWIZZLE_128B, uint32_t box_cols = 64) {
    cuuint64_t dims[2] = {cols, rows};
    cuuint64_t str[1] = {cols * 2};
    cuuint32_t box[2] = {box_cols, box_rows};
    cuuint32_t es[2] = {1, 1};
    enc(m, CU_TENSOR_MAP_DATA_TYPE_BFLOAT16, 2, (void*)base, dims, str, box, es, CU_TENSOR_MAP_INTERLEAVE_NONE,
        sw, CU_TENSOR_MAP_L2_PROMOTION_L2_128B, CU_TENSOR_MAP_FLOAT_OOB_FILL_NONE);
}

static void make_map_chunks(EncodeTiledFn enc, CUtensorMap* m, const void* base, uint64_t rows, uint32_t box_rows, uint32_t n = 1) {
    cuuint64_t dims[3] = {64, rows, 8};
    cuuint64_t str[2] = {D_ * 2, 128};
    cuuint32_t box[3] = {64, box_rows, n};
    cuuint32_t es[3] = {1, 1, 1};
    enc(m, CU_TENSOR_MAP_DATA_TYPE_BFLOAT16, 3, (void*)base, dims, str, box, es, CU_TENSOR_MAP_INTERLEAVE_NONE,
        CU_TENSOR_MAP_SWIZZLE_128B, CU_TENSOR_MAP_L2_PROMOTION_L2_128B, CU_TENSOR_MAP_FLOAT_OOB_FILL_NONE);
}

static void make_map_out(EncodeTiledFn enc, CUtensorMap* m, const void* base) {
    cuuint64_t dims[4] = {D_, 4, 2, S_ / 8};
    cuuint64_t str[3] = {2 * D_ * 2, D_ * 2, 8 * D_ * 2};
    cuuint32_t box[4] = {64, 4, 2, 2};
    cuuint32_t es[4] = {1, 1, 1, 1};
    enc(m, CU_TENSOR_MAP_DATA_TYPE_BFLOAT16, 4, (void*)base, dims, str, box, es, CU_TENSOR_MAP_INTERLEAVE_NONE,
        CU_TENSOR_MAP_SWIZZLE_128B, CU_TENSOR_MAP_L2_PROMOTION_NONE, CU_TENSOR_MAP_FLOAT_OOB_FILL_NONE);
}

extern "C" void kernel_launch(void* const* d_in, const int* in_sizes, int n_in, void* d_out, int out_size) {
    (void)in_sizes; (void)n_in; (void)out_size;
    static EncodeTiledFn enc = nullptr;
    static bool fused_ok = false;
    static void* scratch = nullptr;
    if (!enc) {
        void* fn = nullptr;
        cudaDriverEntryPointQueryResult q;
        cudaGetDriverEntryPoint("cuTensorMapEncodeTiled", &fn, cudaEnableDefault, &q);
        enc = (EncodeTiledFn)fn;
        cudaGetSymbolAddress(&scratch, g_s);
        cudaFuncSetAttribute(fused_kernel, cudaFuncAttributeMaxDynamicSharedMemorySize, SMEM_BYTES);
        int dev = 0, nsm = 0, ncl = 0;
        cudaGetDevice(&dev);
        cudaDeviceGetAttribute(&nsm, cudaDevAttrMultiProcessorCount, dev);
        cudaLaunchConfig_t cfg = {};
        cfg.gridDim = dim3(132); cfg.blockDim = dim3(NTHREADS); cfg.dynamicSmemBytes = SMEM_BYTES;
        cudaLaunchAttribute at;
        at.id = cudaLaunchAttributeClusterDimension;
        at.val.clusterDim.x = 2; at.val.clusterDim.y = 1; at.val.clusterDim.z = 1;
        cfg.attrs = &at; cfg.numAttrs = 1;
        fused_ok = cudaOccupancyMaxActiveClusters(&ncl, fused_kernel, &cfg) == cudaSuccess && nsm == 132 && ncl == 66;
        (void)cudaGetLastError();
    }
    if (!fused_ok) {
        const bf16* const* in = (const bf16* const*)d_in;
        fb_hidden<<<S_, D_, 0, cudaStreamPerThread>>>(in[0], in[3], in[4], in[10], in[6]);
        fb_ffn1<<<F_ / 128, 128, 0, cudaStreamPerThread>>>(in[0], in[7], in[8]);
        fb_ffn2<<<D_ / 64, 64, 0, cudaStreamPerThread>>>(in[9]);
        fb_seq<<<S_, D_, 0, cudaStreamPerThread>>>(in[0], in[1], in[2], (bf16*)d_out);
        return;
    }
    Params p;
    p.s = (Scratch*)scratch;
    p.x = (const bf16*)d_in[0];
    p.w_r = (const bf16*)d_in[6];
    p.wg = (const bf16*)d_in[7];
    p.wu = (const bf16*)d_in[8];
    p.wd = (const bf16*)d_in[9];
    p.gate_w = (const bf16*)d_in[10];
    p.out = (bf16*)d_out;
    make_map_chunks(enc, &p.mX1, d_in[0], S_, 64);
    make_map_chunks(enc, &p.mX2, d_in[0], S_, 64, 2);
    make_map(enc, &p.mCre, d_in[1], S_, S_, 128);
    make_map(enc, &p.mCim, d_in[2], S_, S_, 128);
    make_map_chunks(enc, &p.mDre, d_in[3], D_, 128);
    make_map_chunks(enc, &p.mDim, d_in[4], D_, 128);
    make_map(enc, &p.mAB, scratch, 64, 8 * 32 * 128, 64, CU_TENSOR_MAP_SWIZZLE_NONE);
    make_map_out(enc, &p.mOut, d_out);
    make_map(enc, &p.mWg, d_in[7], F_, D_, 64, CU_TENSOR_MAP_SWIZZLE_NONE, 32);
    make_map(enc, &p.mWu, d_in[8], F_, D_, 64, CU_TENSOR_MAP_SWIZZLE_NONE, 32);
    make_map(enc, &p.mWd, d_in[9], D_, F_, 8, CU_TENSOR_MAP_SWIZZLE_NONE, 256);
    fused_kernel<<<132, NTHREADS, SMEM_BYTES, cudaStreamPerThread>>>(p);
}
```

```cpp
#include <cuda_runtime.h>
#include <cuda.h>
#include <cuda_bf16.h>
#include <stdint.h>

typedef __nv_bfloat16 bf16;

constexpr int S_ = 2048, D_ = 512, F_ = 1792;
constexpr int NCTA = 128;
constexpr int NTHREADS = 512;
constexpr int NSTAGE = 6;
constexpr int REGION = 32768;
constexpr int FFN_CTAS = F_ / 16;
constexpr uint32_t SPIN_LIMIT = 1u << 22;
constexpr int HOLD = 200;
constexpr int PACE = 270;
constexpr int PACE0 = 100;
constexpr int A_GAP = 260;
constexpr int B_GAP = 260;
constexpr int LATE_GAP = 240;
constexpr int INIT_GAP = 360;
constexpr int INIT_NS = 300;
constexpr int PF_T0 = 3000;
constexpr int PF_GAP = 850;
constexpr int PF_N0 = 4;
constexpr int FFN_S0 = 4;
constexpr int FFN_W = 7;
constexpr int ROUTER_C = 4;
constexpr int HINT_AT = 5;
constexpr int SUM_T0 = 15000;
constexpr int PS1 = 24;
constexpr int NA = 3;
constexpr int KEY_NS = 300;
constexpr int SETUP = 13;
constexpr int HSK = 2;

constexpr int OFF_MISC = 7 * REGION;
constexpr int B_F = OFF_MISC;
constexpr int B_G1 = B_F + 64;
constexpr int B_G4 = B_G1 + 8;
constexpr int B_XE = B_G4 + 8;
constexpr int B_GO1 = B_XE + 8;
constexpr int B_GO0 = B_GO1 + 8;
constexpr int B_EPOCH = B_GO0 + 8;
constexpr int B_RETRY = B_EPOCH + 8;
constexpr int B_INIT = B_RETRY + 8;
constexpr int B_FULL = B_INIT + 8;
constexpr int B_EMPTY = B_FULL + 48;
constexpr int B_PUB = B_EMPTY + 48;
constexpr int B_FREE = B_PUB + 8;
constexpr int B_BL = B_FREE + 24;
constexpr int B_TAIL = B_BL + 48;
constexpr int B_HX = B_TAIL + 8;
constexpr int B_FFN = B_HX + 8;
constexpr int B_ROLE = B_FFN + 40;
constexpr int B_EARLY = B_ROLE + 8;
constexpr int B_GATE = B_EARLY + 8;
constexpr int B_G2 = B_GATE + 8;
constexpr int B_LOW = B_G2 + 8;
constexpr int B_G0 = B_LOW + 8;
constexpr int M_EPOCH = B_G0 + 8;
constexpr int M_ROLE = M_EPOCH + 4;
constexpr int M_KEY = OFF_MISC + 416;
constexpr int M_HX = OFF_MISC + 512;
constexpr int M_G = M_HX + 1024;
constexpr int M_XS = M_G + 512;
constexpr int SMEM_BYTES = 232448;
static_assert(M_ROLE + 4 <= M_KEY && M_XS + 512 <= SMEM_BYTES, "smem");

struct Scratch {
    unsigned char ab[8 * 32 * 16384];
    unsigned int pair[65 * 32];
    unsigned int ready[16 * 32];
    unsigned int gate[S_];
    unsigned int part[FFN_CTAS / 2 * D_];
    unsigned int phint[4 * 16 * 8];
    unsigned int keys[8 * NCTA];
};
__device__ __align__(1024) Scratch g_s;

struct Params {
    Scratch* s;
    bf16* out;
    const bf16 *x, *gate_w, *w_r, *wg, *wu, *wd;
    CUtensorMap mDre, mDim, mX1, mX2, mCre, mCim, mAB, mOut, mWg, mWu, mWd;
};

#define ELECT "{.reg .pred p; elect.sync _|p, 0xffffffff; @p "
__device__ __forceinline__ uint32_t smem_u32(const void* p) { return (uint32_t)__cvta_generic_to_shared(p); }
__device__ __forceinline__ uint32_t clk() { return (uint32_t)clock64(); }
__device__ __forceinline__ void spin_until(uint32_t t) { while ((int)(clk() - t) < 0) {} }
template <int NS>
__device__ __forceinline__ void sleep_until(uint32_t t) { while ((int)(clk() - t) < 0) __nanosleep(NS); }
__device__ __forceinline__ void mbar_init_elect(uint32_t bar, uint32_t cnt) {
    asm volatile(ELECT "mbarrier.init.shared::cta.b64 [%0], %1;}" ::"r"(bar), "r"(cnt) : "memory");
}
__device__ __forceinline__ void mbar_expect_tx_elect(uint32_t bar, uint32_t bytes) {
    asm volatile(ELECT "mbarrier.arrive.expect_tx.shared::cta.b64 _, [%0], %1;}" ::"r"(bar), "r"(bytes) : "memory");
}
template <int N = 1>
__device__ __forceinline__ void mbar_arrive_elect(uint32_t bar) {
    asm volatile(ELECT "mbarrier.arrive.shared::cta.b64 _, [%0], %1;}" ::"r"(bar), "n"(N) : "memory");
}
__device__ __forceinline__ void mbar_arrive_if(uint32_t bar, bool pred) {
    asm volatile("{.reg .pred p; setp.ne.b32 p, %1, 0; @p mbarrier.arrive.shared::cta.b64 _, [%0];}" ::"r"(bar), "r"((int)pred) : "memory");
}
__device__ __forceinline__ void mbar_arrive_warp(uint32_t bar) {
    __syncwarp();
    mbar_arrive_if(bar, (threadIdx.x & 31) == 0);
}
template <int N>
__device__ __forceinline__ void release_pair(uint32_t bar, uint32_t rbar, bool pred) {
    asm volatile("{.reg .pred p; setp.ne.b32 p, %2, 0; @p mbarrier.arrive.shared::cta.b64 _, [%0], %3;"
                 " @p mbarrier.arrive.shared::cluster.b64 _, [%1], %3;}" ::"r"(bar), "r"(rbar), "r"((int)pred), "n"(N) : "memory");
}
__device__ __forceinline__ uint32_t mapa(uint32_t a, uint32_t cta) {
    uint32_t r;
    asm volatile("mapa.shared::cluster.u32 %0, %1, %2;" : "=r"(r) : "r"(a), "r"(cta));
    return r;
}
__device__ __forceinline__ bool mbar_test(uint32_t bar, uint32_t parity) {
    uint32_t ok;
    asm volatile("{.reg .pred p; mbarrier.test_wait.parity.shared::cta.b64 p, [%1], %2; selp.u32 %0,1,0,p;}"
                 : "=r"(ok) : "r"(bar), "r"(parity) : "memory");
    return ok;
}
__device__ __forceinline__ void mbar_wait(uint32_t bar, uint32_t parity) {
    asm volatile("{.reg .pred p, q; .reg .u32 n; mov.u32 n, 0;\n"
                 "W%=: mbarrier.try_wait.parity.shared::cta.b64 p, [%0], %1;\n"
                 "add.u32 n, n, 1; setp.lt.and.u32 q, n, %2, !p; @q bra W%=; @!p trap;}" ::"r"(bar), "r"(parity), "n"(SPIN_LIMIT) : "memory");
}
__device__ __forceinline__ void mbar_wait_cluster(uint32_t bar, uint32_t parity) {
    asm volatile("{.reg .pred p, q; .reg .u32 n; mov.u32 n, 0;\n"
                 "W%=: mbarrier.try_wait.parity.acquire.cluster.shared::cta.b64 p, [%0], %1;\n"
                 "add.u32 n, n, 1; setp.lt.and.u32 q, n, %2, !p; @q bra W%=; @!p trap;}" ::"r"(bar), "r"(parity), "n"(SPIN_LIMIT) : "memory");
}
__device__ __forceinline__ void mbar_spin(uint32_t bar, uint32_t parity) {
    asm volatile("{.reg .pred p;\nW%=: mbarrier.try_wait.parity.shared::cta.b64 p, [%0], %1; @!p bra W%=;}" ::"r"(bar), "r"(parity) : "memory");
}
__device__ __forceinline__ void cluster_arrive() { asm volatile("barrier.cluster.arrive.relaxed.aligned;" ::: "memory"); }
__device__ __forceinline__ void cluster_wait() { asm volatile("barrier.cluster.wait.acquire.aligned;" ::: "memory"); }
__device__ __forceinline__ void cta_bar() { asm volatile("bar.sync 0, 512;" ::: "memory"); }
__device__ __forceinline__ void side_bar() { asm volatile("bar.sync 1, 128;" ::: "memory"); }
__device__ __forceinline__ void tma2d_elect(uint32_t dst, const CUtensorMap* m, int c0, int c1, uint32_t bar) {
    asm volatile(ELECT "cp.async.bulk.tensor.2d.shared::cluster.global.mbarrier::complete_tx::bytes [%0], [%1, {%3,%4}], [%2];}"
                 ::"r"(dst), "l"(m), "r"(bar), "r"(c0), "r"(c1) : "memory");
}
__device__ __forceinline__ void tma2d_pair_elect(uint32_t dst, const CUtensorMap* m, int c0, int c1, uint32_t bar) {
    asm volatile(ELECT "cp.async.bulk.tensor.2d.shared::cluster.global.mbarrier::complete_tx::bytes.multicast::cluster"
                 " [%0], [%1, {%3,%4}], [%2], %5;}" ::"r"(dst), "l"(m), "r"(bar), "r"(c0), "r"(c1), "h"((uint16_t)3) : "memory");
}
__device__ __forceinline__ void tma3d_elect(uint32_t dst, const CUtensorMap* m, int row, int chunk, uint32_t bar) {
    asm volatile(ELECT "cp.async.bulk.tensor.3d.shared::cluster.global.mbarrier::complete_tx::bytes [%0], [%1, {%3,%4,%5}], [%2];}"
                 ::"r"(dst), "l"(m), "r"(bar), "r"(0), "r"(row), "r"(chunk) : "memory");
}
__device__ __forceinline__ void bulk_wait_read() {
    asm volatile("cp.async.bulk.commit_group; cp.async.bulk.wait_group.read 0;" ::: "memory");
    __syncwarp();
}
__device__ __forceinline__ void fence_proxy_async_smem() { asm volatile("fence.proxy.async.shared::cta;" ::: "memory"); }
__device__ __forceinline__ uint32_t ld_relaxed(const void* p) {
    uint32_t v;
    asm volatile("ld.relaxed.gpu.global.u32 %0, [%1];" : "=r"(v) : "l"(p) : "memory");
    return v;
}
__device__ __forceinline__ uint4 ld_relaxed4(const void* p) {
    uint4 v;
    asm volatile("ld.relaxed.gpu.global.v4.u32 {%0,%1,%2,%3}, [%4];" : "=r"(v.x), "=r"(v.y), "=r"(v.z), "=r"(v.w) : "l"(p) : "memory");
    return v;
}
__device__ __forceinline__ void red_inc_if(unsigned int* p, bool pred) {
    asm volatile("{.reg .pred p; setp.ne.b32 p, %1, 0; @p red.relaxed.gpu.global.add.u32 [%0], 1;}" ::"l"(p), "r"((int)pred) : "memory");
}
__device__ __forceinline__ uint32_t tagf(float v, uint32_t par) { return (__float_as_uint(v) & ~1u) | par; }
__device__ __forceinline__ uint4 wait_tags(const unsigned int* p, int bit, uint32_t par) {
    uint32_t n = 0;
    while (true) {
        const uint4 v = ld_relaxed4(p);
        const uint32_t m = par ? (v.x & v.y & v.z & v.w) : ~(v.x | v.y | v.z | v.w);
        if (__all_sync(0xffffffffu, (m >> bit) & 1u)) return v;
        __nanosleep(100);
        if (++n > SPIN_LIMIT) __trap();
    }
}
__device__ __forceinline__ void wait_counter(const unsigned int* p, uint32_t want) {
    uint32_t n = 0;
    while (!__all_sync(0xffffffffu, (int)(ld_relaxed(p) - want) >= 0)) {
        __nanosleep(200);
        if (++n > SPIN_LIMIT) __trap();
    }
    asm volatile("fence.acquire.gpu;" ::: "memory");
}
__device__ __forceinline__ uint32_t stale_tags(uint32_t a, uint32_t par) {
    uint32_t r;
    asm volatile("{.reg .b32 v<16>;\n"
                 "ld.shared.u32 v0, [%1]; ld.shared.u32 v1, [%1+256]; ld.shared.u32 v2, [%1+512]; ld.shared.u32 v3, [%1+768];\n"
                 "ld.shared.u32 v4, [%1+4096]; ld.shared.u32 v5, [%1+4352]; ld.shared.u32 v6, [%1+4608]; ld.shared.u32 v7, [%1+4864];\n"
                 "ld.shared.u32 v8, [%1+8192]; ld.shared.u32 v9, [%1+8448]; ld.shared.u32 v10, [%1+8704]; ld.shared.u32 v11, [%1+8960];\n"
                 "ld.shared.u32 v12, [%1+12288]; ld.shared.u32 v13, [%1+12544]; ld.shared.u32 v14, [%1+12800]; ld.shared.u32 v15, [%1+13056];\n"
                 "lop3.b32 v0, v0, v1, %2, 0x7e; lop3.b32 v2, v2, v3, %2, 0x7e; lop3.b32 v4, v4, v5, %2, 0x7e; lop3.b32 v6, v6, v7, %2, 0x7e;\n"
                 "lop3.b32 v8, v8, v9, %2, 0x7e; lop3.b32 v10, v10, v11, %2, 0x7e; lop3.b32 v12, v12, v13, %2, 0x7e; lop3.b32 v14, v14, v15, %2, 0x7e;\n"
                 "lop3.b32 v0, v0, v2, v4, 0xfe; lop3.b32 v6, v6, v8, v10, 0xfe; lop3.b32 v0, v0, v6, v12, 0xfe; or.b32 %0, v0, v14;}"
                 : "=r"(r) : "r"(a), "r"(par) : "memory");
    return r;
}
template <int OFF>
__device__ __forceinline__ uint4 ldg_nc(const void* p) {
    uint4 v;
    asm volatile("ld.global.nc.v4.u32 {%0,%1,%2,%3}, [%4+%5];" : "=r"(v.x), "=r"(v.y), "=r"(v.z), "=r"(v.w) : "l"(p), "n"(OFF));
    return v;
}
template <int OFF>
__device__ __forceinline__ void stg128(void* p, const uint4& v) {
    asm volatile("st.global.v4.u32 [%0+%5], {%1,%2,%3,%4};" ::"l"(p), "r"(v.x), "r"(v.y), "r"(v.z), "r"(v.w), "n"(OFF) : "memory");
}
template <int OFF>
__device__ __forceinline__ void sts128(uint32_t a, const uint4& v) {
    asm volatile("st.shared.v4.u32 [%0+%5], {%1,%2,%3,%4};" ::"r"(a), "r"(v.x), "r"(v.y), "r"(v.z), "r"(v.w), "n"(OFF) : "memory");
}
__device__ __forceinline__ uint4 lds128(uint32_t a) {
    uint4 v;
    asm volatile("ld.shared.v4.u32 {%0,%1,%2,%3}, [%4];" : "=r"(v.x), "=r"(v.y), "=r"(v.z), "=r"(v.w) : "r"(a) : "memory");
    return v;
}
template <int OFF>
__device__ __forceinline__ void red_bf16x8(void* p, uint32_t x, uint32_t y, uint32_t z, uint32_t w) {
    asm volatile("red.relaxed.gpu.global.add.noftz.v4.bf16x2 [%0+%5], {%1,%2,%3,%4};"
                 ::"l"(p), "r"(x), "r"(y), "r"(z), "r"(w), "n"(OFF) : "memory");
}
__device__ __forceinline__ void sched_cut() {
    asm volatile("{.reg .pred p; .reg .u64 t; .reg .u32 a, b;\n"
                 "C%=: mov.u64 t, %%clock64; mov.b64 {a, b}, t; setp.eq.u32 p, a, %0; @p bra C%=;}" ::"n"(0) : "memory");
}
__device__ __forceinline__ uint32_t pin(uint32_t v) { return __shfl_xor_sync(0xffffffffu, v, 0); }
template <class T>
__device__ __forceinline__ T* pin(T* p) { return (T*)__shfl_xor_sync(0xffffffffu, (unsigned long long)p, 0); }
__device__ __forceinline__ float selpf(float a, float b, bool p) {
    float r;
    asm("{.reg .pred q; setp.ne.b32 q, %3, 0; selp.f32 %0, %1, %2, q;}" : "=f"(r) : "f"(a), "f"(b), "r"((int)p));
    return r;
}
template <int N, int MASK, int SZ>
__device__ __forceinline__ void halve(float (&a)[SZ]) {
    const bool up = threadIdx.x & MASK;
#pragma unroll
    for (int j = 0; j < N; j++) a[j] = selpf(a[N + j], a[j], up) + __shfl_xor_sync(0xffffffffu, selpf(a[j], a[N + j], up), MASK);
}
__device__ __forceinline__ float bflo(uint32_t u) { return __uint_as_float(u << 16); }
__device__ __forceinline__ float bfhi(uint32_t u) { return __uint_as_float(u & 0xffff0000u); }
__device__ __forceinline__ uint32_t pack_bf16(float lo, float hi) {
    uint32_t r;
    asm("cvt.rn.bf16x2.f32 %0, %1, %2;" : "=r"(r) : "f"(hi), "f"(lo));
    return r;
}
__device__ __forceinline__ uint32_t hmul2_bf16(uint32_t a, uint32_t b) {
    uint32_t r;
    asm("mul.rn.bf16x2 %0, %1, %2;" : "=r"(r) : "r"(a), "r"(b));
    return r;
}
__device__ __forceinline__ float rbf(float v) { return bflo(pack_bf16(v, 0.f)); }
__device__ __forceinline__ float sigmoidf_(float v) { return __fdividef(1.0f, 1.0f + __expf(-v)); }

__device__ __forceinline__ void wg_fence() { asm volatile("wgmma.fence.sync.aligned;" ::: "memory"); }
__device__ __forceinline__ void wg_commit() { asm volatile("wgmma.commit_group.sync.aligned;" ::: "memory"); }
template <int N> __device__ __forceinline__ void wg_wait() { asm volatile("wgmma.wait_group.sync.aligned %0;" ::"n"(N) : "memory"); }
__device__ __forceinline__ uint64_t desc128(uint32_t lo) { return (uint64_t)lo | (0x40000040ull << 32); }
__device__ __forceinline__ uint64_t desc64(uint32_t lo) { return (uint64_t)lo | (0x80000020ull << 32); }
__device__ __forceinline__ void fence_regs(float (&d)[64]) {
#pragma unroll
    for (int i = 0; i < 64; i++) asm volatile("" : "+f"(d[i])::"memory");
}
template <int TB>
__device__ __forceinline__ void wgmma128(float (&d)[64], uint64_t da, uint64_t db, int scaleD) {
    asm volatile(
        "{ .reg .pred p; setp.ne.b32 p, %66, 0;\n"
        "wgmma.mma_async.sync.aligned.m64n128k16.f32.bf16.bf16 "
        "{%0,%1,%2,%3,%4,%5,%6,%7,%8,%9,%10,%11,%12,%13,%14,%15,%16,%17,%18,%19,%20,%21,%22,%23,%24,%25,%26,%27,%28,%29,%30,%31,"
        "%32,%33,%34,%35,%36,%37,%38,%39,%40,%41,%42,%43,%44,%45,%46,%47,%48,%49,%50,%51,%52,%53,%54,%55,%56,%57,%58,%59,%60,%61,%62,%63}, "
        "%64, %65, p, 1, 1, 0, %67;\n}"
        : "+f"(d[0]), "+f"(d[1]), "+f"(d[2]), "+f"(d[3]), "+f"(d[4]), "+f"(d[5]), "+f"(d[6]), "+f"(d[7]),
          "+f"(d[8]), "+f"(d[9]), "+f"(d[10]), "+f"(d[11]), "+f"(d[12]), "+f"(d[13]), "+f"(d[14]), "+f"(d[15]),
          "+f"(d[16]), "+f"(d[17]), "+f"(d[18]), "+f"(d[19]), "+f"(d[20]), "+f"(d[21]), "+f"(d[22]), "+f"(d[23]),
          "+f"(d[24]), "+f"(d[25]), "+f"(d[26]), "+f"(d[27]), "+f"(d[28]), "+f"(d[29]), "+f"(d[30]), "+f"(d[31]),
          "+f"(d[32]), "+f"(d[33]), "+f"(d[34]), "+f"(d[35]), "+f"(d[36]), "+f"(d[37]), "+f"(d[38]), "+f"(d[39]),
          "+f"(d[40]), "+f"(d[41]), "+f"(d[42]), "+f"(d[43]), "+f"(d[44]), "+f"(d[45]), "+f"(d[46]), "+f"(d[47]),
          "+f"(d[48]), "+f"(d[49]), "+f"(d[50]), "+f"(d[51]), "+f"(d[52]), "+f"(d[53]), "+f"(d[54]), "+f"(d[55]),
          "+f"(d[56]), "+f"(d[57]), "+f"(d[58]), "+f"(d[59]), "+f"(d[60]), "+f"(d[61]), "+f"(d[62]), "+f"(d[63])
        : "l"(da), "l"(db), "r"(scaleD), "n"(TB));
}

__device__ __forceinline__ uint32_t get_role(uint32_t& smid) {
    uint32_t role;
    asm volatile("mov.u32 %0, %%smid;" : "=r"(smid));
    asm("{.reg .pred p, q; .reg .u32 t, a, b; shr.u32 t, %1, 1; mad.lo.u32 a, t, 293, -928; shr.u32 a, a, 8; mad.lo.u32 b, t, 8, -464;"
        " setp.lt.u32 p, t, 32; setp.lt.u32 q, t, 62; selp.u32 a, a, b, q; selp.u32 %0, t, a, p;}" : "=r"(role) : "r"(smid));
    return role;
}
__device__ __forceinline__ int tile_of_step(int step, int own) {
    const int u = step >= 17 ? step - 17 - (step > PS1) : step - 2;
    int e = u + (u >= (own & 14) ? 2 : 0);
    if (step == 16 || step == PS1) e = own ^ 1;
    if (step < 2) e = own;
    return e + (step >= 17 || step == 1 ? 16 : 0);
}
__device__ __forceinline__ uint32_t router_key(float score, int row) {
    const float r = score + 0.0f;
    uint32_t u = pack_bf16(r, 0.f) & 0xffffu;
    u = (u & 0x8000u) ? (~u & 0xffffu) : (u | 0x8000u);
    if (r != r) u = 0;
    return (u << 16) | (uint32_t)(0x7fff - row);
}

#define g_fb_h ((float*)g_s.part)
#define g_fb_upd (g_fb_h + 2048)
#define g_fb_gate (g_fb_h + 4096)
#define g_fb_keys (g_s.part + 8192)
__global__ void fb_hidden(const bf16* x, const bf16* dre, const bf16* dim, const bf16* gw, const bf16* wr) {
    __shared__ float xs[D_];
    const int s = blockIdx.x, t = threadIdx.x;
    xs[t] = __bfloat162float(x[s * D_ + t]);
    __syncthreads();
    float a = 0.f, b = 0.f;
    for (int d = 0; d < D_; d++) { a = fmaf(xs[d], __bfloat162float(dre[t * D_ + d]), a); b = fmaf(xs[d], __bfloat162float(dim[t * D_ + d]), b); }
    ((bf16*)g_s.ab)[s * 1024 + t] = __float2bfloat16(a);
    ((bf16*)g_s.ab)[s * 1024 + 512 + t] = __float2bfloat16(b);
    if (t == 0) {
        float u = 0.f, v = 0.f;
        for (int d = 0; d < D_; d++) { u = fmaf(xs[d], __bfloat162float(gw[d]), u); v = fmaf(xs[d], __bfloat162float(wr[d]), v); }
        g_fb_gate[s] = sigmoidf_(u);
        g_fb_keys[s] = router_key(v, s);
    }
}
__device__ uint32_t fb_best() {
    uint32_t k = 0;
    for (int i = 0; i < S_; i++) k = max(k, g_fb_keys[i]);
    return k;
}
__global__ void fb_ffn1(const bf16* x, const bf16* wg, const bf16* wu) {
    const int f = blockIdx.x * blockDim.x + threadIdx.x, idx = 0x7fff - (int)(fb_best() & 0x7fffu);
    float a = 0.f, b = 0.f;
    for (int d = 0; d < D_; d++) {
        const float xv = __bfloat162float(x[idx * D_ + d]);
        a = fmaf(xv, __bfloat162float(wg[d * F_ + f]), a); b = fmaf(xv, __bfloat162float(wu[d * F_ + f]), b);
    }
    g_fb_h[f] = a * sigmoidf_(a) * b;
}
__global__ void fb_ffn2(const bf16* wd) {
    const int e = blockIdx.x * blockDim.x + threadIdx.x;
    const uint32_t u = fb_best() >> 16, rb = (u & 0x8000u) ? (u & 0x7fffu) : (~u & 0xffffu);
    float a = 0.f;
    for (int f = 0; f < F_; f++) a = fmaf(g_fb_h[f], __bfloat162float(wd[f * D_ + e]), a);
    g_fb_upd[e] = a * sigmoidf_(__uint_as_float(rb << 16));
}
__global__ void fb_seq(const bf16* x, const bf16* cre, const bf16* cim, bf16* out) {
    __shared__ float c[2][S_];
    __shared__ int idx;
    const int t = blockIdx.x, e = threadIdx.x;
    for (int i = e; i < S_; i += D_) { c[0][i] = __bfloat162float(cre[t * S_ + i]); c[1][i] = __bfloat162float(cim[t * S_ + i]); }
    if (e == 0) idx = 0x7fff - (int)(fb_best() & 0x7fffu);
    __syncthreads();
    float y = 0.f;
    for (int s = 0; s < S_; s++)
        y += c[0][s] * __bfloat162float(((const bf16*)g_s.ab)[s * 1024 + e]) - c[1][s] * __bfloat162float(((const bf16*)g_s.ab)[s * 1024 + 512 + e]);
    const float g = g_fb_gate[t];
    out[t * D_ + e] = __float2bfloat16(g * y + (1.f - g) * (__bfloat162float(x[t * D_ + e]) + (t == idx ? g_fb_upd[e] : 0.f)));
}

__device__ __forceinline__ void spare_job(const Params& p, unsigned char* smem, int sp, uint32_t tstart) {
    const int tid = threadIdx.x, warp = tid >> 5, lane = tid & 31;
    const uint32_t e1 = *(volatile unsigned int*)&p.s->pair[64 * 32 + sp] + 1u;
    const uint32_t par = e1 & 1u;
    uint32_t* sel = (uint32_t*)smem;
    float* acc = (float*)(smem + 1024);
    __syncthreads();
    if (tid == 0) *(volatile unsigned int*)&p.s->pair[64 * 32 + sp] = e1;
    sleep_until<500>(tstart + SUM_T0);
    if (warp < 14) {
        uint32_t n = 0;
        while ((int)(ld_relaxed(p.s->phint + (sp * 16 + warp) * 8) - e1 * 8u) < 0) {
            __nanosleep(100);
            if (++n > SPIN_LIMIT) __trap();
        }
        const unsigned int* src = p.s->part + warp * 4 * D_ + sp * 128 + lane * 4;
        uint4 v[4];
        while (true) {
            uint32_t bad = 0;
#pragma unroll
            for (int i = 0; i < 4; i++) v[i] = ld_relaxed4(src + i * D_);
#pragma unroll
            for (int i = 0; i < 4; i++) bad |= (v[i].x ^ par) | (v[i].y ^ par) | (v[i].z ^ par) | (v[i].w ^ par);
            if (!__any_sync(0xffffffffu, bad & 1u)) break;
            if (++n > SPIN_LIMIT) __trap();
        }
        float4 s = make_float4(0.f, 0.f, 0.f, 0.f);
#pragma unroll
        for (int i = 0; i < 4; i++) {
            s.x += __uint_as_float(v[i].x); s.y += __uint_as_float(v[i].y);
            s.z += __uint_as_float(v[i].z); s.w += __uint_as_float(v[i].w);
        }
        *(float4*)&acc[warp * 128 + lane * 4] = s;
    } else if (warp == 14) {
        const uint4 k4 = wait_tags(p.s->keys + lane * 4, 15, par);
        const uint32_t k = __reduce_max_sync(0xffffffffu, max(max(k4.x, k4.y), max(k4.z, k4.w)));
        const int idx = 0x7fff - (int)(k & 0x7fffu);
        const uint4 g4 = wait_tags(p.s->gate + (idx & ~3), 0, par);
        const uint32_t gw = (idx & 2) ? ((idx & 1) ? g4.w : g4.z) : ((idx & 1) ? g4.y : g4.x);
        const uint32_t u = k >> 16;
        const uint32_t rb = (u & 0x8000u) ? (u & 0x7fffu) : (~u & 0xffffu);
        const float og = 1.f - __uint_as_float(gw & ~1u), rs = sigmoidf_(__uint_as_float(rb << 16));
        if (lane == 0) { sel[0] = idx; sel[1] = pack_bf16(og, og); sel[2] = pack_bf16(rs, rs); }
        sleep_until<500>(tstart + SUM_T0 + 3000);
        wait_counter(p.s->ready + (idx >> 7) * 32, e1 * 8u);
    }
    __syncthreads();
    if (tid < 64) {
        float t0 = 0.f, t1 = 0.f;
#pragma unroll
        for (int i = 0; i < 14; i++) {
            const float2 z = *(const float2*)&acc[i * 128 + tid * 2];
            t0 += z.x; t1 += z.y;
        }
        asm volatile("red.relaxed.gpu.global.add.noftz.bf16x2 [%0], %1;" ::"l"(p.out + sel[0] * D_ + sp * 128 + tid * 2),
                     "r"(hmul2_bf16(sel[1], hmul2_bf16(sel[2], pack_bf16(t0, t1)))) : "memory");
    }
}

__host__ __device__ constexpr int off_d(int c) { return (c < 2 ? 1 : c / 2 + 2) * REGION + (c & 1) * 16384; }
__host__ __device__ constexpr int off_xe(int c) { return (c < 2 ? 6 * REGION : c < 4 ? 16384 : c < 6 ? 0 : 6 * REGION + 16384) + (c & 1) * 8192; }
__host__ __device__ constexpr int off_xl(int c) { return c < 4 ? 2 * REGION + c * 8192 : off_xe(c - 4); }

__global__ void __cluster_dims__(2, 1, 1) __launch_bounds__(NTHREADS, 1)
fused_kernel(const __grid_constant__ Params p) {
    extern __shared__ __align__(1024) unsigned char smem[];
    const uint32_t sb = smem_u32(smem);
    const int tid = threadIdx.x, lane = tid & 31;
    const int rank = blockIdx.x & 1;
    if (__all_sync(0xffffffffu, tid != 0)) {
        spin_until(clk() + HOLD);
        const int w = __shfl_sync(0xffffffffu, tid >> 5, 0);
        const uint32_t b1 = sb + B_F + 8 * w;
        if (w >= 2) mbar_init_elect(b1, 1);
        if (w < 5) mbar_init_elect(b1 + 360, w < 4 ? 1 : 4);
        mbar_init_elect(b1 + 120, w < 7 ? 5 : w < 14 ? 4 : w - 12);
        mbar_init_elect(b1 + 240, 1);
        if (w == 9 || w == 15) mbar_expect_tx_elect(b1 + 240, w == 9 ? 2048 : 4);
        asm volatile("fence.mbarrier_init.release.cluster;" ::: "memory");
        cta_bar();
        cluster_arrive();
    } else {
        uint32_t s0, t1 = 0;
        const uint32_t r0 = get_role(s0);
        const int xrow = (r0 & 3) * 256 + (r0 & 32) * 4 + rank * 64;
        mbar_init_elect(sb + B_F, 1);
        if (r0 >= 64) {
            cta_bar();
            cluster_arrive();
        } else {
#pragma unroll
            for (int c = 0; c < 8; c++) {
                if (c == 2) { cta_bar(); cluster_arrive(); }
                if (c) spin_until(t1 + c * PACE);
                if (c == 1) mbar_init_elect(sb + B_F + 8, 1);
                tma2d_elect(sb + off_xe(c), &p.mX1, c * 64, xrow, sb + B_F + 8 * c);
                tma2d_elect(sb + off_d(c), &p.mDre + ((r0 >> 2) & 1), c * 64, (r0 & 24) * 16, sb + B_F + 8 * c);
                mbar_expect_tx_elect(sb + B_F + 8 * c, 24576);
                if (!c) {
                    t1 = clk() + PACE0;
                    sched_cut();
                    mbar_init_elect(sb + B_G0, 1);
                    tma2d_elect(sb + off_xl(0), &p.mX1, 0, xrow + 1024, sb + B_G0);
                    mbar_expect_tx_elect(sb + B_G0, 8192);
                }
            }
            tma2d_elect(sb + off_xl(1), &p.mX1, 64, xrow + 1024, sb + B_G1);
            mbar_expect_tx_elect(sb + B_G1, 8192);
            spin_until(t1 + 8 * PACE);
            tma3d_elect(sb + off_xl(2), &p.mX2, xrow + 1024, 2, sb + B_G2);
            mbar_expect_tx_elect(sb + B_G2, 16384);
            if (!(r0 & 16))
                asm volatile(ELECT "cp.async.bulk.prefetch.tensor.3d.L2.global [%0, {%1,%2,%3}];}"
                             ::"l"(&p.mX2), "r"(0), "r"(xrow + 1024), "r"(4 + ((r0 >> 2) & 2)) : "memory");
        }
    }
    uint32_t tstart = clk() - 1000;
    const int warp = __shfl_sync(0xffffffffu, tid >> 5, 0);
    uint32_t smid;
    const uint32_t role = get_role(smid);
    if (role >= 64) {
        spare_job(p, smem, smid & 3, tstart);
        return;
    }
    const int gpc = role & 7;
    const int tn = (role >> 3) & 3;
    const int comp = gpc >> 2;
    const int own = (gpc & 3) * 4 + ((role >> 5) & 1) * 2 + rank;
    const int blk = comp * 4 + tn;
    const int cta = gpc * 16 + (role >> 3) * 2 + rank;
    constexpr unsigned long long FFN_PAIRS = 0xffff3f3f7fffff1full;
    const bool ffn = (FFN_PAIRS >> (cta >> 1)) & 1;
    const int fp = __popcll(FFN_PAIRS & ((1ull << (cta >> 1)) - 1));

    if (warp < 4) {
        const int tab = tile_of_step(lane, own);
        const uint32_t bdst = sb + 16384 + rank * 8192;
        const int brow = blk * 4096 + rank * 64;
        if (warp == 0) {
            mbar_spin(sb + B_XE, 0);
            tma3d_elect(sb + off_xl(4), &p.mX2, own * 64 + 1024, 4, sb + B_G4);
            tma3d_elect(sb + off_xl(6), &p.mX2, own * 64 + 1024, 6, sb + B_G4);
            mbar_expect_tx_elect(sb + B_G4, 32768);
#define LOAD_A() const int e = __shfl_sync(0xffffffffu, tab, step);                                             \
                 const uint32_t bar = sb + 8 * slot;                                                            \
                 mbar_spin(bar + B_EMPTY, ph);                                                                  \
                 tma2d_elect(sb + slot * REGION, &p.mCre + comp, e * 64, own * 128, bar + B_FULL);              \
                 mbar_expect_tx_elect(bar + B_FULL, 16384)
            uint32_t slot = 0, ph = 0;
            int step = 0;
#pragma unroll 1
            for (int i = 0; i < NSTAGE; i++) {
                step = slot = i < 2 ? i ^ 1 : i;
                LOAD_A();
                if (i == 2 || i == 3) spin_until(clk() + A_GAP);
            }
            step = NSTAGE;
            slot = 0; ph = 1;
#pragma unroll 1
            for (int h = 0; h < 3; h++) {
                const int last = h == 0 ? 16 : h == 1 ? PS1 : 32 - NA;
#pragma unroll 1
                for (; step < last; step++) {
                    LOAD_A();
                    tma2d_pair_elect(bdst + slot * REGION, &p.mAB, 0, brow + e * 128, bar + B_BL);
                    mbar_expect_tx_elect(bar + B_BL, 16384);
                    if (++slot == NSTAGE) { slot = 0; ph ^= 1; }
                }
                if (h == 2) break;
                LOAD_A();
                tma2d_elect(bdst + slot * REGION, &p.mAB, 0, brow + e * 128, bar + B_BL);
                tma2d_elect((bdst ^ 8192) + slot * REGION, &p.mAB, 0, (brow ^ 64) + e * 128, bar + B_BL);
                mbar_expect_tx_elect(bar + B_BL, 16384);
                step++;
                if (++slot == NSTAGE) { slot = 0; ph ^= 1; }
            }
            mbar_spin(sb + B_LOW, 0);
            uint32_t aslot = 6;
#pragma unroll 1
            for (; step < 32; step++) {
                const int e = __shfl_sync(0xffffffffu, tab, step);
                const uint32_t bar = sb + 8 * slot;
                tma2d_elect(sb + aslot * REGION, &p.mCre + comp, e * 64, own * 128, bar + B_FULL);
                mbar_expect_tx_elect(bar + B_FULL, 16384);
                mbar_expect_tx_elect(bar + B_BL, 16384);
                mbar_spin(bar + B_EMPTY, ph);
                tma2d_pair_elect(bdst + slot * REGION, &p.mAB, 0, brow + e * 128, bar + B_BL);
                aslot = slot;
                if (++slot == NSTAGE) { slot = 0; ph ^= 1; }
            }
        } else if (warp == 1) {
            cluster_wait();
            if (lane == 0)
                asm volatile("st.async.weak.shared::cluster.mbarrier::complete_tx::bytes.u32 [%0], %1, [%2];"
                             ::"r"(mapa(sb + M_ROLE, rank ^ 1)), "r"(role), "r"(mapa(sb + B_ROLE, rank ^ 1)) : "memory");
            mbar_wait_cluster(sb + B_ROLE, 0);
            if (*(volatile uint32_t*)(smem + M_ROLE) != role) __trap();
            mbar_wait(sb + B_EPOCH, 0);
            const uint32_t want = (*(volatile uint32_t*)(smem + M_EPOCH) + 1u) * 4u;
            const int eh = __shfl_sync(0xffffffffu, tab, 2 + (lane & 3));
            const unsigned int* hp = p.s->pair + (blk * 8 + (eh >> 1)) * 32 + 2 + (eh & 1);
            uint32_t seen = 0;
            int rows[4];
#pragma unroll
            for (int i = 0; i < 4; i++) {
                rows[i] = brow + __shfl_sync(0xffffffffu, tab, 2 + i) * 128;
                mbar_expect_tx_elect(sb + B_BL + 8 * (2 + i), 16384);
            }
            mbar_wait(sb + B_GO1, 0);
            asm volatile(ELECT "prefetch.tensormap [%0];}" ::"l"(&p.mAB) : "memory");
            mbar_wait(sb + B_EMPTY + 8 * 3, 0);
            mbar_spin(sb + B_EMPTY + 8 * 2, 0);
            uint32_t t3 = 0;
#pragma unroll
            for (int i = 0; i < 4; i++) {
                while (!((seen >> i) & 1u)) seen = __ballot_sync(0xffffffffu, ld_relaxed(hp) == want);
                if (i) spin_until(t3 + B_GAP);
                t3 = clk();
                if (i >= 2) mbar_spin(sb + B_EMPTY + 8 * (2 + i), 0);
                tma2d_pair_elect(bdst + (2 + i) * REGION, &p.mAB, 0, rows[i], sb + B_BL + 8 * (2 + i));
            }
            mbar_wait(sb + B_FREE, 0);
            unsigned char* gdst = p.s->ab + (blk * 32 + own + 16) * 16384;
            t3 = clk();
#pragma unroll 1
            for (int i = 0; i < 16; i++) {
                sleep_until<20>(t3);
                t3 += LATE_GAP;
                asm volatile(ELECT "cp.async.bulk.global.shared::cta.bulk_group [%0], [%1], 1024;}"
                             ::"l"(gdst + i * 1024), "r"(sb + 6 * REGION + i * 1024) : "memory");
            }
            bulk_wait_read();
            mbar_arrive_elect(sb + B_FREE + 8);
            mbar_wait(sb + B_PUB, 0);
            if (lane == 0) {
                asm volatile("fence.proxy.async.global;" ::: "memory");
                asm volatile("red.release.gpu.global.add.u32 [%0], 1;" ::"l"(p.s->ready + (cta >> 3) * 32) : "memory");
            }
            __syncwarp();
            __nanosleep(INIT_NS);
            wait_counter(p.s->ready + own * 32, want * 2u);
            mbar_arrive_elect(sb + B_INIT);
            asm volatile(ELECT "prefetch.tensormap [%0];}" ::"l"(&p.mOut) : "memory");
        } else {
            mbar_arrive_elect(sb + B_BL + 8 * (warp & 1));
            uint32_t k = warp == 3 ? 0 : 12;
#define PREFETCH_W() {                                                                                          \
                const char* src = (k >= 8 ? (const char*)p.wd + ((cta >> 5) * 2 + (k >> 1) - 4) * 229376        \
                                          : (const char*)((cta & 32) ? p.wu : p.wg) + ((cta >> 6) * 4 + (k >> 1)) * 229376) \
                                  + ((cta & 31) * 2 + (k & 1)) * 3584;                                          \
                asm volatile(ELECT "cp.async.bulk.prefetch.L2.global [%0], 3584;}" ::"l"(src) : "memory");      \
                k++; }
#pragma unroll 1
            while (k < PF_N0) {
                sleep_until<50>(tstart + PF_T0 + k * PF_GAP);
                __syncwarp();
                PREFETCH_W();
            }
            mbar_wait(sb + B_EPOCH, 0);
            const uint32_t par = (*(volatile uint32_t*)(smem + M_EPOCH) + 1u) & 1u;
            const uint32_t a0 = sb + 16384 + (lane >> 3) * 1028 + ((lane >> 2) & 1) * 144 + (lane & 3) * 32;
            const uint32_t retry = sb + B_RETRY + (warp & 1) * 240;
            uint32_t slot = warp, ph = 0, rph = 0;
            uint32_t j = ffn ? warp & 1 : 12;
#pragma unroll 1
            for (int step = warp; step < 32 || j < 12;) {
                const bool go = step < (j < 8 ? 32 - NA : 32);
                if (go) {
                    const uint32_t bar = sb + 8 * slot;
                    mbar_wait(bar + B_BL, ph);
#pragma unroll 1
                    while (__any_sync(0xffffffffu, stale_tags(a0 + slot * REGION, par) & 1u)) {
                        const int row = blk * 4096 + __shfl_sync(0xffffffffu, tab, step) * 128;
                        mbar_expect_tx_elect(retry, 16384);
                        tma2d_elect(sb + slot * REGION + 16384, &p.mAB, 0, row, retry);
                        tma2d_elect(sb + slot * REGION + 24576, &p.mAB, 0, row + 64, retry);
                        mbar_spin(retry, rph);
                        rph ^= 1u;
                    }
                    mbar_arrive_elect<4>(bar + B_FULL);
                }
                if (j < 12 && step >= FFN_S0 + j * FFN_W / 4 && __any_sync(0xffffffffu, mbar_test(sb + B_FREE + 2 * (j & 12), 0))) {
                    const uint32_t fb = sb + B_FFN + 4 * (j & 6);
                    if (!(j & 1)) mbar_expect_tx_elect(fb, 8192);
                    tma2d_elect(sb + 6 * REGION + ((j + 4) & 7) * 4096, j < 8 ? &p.mWg + (j & 1) : &p.mWd,
                                j < 8 ? fp * 32 : rank * 256, j < 8 ? rank * 256 + (j >> 1) * 64 : fp * 32 + j * 8 - 64, fb);
                    j += 2;
                }
                if (k < 12) PREFETCH_W();
                if (go) {
                    step += 2;
                    slot += 2;
                    if (slot >= NSTAGE) { slot -= NSTAGE; ph ^= 1; }
                }
            }
        }
    } else if (warp < 8) {
        const int t = tid - 128, w = warp - 4;
        if (t == 0) {
            volatile unsigned int* ep = &p.s->pair[(blk * 8 + (own >> 1)) * 32 + rank];
            const uint32_t epoch = *ep;
            *(volatile uint32_t*)(smem + M_EPOCH) = epoch;
            *ep = epoch + 1;
        }
        mbar_arrive_if(sb + B_EPOCH, t == 0);
        const uint4 gw0 = ldg_nc<0>(p.gate_w + lane * 8), gw1 = ldg_nc<512>(p.gate_w + lane * 8);
        const uint4 rw0 = ldg_nc<0>(p.w_r + lane * 8), rw1 = ldg_nc<512>(p.w_r + lane * 8);
        mbar_wait(sb + B_EPOCH, 0);
        const uint32_t par = (*(volatile uint32_t*)(smem + M_EPOCH) + 1u) & 1u;
        mbar_wait(sb + B_F + 8 * ROUTER_C, 0);
        const int row0 = cta * 16 + w * 4;
        uint4 xr[8];
        {
            const char* xp = (const char*)p.x + (uint32_t)row0 * (D_ * 2) + lane * 16;
            xr[0] = ldg_nc<0>(xp);    xr[1] = ldg_nc<512>(xp);  xr[2] = ldg_nc<1024>(xp); xr[3] = ldg_nc<1536>(xp);
            xr[4] = ldg_nc<2048>(xp); xr[5] = ldg_nc<2560>(xp); xr[6] = ldg_nc<3072>(xp); xr[7] = ldg_nc<3584>(xp);
            float a[8];
#pragma unroll
            for (int i = 0; i < 4; i++) {
                const uint32_t xv[8] = {xr[2 * i].x, xr[2 * i].y, xr[2 * i].z, xr[2 * i].w,
                                        xr[2 * i + 1].x, xr[2 * i + 1].y, xr[2 * i + 1].z, xr[2 * i + 1].w};
                const uint32_t gv[8] = {gw0.x, gw0.y, gw0.z, gw0.w, gw1.x, gw1.y, gw1.z, gw1.w};
                const uint32_t rv[8] = {rw0.x, rw0.y, rw0.z, rw0.w, rw1.x, rw1.y, rw1.z, rw1.w};
                float u = 0.f, v = 0.f;
#pragma unroll
                for (int j = 0; j < 8; j++) {
                    const uint32_t pr = hmul2_bf16(xv[j], gv[j]);
                    u += bflo(pr); u += bfhi(pr);
                    v = fmaf(bflo(xv[j]), bflo(rv[j]), v); v = fmaf(bfhi(xv[j]), bfhi(rv[j]), v);
                }
                a[i] = u; a[4 + i] = v;
            }
            mbar_wait(sb + B_EARLY, 0);
            halve<4, 16>(a); halve<2, 8>(a); halve<1, 4>(a);
            a[0] += __shfl_xor_sync(0xffffffffu, a[0], 1);
            a[0] += __shfl_xor_sync(0xffffffffu, a[0], 2);
            const int row = row0 + ((lane >> 2) & 3);
            const float gate = rbf(sigmoidf_(rbf(a[0])));
            if (lane < 16 && (lane & 3) == 0)
                asm volatile("st.relaxed.gpu.global.u32 [%0], %1;" ::"l"(&p.s->gate[row]), "r"(tagf(gate, par)) : "memory");
            const uint32_t best = __reduce_max_sync(0xffffffffu, lane >= 16 ? router_key(a[0], row) : 0u);
            if (lane == 0) *(volatile uint32_t*)(smem + M_KEY + w * 4) = best;
            side_bar();
            if (t < 8) {
                const uint4 k = *(const uint4*)(smem + M_KEY);
                asm volatile("{.reg .b32 old; atom.relaxed.gpu.global.exch.b32 old, [%0], %1;}" ::"l"(&p.s->keys[t * NCTA + cta]),
                             "r"(max(max(k.x, k.y), max(k.z, k.w)) | (par << 15)) : "memory");
            }
            const uint32_t og = pack_bf16(1.f - gate, 1.f - gate);
#pragma unroll
            for (int i = 0; i < 8; i++) {
                const uint32_t o = __shfl_sync(0xffffffffu, og, 4 * (i >> 1));
                xr[i] = make_uint4(hmul2_bf16(o, xr[i].x), hmul2_bf16(o, xr[i].y), hmul2_bf16(o, xr[i].z), hmul2_bf16(o, xr[i].w));
            }
        }
        mbar_wait(sb + B_FREE, 0);
        __nanosleep(KEY_NS);
        if (w == 0) {
            const uint4 k4 = wait_tags(p.s->keys + gpc * NCTA + lane * 4, 15, par);
            const uint32_t k = __reduce_max_sync(0xffffffffu, max(max(k4.x, k4.y), max(k4.z, k4.w)));
            sts128<M_XS>(sb + lane * 16, ldg_nc<0>(p.x + (0x7fff - (k & 0x7fffu)) * D_ + rank * 256 + lane * 8));
        } else if (w == 1) {
            const uint4 g4 = wait_tags(p.s->gate + own * 128 + lane * 4, 0, par);
            const uint32_t sg = comp ? 0x80000000u : 0u;
            sts128<M_G>(sb + lane * 16, make_uint4((g4.x & ~1u) ^ sg, (g4.y & ~1u) ^ sg, (g4.z & ~1u) ^ sg, (g4.w & ~1u) ^ sg));
            mbar_arrive_warp(sb + B_GATE);
        }
        side_bar();
        char* op = (char*)p.out + (uint32_t)row0 * (D_ * 2) + lane * 16;
        float a[16];
#pragma unroll
        for (int i = 0; i < 16; i++) a[i] = 0.f;
#pragma unroll 1
        for (int i = 0; i < 4; i++) {
            if (i == 2) {
                mbar_wait(sb + B_FREE + 8, 0);
                const uint32_t t2 = clk() + w * (INIT_GAP / 4);
#pragma unroll
                for (int j = 0; j < 8; j++) {
                    sleep_until<20>(t2 + j * INIT_GAP);
                    *(uint4*)(op + j * 512) = xr[j];
                }
                mbar_arrive_warp(sb + B_PUB);
            }
            if (ffn) {
                const float xs0 = __bfloat162float(((const bf16*)(smem + M_XS))[64 * i + (t >> 2)]);
                const float xs1 = __bfloat162float(((const bf16*)(smem + M_XS))[64 * i + 32 + (t >> 2)]);
                const uint32_t wa = sb + 6 * REGION + (i ^ 2) * 8192 + t * 16;
                mbar_wait(sb + B_FFN + 8 * i, 0);
                const uint4 v0 = lds128(wa), v1 = lds128(wa + 4096), v2 = lds128(wa + 2048), v3 = lds128(wa + 6144);
                const uint32_t w0[8] = {v0.x, v0.y, v0.z, v0.w, v1.x, v1.y, v1.z, v1.w};
                const uint32_t w1[8] = {v2.x, v2.y, v2.z, v2.w, v3.x, v3.y, v3.z, v3.w};
#pragma unroll
                for (int k = 0; k < 8; k++) {
                    a[2 * k] = fmaf(xs1, bflo(w1[k]), fmaf(xs0, bflo(w0[k]), a[2 * k]));
                    a[2 * k + 1] = fmaf(xs1, bfhi(w1[k]), fmaf(xs0, bfhi(w0[k]), a[2 * k + 1]));
                }
                if (i == 1) {
                    side_bar();
                    mbar_arrive_if(sb + B_FREE + 16, t == 0);
                }
            }
        }
        if (!ffn) {
            mbar_arrive_warp(sb + B_LOW);
            return;
        }
        halve<8, 16>(a); halve<4, 8>(a); halve<2, 4>(a);
        const uint32_t ho = (lane >> 4) * 128 + (lane & 3) * 32 + ((lane >> 2) & 3) * 8;
        cluster_wait();
#pragma unroll
        for (int k = 0; k < 2; k++)
            asm volatile("st.async.weak.shared::cluster.mbarrier::complete_tx::bytes.v2.f32 [%0], {%1,%2}, [%3];"
                         ::"r"(mapa(sb + (k ? 6 * REGION + w * 512 : M_HX + w * 256) + ho, rank ^ k ^ 1)), "f"(a[0]), "f"(a[1]),
                           "r"(mapa(sb + B_HX, rank ^ k ^ 1)) : "memory");
        mbar_wait_cluster(sb + B_HX, 0);
        const float *hx = (const float*)(smem + M_HX) + lane, *hy = (const float*)(smem + 6 * REGION) + lane;
        const float gs = rbf(((hx[0] + hy[0]) + (hx[64] + hy[128])) + ((hx[128] + hy[256]) + (hx[192] + hy[384])));
        const float us = rbf(((hx[32] + hy[32]) + (hx[96] + hy[160])) + ((hx[160] + hy[288]) + (hx[224] + hy[416])));
        float* hrow = (float*)(smem + M_XS) + w * 32;
        hrow[lane] = rbf(rbf(gs * sigmoidf_(gs)) * us);
        fence_proxy_async_smem();
        mbar_arrive_warp(sb + B_LOW);
        float o0 = 0.f, o1 = 0.f;
#pragma unroll 1
        for (int i = 0; i < 2; i++) {
            float4 hv[4];
            uint32_t vd[16];
#pragma unroll
            for (int k = 0; k < 4; k++) hv[k] = *(const float4*)&hrow[i * 16 + k * 4];
            mbar_wait(sb + B_FFN + 8 * i, 1);
#pragma unroll
            for (int k = 0; k < 16; k++) vd[k] = *(const volatile uint32_t*)(smem + 6 * REGION + 16384 + i * 8192 + k * 512 + t * 4);
#pragma unroll
            for (int k = 0; k < 4; k++) {
                o0 = fmaf(hv[k].x, bflo(vd[4 * k]), o0);     o1 = fmaf(hv[k].x, bfhi(vd[4 * k]), o1);
                o0 = fmaf(hv[k].y, bflo(vd[4 * k + 1]), o0); o1 = fmaf(hv[k].y, bfhi(vd[4 * k + 1]), o1);
                o0 = fmaf(hv[k].z, bflo(vd[4 * k + 2]), o0); o1 = fmaf(hv[k].z, bfhi(vd[4 * k + 2]), o1);
                o0 = fmaf(hv[k].w, bflo(vd[4 * k + 3]), o0); o1 = fmaf(hv[k].w, bfhi(vd[4 * k + 3]), o1);
            }
        }
        asm volatile("st.relaxed.gpu.global.v2.u32 [%0], {%1,%2};" ::"l"(&p.s->part[fp * D_ + rank * 256 + t * 2]),
                     "r"(tagf(o0, par)), "r"(tagf(o1, par)) : "memory");
        red_inc_if(p.s->phint + ((rank * 2 + (w >> 1)) * 16 + (fp >> 2)) * 8 + lane, lane == 0);
    } else {
        const int wg = (warp >> 2) - 2, wq = warp & 3;
        const uint32_t sbd = ((sb & 0x3FFFF) >> 4) + 0x10000;
        const bool lead = (tid & 127) == 0;
        const bool lead0 = lead && !wg, lead1 = lead && wg;
        const int q = lane & 3;
        float acc[64];
        const uint32_t rE = mapa(sb + B_EMPTY, rank ^ 1);
#define RELEASE(n, slot, pred) release_pair<n>(sb + B_EMPTY + 8 * (slot), rE + 8 * (slot), pred)
        const uint32_t ioff = wq * 4096 + (lane >> 2) * 64 + ((q ^ (lane >> 3)) << 4);
        const uint32_t sdst = pin(sb + 6 * REGION + (wg ? 0 : 16384) + ioff);
        unsigned char* gdst = pin(p.s->ab + (blk * 32 + own) * 16384 + ioff);
        unsigned int* hint = pin(p.s->pair + (blk * 8 + (own >> 1)) * 32 + 2 + rank + lane);
        uint32_t par = 0;
#define GET_PAR() mbar_spin(sb + B_EPOCH, 0); par = (*(volatile uint32_t*)(smem + M_EPOCH) + 1u) & 1u
        cluster_wait();
        if (wg) mbar_spin(sb + B_G0, 0);
#pragma unroll
        for (int c = 0; c < 8; c++) {
            if (c == 1 && wg) {
                wg_wait<0>();
                RELEASE(1, 1, lead);
                GET_PAR();
                mbar_spin(sb + B_G1, 0);
            }
            if (!wg || c < 3 || c == 4) mbar_spin(sb + (!wg || c == 0 ? B_F + 8 * c : c == 1 ? B_GO1 : c == 2 ? B_G2 : B_G4), 0);
            const uint32_t xa = sbd + wg * ((off_xl(c) - off_xe(c)) / 16);
            wg_fence();
#pragma unroll
            for (int kk = 0; kk < 4; kk++) {
                wgmma128<0>(acc, desc128(xa + off_xe(c) / 16 + 2 * kk), desc128(sbd + off_d(c) / 16 + 2 * kk), (c | kk) != 0);
                if (c == 7 && kk == 0) wg_commit();
            }
            wg_commit();
            if (c == 5 && !wg) { GET_PAR(); }
            if (c == 7) {
                if (wg) mbar_spin(sb + B_FULL, 0);
                wg_wait<2>();
                mbar_arrive_if(sb + B_GO1, lead0);
            }
            if (c == 4 || c >= 6) wg_wait<1>();
            if (c == 4) { mbar_arrive_if(sb + B_XE, lead0); RELEASE(1, 1, lead0); RELEASE(2, 2, lead1); RELEASE(2, 3, lead1); }
            if (c == 6) RELEASE(2, 4 * wg, lead);
            if (c == 7) mbar_arrive_if(sb + B_GO0, lead1);
        }
        const int rh = wg ^ comp;
        const uint32_t da0 = sbd + rh * 512, db0 = sbd - 0x10000 + 0x400000 + 1024;
        const uint32_t dbe = db0 + 6 * (REGION / 16), dbl = dbe - 1024;
#define STEP(da, db, first) wg_fence();                                                                     \
        _Pragma("unroll") for (int kk = 0; kk < 4; kk++)                                                    \
            wgmma128<1>(acc, desc128((da) + kk * 2), desc64((db) + kk * 256), !((first) && kk == 0));       \
        wg_commit()
#define ACC(i, j) (16 * ((i) >> 1) + 2 * ((i) & 1) + 4 * (j))
#define PW(i, j) pack_bf16(acc[ACC(i, j)], acc[ACC(i, j) + 1])
#define PT(i, j) ((j) == ((i) >> 1) ? (PW(i, j) & ~1u) | par : PW(i, j))
#define PIECE(i) make_uint4(PT(i, 0), PT(i, 1), PT(i, 2), PT(i, 3))
#define PIECES(F) F(0); F(1); sched_cut(); F(2); F(3); F(4); F(5); F(6); F(7)
        if (wg) {
            wg_wait<0>();
            fence_regs(acc);
#define STS1(i) sts128<(i) * 512>(sdst, PIECE(i))
            PIECES(STS1);
            STEP(da0, dbe, true);
            fence_proxy_async_smem();
            mbar_arrive_warp(sb + B_FULL + 8);
            RELEASE(1, 5, lead);
        } else {
            wg_wait<0>();
            fence_regs(acc);
            uint4 v[8];
#define STG0(i) v[i] = PIECE(i); stg128<(i) * 512>(gdst, v[i]); if (HINT_AT == (i) + 1) red_inc_if(hint, own < 6 && lane == 0)
            PIECES(STG0);
            mbar_spin(sb + B_EPOCH, 0);
            asm volatile("bar.sync 2, 128;" ::: "memory");
#define STS0(i) if ((i) % 2 == 0) mbar_spin(sb + B_EPOCH, 0); sts128<(i) * 512>(sdst, v[i])
            STS0(0); STS0(1); STS0(2); STS0(3); STS0(4); STS0(5); STS0(6); STS0(7);
            fence_proxy_async_smem();
            mbar_arrive_warp(sb + B_FULL);
            RELEASE(1, 5, lead);
            mbar_arrive_if(sb + B_EARLY, lead);
            mbar_spin(sb + B_FULL, 0);
            mbar_spin(sb + B_GO0, 0);
            STEP(da0, dbe, true);
        }
#pragma unroll
        for (int step = 1; step < 3; step++) {
            mbar_spin(sb + B_FULL + 8 * step, 0);
            STEP(da0 + step * (REGION / 16), step == 1 ? dbl : db0 + step * (REGION / 16), false);
            wg_wait<1>();
            RELEASE(1, step - 1, lead);
            mbar_arrive_if(sb + B_FREE + 8 * (step - 1), lead);
        }
        int slot = 3, ph = 0, pslot = 2;
        float g0 = 0.f, g1 = 0.f;
        uint32_t oa = 0;
#pragma unroll 1
        for (int step = 3; step < 26; step++) {
            mbar_wait(sb + B_FULL + 8 * slot, ph);
            STEP(da0 + slot * (REGION / 16), db0 + slot * (REGION / 16), false);
            if (step == SETUP + wg) {
                const int r0 = rh * 64 + wq * 16 + (lane >> 2), sr = ((lane >> 2) & 1) * 4 + (lane >> 3);
                mbar_wait(sb + B_GATE, 0);
                g0 = ((const volatile float*)(smem + M_G))[r0];
                g1 = ((const volatile float*)(smem + M_G))[r0 + 8];
                oa = pin(wg ? ((own * 128 + (r0 & ~1)) * D_ + tn * 128 + (lane & 7) * 8) * 2u
                            : sb + rh * 8192 + wq * 2048 + sr * 128 + ((q ^ sr) << 4));
            }
            wg_wait<1>();
            RELEASE(1, pslot, lead);
            pslot = slot;
            if (++slot == NSTAGE) { slot = 0; ph ^= 1; }
        }
        mbar_wait(sb + B_FULL + 8 * 2, 0);
        wg_fence();
#pragma unroll
        for (int kk = 0; kk < 4; kk++) {
            if (kk == HSK) {
                wg_commit();
                if (wg) {
                    wg_wait<1>();
                    RELEASE(1, 1, lead);
                    mbar_wait(sb + B_INIT, 0);
                    mbar_wait(sb + B_TAIL, 0);
                }
                wg_fence();
            }
            wgmma128<1>(acc, desc128(da0 + 2 * (REGION / 16) + kk * 2), desc64(db0 + 2 * (REGION / 16) + kk * 256), 1);
        }
        wg_commit();
        if (!wg) {
            wg_wait<2>();
            RELEASE(1, 1, lead);
        }
        slot = 3;
#pragma unroll 1
        for (int step = 27; step < 32; step++) {
            if (!wg) mbar_wait(sb + B_FULL + 8 * slot, ph);
            STEP(da0 + (step < 32 - NA ? slot : step == 32 - NA ? 6 : pslot) * (REGION / 16), db0 + slot * (REGION / 16), false);
            pslot = slot;
            if (++slot == NSTAGE) { slot = 0; ph ^= 1; }
        }
#define OW(i, j) pack_bf16((((i) & 1) ? g1 : g0) * acc[ACC(i, j)], (((i) & 1) ? g1 : g0) * acc[ACC(i, j) + 1])
        if (!wg) {
            wg_wait<1>();
            mbar_arrive_if(sb + B_TAIL, lead);
            const uint32_t st0 = sb + rh * 8192 + wq * 2048;
            mbar_wait(sb + B_INIT, 0);
            wg_wait<0>();
            fence_regs(acc);
#define OSTS(i) sts128<((i) >> 2) * REGION + ((i) & 1) * 1024>(((i) & 2) ? oa ^ 64 : oa, make_uint4(OW(i, 0), OW(i, 1), OW(i, 2), OW(i, 3)))
#define ORED(h) fence_proxy_async_smem(); __syncwarp();                                                     \
            asm volatile(ELECT "cp.reduce.async.bulk.tensor.4d.global.shared::cta.add.tile.bulk_group [%0, {%2,%3,%3,%4}], [%1];}" \
                         ::"l"(&p.mOut), "r"(st0 + (h) * REGION), "r"(tn * 128 + (h) * 64), "r"(0), "r"(own * 16 + rh * 8 + wq * 2) : "memory")
            OSTS(0); OSTS(1); OSTS(2); OSTS(3);
            ORED(0);
            sched_cut();
            OSTS(4); OSTS(5); OSTS(6); OSTS(7);
            ORED(1);
            bulk_wait_read();
        } else {
            const bool odd = lane & 4;
            char *op = pin((char*)p.out + oa), *opb = pin((char*)p.out + (oa ^ 64) + 1024);
            sched_cut();
            wg_wait<0>();
            fence_regs(acc);
#define REDLINE(i) {                                                                                        \
                uint32_t k[4], r[4];                                                                        \
                _Pragma("unroll") for (int j = 0; j < 4; j++) {                                             \
                    r[j] = __shfl_xor_sync(0xffffffffu, OW((i) + 2, j), 4);                                 \
                    k[j] = OW(i, j);                                                                        \
                }                                                                                           \
                red_bf16x8<((i) & 1) * 8192 + ((i) >> 2) * 128>(op, odd ? r[0] : k[0], odd ? r[1] : k[1], odd ? r[2] : k[2], odd ? r[3] : k[3]);  \
                red_bf16x8<((i) & 1) * 8192 + ((i) >> 2) * 128>(opb, odd ? k[0] : r[0], odd ? k[1] : r[1], odd ? k[2] : r[2], odd ? k[3] : r[3]); }
            REDLINE(0)
            sched_cut();
            REDLINE(4) REDLINE(1) REDLINE(5)
        }
    }
}

typedef CUresult (*EncodeTiledFn)(CUtensorMap*, CUtensorMapDataType, cuuint32_t, void*, const cuuint64_t*, const cuuint64_t*,
                                  const cuuint32_t*, const cuuint32_t*, CUtensorMapInterleave, CUtensorMapSwizzle,
                                  CUtensorMapL2promotion, CUtensorMapFloatOOBfill);

static void make_map(EncodeTiledFn enc, CUtensorMap* m, const void* base, uint64_t cols, uint64_t rows, uint32_t box_rows,
                     CUtensorMapSwizzle sw = CU_TENSOR_MAP_SWIZZLE_128B, uint32_t box_cols = 64) {
    cuuint64_t dims[2] = {cols, rows};
    cuuint64_t str[1] = {cols * 2};
    cuuint32_t box[2] = {box_cols, box_rows};
    cuuint32_t es[2] = {1, 1};
    enc(m, CU_TENSOR_MAP_DATA_TYPE_BFLOAT16, 2, (void*)base, dims, str, box, es, CU_TENSOR_MAP_INTERLEAVE_NONE,
        sw, CU_TENSOR_MAP_L2_PROMOTION_L2_128B, CU_TENSOR_MAP_FLOAT_OOB_FILL_NONE);
}

static void make_map_x2(EncodeTiledFn enc, CUtensorMap* m, const void* base) {
    cuuint64_t dims[3] = {64, S_, 8};
    cuuint64_t str[2] = {D_ * 2, 128};
    cuuint32_t box[3] = {64, 64, 2};
    cuuint32_t es[3] = {1, 1, 1};
    enc(m, CU_TENSOR_MAP_DATA_TYPE_BFLOAT16, 3, (void*)base, dims, str, box, es, CU_TENSOR_MAP_INTERLEAVE_NONE,
        CU_TENSOR_MAP_SWIZZLE_128B, CU_TENSOR_MAP_L2_PROMOTION_L2_128B, CU_TENSOR_MAP_FLOAT_OOB_FILL_NONE);
}

static void make_map_out(EncodeTiledFn enc, CUtensorMap* m, const void* base) {
    cuuint64_t dims[4] = {D_, 4, 2, S_ / 8};
    cuuint64_t str[3] = {2 * D_ * 2, D_ * 2, 8 * D_ * 2};
    cuuint32_t box[4] = {64, 4, 2, 2};
    cuuint32_t es[4] = {1, 1, 1, 1};
    enc(m, CU_TENSOR_MAP_DATA_TYPE_BFLOAT16, 4, (void*)base, dims, str, box, es, CU_TENSOR_MAP_INTERLEAVE_NONE,
        CU_TENSOR_MAP_SWIZZLE_128B, CU_TENSOR_MAP_L2_PROMOTION_NONE, CU_TENSOR_MAP_FLOAT_OOB_FILL_NONE);
}

extern "C" void kernel_launch(void* const* d_in, const int* in_sizes, int n_in, void* d_out, int out_size) {
    (void)in_sizes; (void)n_in; (void)out_size;
    static EncodeTiledFn enc = nullptr;
    static bool fused_ok = false;
    static void* scratch = nullptr;
    if (!enc) {
        void* fn = nullptr;
        cudaDriverEntryPointQueryResult q;
        cudaGetDriverEntryPoint("cuTensorMapEncodeTiled", &fn, cudaEnableDefault, &q);
        enc = (EncodeTiledFn)fn;
        cudaGetSymbolAddress(&scratch, g_s);
        cudaFuncSetAttribute(fused_kernel, cudaFuncAttributeMaxDynamicSharedMemorySize, SMEM_BYTES);
        int dev = 0, nsm = 0, ncl = 0;
        cudaGetDevice(&dev);
        cudaDeviceGetAttribute(&nsm, cudaDevAttrMultiProcessorCount, dev);
        cudaLaunchConfig_t cfg = {};
        cfg.gridDim = dim3(132); cfg.blockDim = dim3(NTHREADS); cfg.dynamicSmemBytes = SMEM_BYTES;
        cudaLaunchAttribute at;
        at.id = cudaLaunchAttributeClusterDimension;
        at.val.clusterDim.x = 2; at.val.clusterDim.y = 1; at.val.clusterDim.z = 1;
        cfg.attrs = &at; cfg.numAttrs = 1;
        fused_ok = cudaOccupancyMaxActiveClusters(&ncl, fused_kernel, &cfg) == cudaSuccess && nsm == 132 && ncl == 66;
        (void)cudaGetLastError();
    }
    if (!fused_ok) {
        const bf16* const* in = (const bf16* const*)d_in;
        fb_hidden<<<S_, D_, 0, cudaStreamPerThread>>>(in[0], in[3], in[4], in[10], in[6]);
        fb_ffn1<<<F_ / 128, 128, 0, cudaStreamPerThread>>>(in[0], in[7], in[8]);
        fb_ffn2<<<D_ / 64, 64, 0, cudaStreamPerThread>>>(in[9]);
        fb_seq<<<S_, D_, 0, cudaStreamPerThread>>>(in[0], in[1], in[2], (bf16*)d_out);
        return;
    }
    Params p;
    p.s = (Scratch*)scratch;
    p.x = (const bf16*)d_in[0];
    p.w_r = (const bf16*)d_in[6];
    p.wg = (const bf16*)d_in[7];
    p.wu = (const bf16*)d_in[8];
    p.wd = (const bf16*)d_in[9];
    p.gate_w = (const bf16*)d_in[10];
    p.out = (bf16*)d_out;
    make_map(enc, &p.mX1, d_in[0], D_, S_, 64);
    make_map_x2(enc, &p.mX2, d_in[0]);
    make_map(enc, &p.mCre, d_in[1], S_, S_, 128);
    make_map(enc, &p.mCim, d_in[2], S_, S_, 128);
    make_map(enc, &p.mDre, d_in[3], D_, D_, 128);
    make_map(enc, &p.mDim, d_in[4], D_, D_, 128);
    make_map(enc, &p.mAB, scratch, 64, 8 * 32 * 128, 64, CU_TENSOR_MAP_SWIZZLE_NONE);
    make_map_out(enc, &p.mOut, d_out);
    make_map(enc, &p.mWg, d_in[7], F_, D_, 64, CU_TENSOR_MAP_SWIZZLE_NONE, 32);
    make_map(enc, &p.mWu, d_in[8], F_, D_, 64, CU_TENSOR_MAP_SWIZZLE_NONE, 32);
    make_map(enc, &p.mWd, d_in[9], D_, F_, 8, CU_TENSOR_MAP_SWIZZLE_NONE, 256);
    fused_kernel<<<132, NTHREADS, SMEM_BYTES, cudaStreamPerThread>>>(p);
}
```

```cpp
#include <cuda_runtime.h>
#include <cuda.h>
#include <cuda_bf16.h>
#include <stdint.h>

typedef __nv_bfloat16 bf16;

constexpr int S_ = 2048, D_ = 512, F_ = 1792;
constexpr int NCTA = 128;
constexpr int NTHREADS = 512;
constexpr int NSTAGE = 6;
constexpr int REGION = 32768;
constexpr int FFN_CTAS = F_ / 16;
constexpr uint32_t SPIN_LIMIT = 1u << 22;
constexpr int HOLD = 200;
constexpr int PACE = 270;
constexpr int PACE0 = 100;
constexpr int A_GAP = 230;
constexpr int B_GAP = 240;
constexpr int LATE_GAP = 240;
constexpr int INIT_GAP = 360;
constexpr int INIT_NS = 300;
constexpr int PF_T0 = 3000;
constexpr int PF_GAP = 850;
constexpr int PF_N0 = 4;
constexpr int FFN_S0 = 4;
constexpr int FFN_W = 7;
constexpr int ROUTER_C = 4;
constexpr int HINT_AT = 5;
constexpr int SUM_T0 = 15000;
constexpr int PS1 = 24;
constexpr int NA = 3;
constexpr int KEY_NS = 300;
constexpr int SETUP = 13;
constexpr int T0 = 8;
constexpr int HSK = 2;

constexpr int OFF_MISC = 7 * REGION;
constexpr int B_F = OFF_MISC;
constexpr int B_G1 = B_F + 64;
constexpr int B_G4 = B_G1 + 8;
constexpr int B_XE = B_G4 + 8;
constexpr int B_GO1 = B_XE + 8;
constexpr int B_GO0 = B_GO1 + 8;
constexpr int B_EPOCH = B_GO0 + 8;
constexpr int B_RETRY = B_EPOCH + 8;
constexpr int B_INIT = B_RETRY + 8;
constexpr int B_FULL = B_INIT + 8;
constexpr int B_EMPTY = B_FULL + 48;
constexpr int B_PUB = B_EMPTY + 48;
constexpr int B_FREE = B_PUB + 8;
constexpr int B_BL = B_FREE + 24;
constexpr int B_TAIL = B_BL + 48;
constexpr int B_HX = B_TAIL + 8;
constexpr int B_FFN = B_HX + 8;
constexpr int B_ROLE = B_FFN + 40;
constexpr int B_EARLY = B_ROLE + 8;
constexpr int B_GATE = B_EARLY + 8;
constexpr int B_G2 = B_GATE + 8;
constexpr int B_LOW = B_G2 + 8;
constexpr int B_G0 = B_LOW + 8;
constexpr int M_EPOCH = B_G0 + 8;
constexpr int M_ROLE = M_EPOCH + 4;
constexpr int M_KEY = OFF_MISC + 416;
constexpr int M_HX = OFF_MISC + 512;
constexpr int M_G = M_HX + 1024;
constexpr int M_XS = M_G + 512;
constexpr int SMEM_BYTES = 232448;
static_assert(M_ROLE + 4 <= M_KEY && M_XS + 512 <= SMEM_BYTES, "smem");

struct Scratch {
    unsigned char ab[8 * 32 * 16384];
    unsigned int pair[65 * 32];
    unsigned int ready[16 * 32];
    unsigned int gate[S_];
    unsigned int part[FFN_CTAS / 2 * D_];
    unsigned int phint[4 * 16 * 8];
    unsigned int keys[8 * NCTA];
};
__device__ __align__(1024) Scratch g_s;

struct Params {
    Scratch* s;
    bf16* out;
    const bf16 *x, *gate_w, *w_r, *wg, *wu, *wd;
    CUtensorMap mDre, mDim, mX1, mX2, mCre, mCim, mAB, mOut, mWg, mWu, mWd;
};

#define ELECT "{.reg .pred p; elect.sync _|p, 0xffffffff; @p "
__device__ __forceinline__ uint32_t smem_u32(const void* p) { return (uint32_t)__cvta_generic_to_shared(p); }
__device__ __forceinline__ uint32_t clk() { return (uint32_t)clock64(); }
__device__ __forceinline__ void spin_until(uint32_t t) { while ((int)(clk() - t) < 0) {} }
template <int NS>
__device__ __forceinline__ void sleep_until(uint32_t t) { while ((int)(clk() - t) < 0) __nanosleep(NS); }
__device__ __forceinline__ void mbar_init_elect(uint32_t bar, uint32_t cnt) {
    asm volatile(ELECT "mbarrier.init.shared::cta.b64 [%0], %1;}" ::"r"(bar), "r"(cnt) : "memory");
}
__device__ __forceinline__ void mbar_expect_tx_elect(uint32_t bar, uint32_t bytes) {
    asm volatile(ELECT "mbarrier.arrive.expect_tx.shared::cta.b64 _, [%0], %1;}" ::"r"(bar), "r"(bytes) : "memory");
}
template <int N = 1>
__device__ __forceinline__ void mbar_arrive_elect(uint32_t bar) {
    asm volatile(ELECT "mbarrier.arrive.shared::cta.b64 _, [%0], %1;}" ::"r"(bar), "n"(N) : "memory");
}
__device__ __forceinline__ void mbar_arrive_if(uint32_t bar, bool pred) {
    asm volatile("{.reg .pred p; setp.ne.b32 p, %1, 0; @p mbarrier.arrive.shared::cta.b64 _, [%0];}" ::"r"(bar), "r"((int)pred) : "memory");
}
__device__ __forceinline__ void mbar_arrive_warp(uint32_t bar) {
    __syncwarp();
    mbar_arrive_if(bar, (threadIdx.x & 31) == 0);
}
template <int N>
__device__ __forceinline__ void release_pair(uint32_t bar, uint32_t rbar, bool pred) {
    asm volatile("{.reg .pred p; setp.ne.b32 p, %2, 0; @p mbarrier.arrive.shared::cta.b64 _, [%0], %3;"
                 " @p mbarrier.arrive.shared::cluster.b64 _, [%1], %3;}" ::"r"(bar), "r"(rbar), "r"((int)pred), "n"(N) : "memory");
}
__device__ __forceinline__ uint32_t mapa(uint32_t a, uint32_t cta) {
    uint32_t r;
    asm volatile("mapa.shared::cluster.u32 %0, %1, %2;" : "=r"(r) : "r"(a), "r"(cta));
    return r;
}
__device__ __forceinline__ bool mbar_test(uint32_t bar, uint32_t parity) {
    uint32_t ok;
    asm volatile("{.reg .pred p; mbarrier.test_wait.parity.shared::cta.b64 p, [%1], %2; selp.u32 %0,1,0,p;}"
                 : "=r"(ok) : "r"(bar), "r"(parity) : "memory");
    return ok;
}
__device__ __forceinline__ void mbar_wait(uint32_t bar, uint32_t parity) {
    asm volatile("{.reg .pred p, q; .reg .u32 n; mov.u32 n, 0;\n"
                 "W%=: mbarrier.try_wait.parity.shared::cta.b64 p, [%0], %1;\n"
                 "add.u32 n, n, 1; setp.lt.and.u32 q, n, %2, !p; @q bra W%=; @!p trap;}" ::"r"(bar), "r"(parity), "n"(SPIN_LIMIT) : "memory");
}
__device__ __forceinline__ void mbar_wait_cluster(uint32_t bar, uint32_t parity) {
    asm volatile("{.reg .pred p, q; .reg .u32 n; mov.u32 n, 0;\n"
                 "W%=: mbarrier.try_wait.parity.acquire.cluster.shared::cta.b64 p, [%0], %1;\n"
                 "add.u32 n, n, 1; setp.lt.and.u32 q, n, %2, !p; @q bra W%=; @!p trap;}" ::"r"(bar), "r"(parity), "n"(SPIN_LIMIT) : "memory");
}
__device__ __forceinline__ void mbar_spin(uint32_t bar, uint32_t parity) {
    asm volatile("{.reg .pred p;\nW%=: mbarrier.try_wait.parity.shared::cta.b64 p, [%0], %1; @!p bra W%=;}" ::"r"(bar), "r"(parity) : "memory");
}
__device__ __forceinline__ void cluster_arrive() { asm volatile("barrier.cluster.arrive.relaxed.aligned;" ::: "memory"); }
__device__ __forceinline__ void cluster_wait() { asm volatile("barrier.cluster.wait.acquire.aligned;" ::: "memory"); }
__device__ __forceinline__ void cta_bar() { asm volatile("bar.sync 0, 512;" ::: "memory"); }
__device__ __forceinline__ void side_bar() { asm volatile("bar.sync 1, 128;" ::: "memory"); }
__device__ __forceinline__ void tma2d_elect(uint32_t dst, const CUtensorMap* m, int c0, int c1, uint32_t bar) {
    asm volatile(ELECT "cp.async.bulk.tensor.2d.shared::cluster.global.mbarrier::complete_tx::bytes [%0], [%1, {%3,%4}], [%2];}"
                 ::"r"(dst), "l"(m), "r"(bar), "r"(c0), "r"(c1) : "memory");
}
__device__ __forceinline__ void tma2d_pair_elect(uint32_t dst, const CUtensorMap* m, int c0, int c1, uint32_t bar) {
    asm volatile(ELECT "cp.async.bulk.tensor.2d.shared::cluster.global.mbarrier::complete_tx::bytes.multicast::cluster"
                 " [%0], [%1, {%3,%4}], [%2], %5;}" ::"r"(dst), "l"(m), "r"(bar), "r"(c0), "r"(c1), "h"((uint16_t)3) : "memory");
}
__device__ __forceinline__ void tma3d_elect(uint32_t dst, const CUtensorMap* m, int row, int chunk, uint32_t bar) {
    asm volatile(ELECT "cp.async.bulk.tensor.3d.shared::cluster.global.mbarrier::complete_tx::bytes [%0], [%1, {%3,%4,%5}], [%2];}"
                 ::"r"(dst), "l"(m), "r"(bar), "r"(0), "r"(row), "r"(chunk) : "memory");
}
__device__ __forceinline__ void bulk_wait_read() {
    asm volatile("cp.async.bulk.commit_group; cp.async.bulk.wait_group.read 0;" ::: "memory");
    __syncwarp();
}
__device__ __forceinline__ void fence_proxy_async_smem() { asm volatile("fence.proxy.async.shared::cta;" ::: "memory"); }
__device__ __forceinline__ uint32_t ld_relaxed(const void* p) {
    uint32_t v;
    asm volatile("ld.relaxed.gpu.global.u32 %0, [%1];" : "=r"(v) : "l"(p) : "memory");
    return v;
}
__device__ __forceinline__ uint4 ld_relaxed4(const void* p) {
    uint4 v;
    asm volatile("ld.relaxed.gpu.global.v4.u32 {%0,%1,%2,%3}, [%4];" : "=r"(v.x), "=r"(v.y), "=r"(v.z), "=r"(v.w) : "l"(p) : "memory");
    return v;
}
__device__ __forceinline__ void red_inc_if(unsigned int* p, bool pred) {
    asm volatile("{.reg .pred p; setp.ne.b32 p, %1, 0; @p red.relaxed.gpu.global.add.u32 [%0], 1;}" ::"l"(p), "r"((int)pred) : "memory");
}
__device__ __forceinline__ uint32_t tagf(float v, uint32_t par) { return (__float_as_uint(v) & ~1u) | par; }
__device__ __forceinline__ uint4 wait_tags(const unsigned int* p, int bit, uint32_t par) {
    uint32_t n = 0;
    while (true) {
        const uint4 v = ld_relaxed4(p);
        const uint32_t m = par ? (v.x & v.y & v.z & v.w) : ~(v.x | v.y | v.z | v.w);
        if (__all_sync(0xffffffffu, (m >> bit) & 1u)) return v;
        __nanosleep(100);
        if (++n > SPIN_LIMIT) __trap();
    }
}
__device__ __forceinline__ void wait_counter(const unsigned int* p, uint32_t want) {
    uint32_t n = 0;
    while (!__all_sync(0xffffffffu, (int)(ld_relaxed(p) - want) >= 0)) {
        __nanosleep(200);
        if (++n > SPIN_LIMIT) __trap();
    }
    asm volatile("fence.acquire.gpu;" ::: "memory");
}
__device__ __forceinline__ uint32_t stale_tags(uint32_t a, uint32_t par) {
    uint32_t r;
    asm volatile("{.reg .b32 v<16>;\n"
                 "ld.shared.u32 v0, [%1]; ld.shared.u32 v1, [%1+256]; ld.shared.u32 v2, [%1+512]; ld.shared.u32 v3, [%1+768];\n"
                 "ld.shared.u32 v4, [%1+4096]; ld.shared.u32 v5, [%1+4352]; ld.shared.u32 v6, [%1+4608]; ld.shared.u32 v7, [%1+4864];\n"
                 "ld.shared.u32 v8, [%1+8192]; ld.shared.u32 v9, [%1+8448]; ld.shared.u32 v10, [%1+8704]; ld.shared.u32 v11, [%1+8960];\n"
                 "ld.shared.u32 v12, [%1+12288]; ld.shared.u32 v13, [%1+12544]; ld.shared.u32 v14, [%1+12800]; ld.shared.u32 v15, [%1+13056];\n"
                 "lop3.b32 v0, v0, v1, %2, 0x7e; lop3.b32 v2, v2, v3, %2, 0x7e; lop3.b32 v4, v4, v5, %2, 0x7e; lop3.b32 v6, v6, v7, %2, 0x7e;\n"
                 "lop3.b32 v8, v8, v9, %2, 0x7e; lop3.b32 v10, v10, v11, %2, 0x7e; lop3.b32 v12, v12, v13, %2, 0x7e; lop3.b32 v14, v14, v15, %2, 0x7e;\n"
                 "lop3.b32 v0, v0, v2, v4, 0xfe; lop3.b32 v6, v6, v8, v10, 0xfe; lop3.b32 v0, v0, v6, v12, 0xfe; or.b32 %0, v0, v14;}"
                 : "=r"(r) : "r"(a), "r"(par) : "memory");
    return r;
}
template <int OFF>
__device__ __forceinline__ uint4 ldg_nc(const void* p) {
    uint4 v;
    asm volatile("ld.global.nc.v4.u32 {%0,%1,%2,%3}, [%4+%5];" : "=r"(v.x), "=r"(v.y), "=r"(v.z), "=r"(v.w) : "l"(p), "n"(OFF));
    return v;
}
template <int OFF>
__device__ __forceinline__ void stg128(void* p, const uint4& v) {
    asm volatile("st.global.v4.u32 [%0+%5], {%1,%2,%3,%4};" ::"l"(p), "r"(v.x), "r"(v.y), "r"(v.z), "r"(v.w), "n"(OFF) : "memory");
}
template <int OFF>
__device__ __forceinline__ void sts128(uint32_t a, const uint4& v) {
    asm volatile("st.shared.v4.u32 [%0+%5], {%1,%2,%3,%4};" ::"r"(a), "r"(v.x), "r"(v.y), "r"(v.z), "r"(v.w), "n"(OFF) : "memory");
}
__device__ __forceinline__ uint4 lds128(uint32_t a) {
    uint4 v;
    asm volatile("ld.shared.v4.u32 {%0,%1,%2,%3}, [%4];" : "=r"(v.x), "=r"(v.y), "=r"(v.z), "=r"(v.w) : "r"(a) : "memory");
    return v;
}
template <int OFF>
__device__ __forceinline__ void red_bf16x8(void* p, uint32_t x, uint32_t y, uint32_t z, uint32_t w) {
    asm volatile("red.relaxed.gpu.global.add.noftz.v4.bf16x2 [%0+%5], {%1,%2,%3,%4};"
                 ::"l"(p), "r"(x), "r"(y), "r"(z), "r"(w), "n"(OFF) : "memory");
}
__device__ __forceinline__ void sched_cut() {
    asm volatile("{.reg .pred p; .reg .u64 t; .reg .u32 a, b;\n"
                 "C%=: mov.u64 t, %%clock64; mov.b64 {a, b}, t; setp.eq.u32 p, a, %0; @p bra C%=;}" ::"n"(0) : "memory");
}
__device__ __forceinline__ uint32_t pin(uint32_t v) { return __shfl_xor_sync(0xffffffffu, v, 0); }
template <class T>
__device__ __forceinline__ T* pin(T* p) { return (T*)__shfl_xor_sync(0xffffffffu, (unsigned long long)p, 0); }
__device__ __forceinline__ float selpf(float a, float b, bool p) {
    float r;
    asm("{.reg .pred q; setp.ne.b32 q, %3, 0; selp.f32 %0, %1, %2, q;}" : "=f"(r) : "f"(a), "f"(b), "r"((int)p));
    return r;
}
template <int N, int MASK, int SZ>
__device__ __forceinline__ void halve(float (&a)[SZ]) {
    const bool up = threadIdx.x & MASK;
#pragma unroll
    for (int j = 0; j < N; j++) a[j] = selpf(a[N + j], a[j], up) + __shfl_xor_sync(0xffffffffu, selpf(a[j], a[N + j], up), MASK);
}
__device__ __forceinline__ float bflo(uint32_t u) { return __uint_as_float(u << 16); }
__device__ __forceinline__ float bfhi(uint32_t u) { return __uint_as_float(u & 0xffff0000u); }
__device__ __forceinline__ uint32_t pack_bf16(float lo, float hi) {
    uint32_t r;
    asm("cvt.rn.bf16x2.f32 %0, %1, %2;" : "=r"(r) : "f"(hi), "f"(lo));
    return r;
}
__device__ __forceinline__ uint32_t hmul2_bf16(uint32_t a, uint32_t b) {
    uint32_t r;
    asm("mul.rn.bf16x2 %0, %1, %2;" : "=r"(r) : "r"(a), "r"(b));
    return r;
}
__device__ __forceinline__ float rbf(float v) { return bflo(pack_bf16(v, 0.f)); }
__device__ __forceinline__ float sigmoidf_(float v) { return __fdividef(1.0f, 1.0f + __expf(-v)); }

__device__ __forceinline__ void wg_fence() { asm volatile("wgmma.fence.sync.aligned;" ::: "memory"); }
__device__ __forceinline__ void wg_commit() { asm volatile("wgmma.commit_group.sync.aligned;" ::: "memory"); }
template <int N> __device__ __forceinline__ void wg_wait() { asm volatile("wgmma.wait_group.sync.aligned %0;" ::"n"(N) : "memory"); }
__device__ __forceinline__ uint64_t desc128(uint32_t lo) { return (uint64_t)lo | (0x40000040ull << 32); }
__device__ __forceinline__ uint64_t desc64(uint32_t lo) { return (uint64_t)lo | (0x80000020ull << 32); }
__device__ __forceinline__ void fence_regs(float (&d)[64]) {
#pragma unroll
    for (int i = 0; i < 64; i++) asm volatile("" : "+f"(d[i])::"memory");
}
template <int TB>
__device__ __forceinline__ void wgmma128(float (&d)[64], uint64_t da, uint64_t db, int scaleD) {
    asm volatile(
        "{ .reg .pred p; setp.ne.b32 p, %66, 0;\n"
        "wgmma.mma_async.sync.aligned.m64n128k16.f32.bf16.bf16 "
        "{%0,%1,%2,%3,%4,%5,%6,%7,%8,%9,%10,%11,%12,%13,%14,%15,%16,%17,%18,%19,%20,%21,%22,%23,%24,%25,%26,%27,%28,%29,%30,%31,"
        "%32,%33,%34,%35,%36,%37,%38,%39,%40,%41,%42,%43,%44,%45,%46,%47,%48,%49,%50,%51,%52,%53,%54,%55,%56,%57,%58,%59,%60,%61,%62,%63}, "
        "%64, %65, p, 1, 1, 0, %67;\n}"
        : "+f"(d[0]), "+f"(d[1]), "+f"(d[2]), "+f"(d[3]), "+f"(d[4]), "+f"(d[5]), "+f"(d[6]), "+f"(d[7]),
          "+f"(d[8]), "+f"(d[9]), "+f"(d[10]), "+f"(d[11]), "+f"(d[12]), "+f"(d[13]), "+f"(d[14]), "+f"(d[15]),
          "+f"(d[16]), "+f"(d[17]), "+f"(d[18]), "+f"(d[19]), "+f"(d[20]), "+f"(d[21]), "+f"(d[22]), "+f"(d[23]),
          "+f"(d[24]), "+f"(d[25]), "+f"(d[26]), "+f"(d[27]), "+f"(d[28]), "+f"(d[29]), "+f"(d[30]), "+f"(d[31]),
          "+f"(d[32]), "+f"(d[33]), "+f"(d[34]), "+f"(d[35]), "+f"(d[36]), "+f"(d[37]), "+f"(d[38]), "+f"(d[39]),
          "+f"(d[40]), "+f"(d[41]), "+f"(d[42]), "+f"(d[43]), "+f"(d[44]), "+f"(d[45]), "+f"(d[46]), "+f"(d[47]),
          "+f"(d[48]), "+f"(d[49]), "+f"(d[50]), "+f"(d[51]), "+f"(d[52]), "+f"(d[53]), "+f"(d[54]), "+f"(d[55]),
          "+f"(d[56]), "+f"(d[57]), "+f"(d[58]), "+f"(d[59]), "+f"(d[60]), "+f"(d[61]), "+f"(d[62]), "+f"(d[63])
        : "l"(da), "l"(db), "r"(scaleD), "n"(TB));
}

__device__ __forceinline__ uint32_t get_role(uint32_t& smid) {
    uint32_t role;
    asm volatile("mov.u32 %0, %%smid;" : "=r"(smid));
    asm("{.reg .pred p, q; .reg .u32 t, a, b; shr.u32 t, %1, 1; mad.lo.u32 a, t, 293, -928; shr.u32 a, a, 8; mad.lo.u32 b, t, 8, -464;"
        " setp.lt.u32 p, t, 32; setp.lt.u32 q, t, 62; selp.u32 a, a, b, q; selp.u32 %0, t, a, p;}" : "=r"(role) : "r"(smid));
    return role;
}
__device__ __forceinline__ int tile_of_step(int step, int own) {
    const int u = step >= 17 ? step - 17 - (step > PS1) : step - 2;
    int e = (u + (u >= ((own ^ T0) & 14) ? 2 : 0)) ^ T0;
    if (step == 16 || step == PS1) e = own ^ 1;
    if (step < 2) e = own;
    return e + (step >= 17 || step == 1 ? 16 : 0);
}
__device__ __forceinline__ uint32_t router_key(float score, int row) {
    const float r = score + 0.0f;
    uint32_t u = pack_bf16(r, 0.f) & 0xffffu;
    u = (u & 0x8000u) ? (~u & 0xffffu) : (u | 0x8000u);
    if (r != r) u = 0;
    return (u << 16) | (uint32_t)(0x7fff - row);
}

#define g_fb_h ((float*)g_s.part)
#define g_fb_upd (g_fb_h + 2048)
#define g_fb_gate (g_fb_h + 4096)
#define g_fb_keys (g_s.part + 8192)
__global__ void fb_hidden(const bf16* x, const bf16* dre, const bf16* dim, const bf16* gw, const bf16* wr) {
    __shared__ float xs[D_];
    const int s = blockIdx.x, t = threadIdx.x;
    xs[t] = __bfloat162float(x[s * D_ + t]);
    __syncthreads();
    float a = 0.f, b = 0.f;
    for (int d = 0; d < D_; d++) { a = fmaf(xs[d], __bfloat162float(dre[t * D_ + d]), a); b = fmaf(xs[d], __bfloat162float(dim[t * D_ + d]), b); }
    ((bf16*)g_s.ab)[s * 1024 + t] = __float2bfloat16(a);
    ((bf16*)g_s.ab)[s * 1024 + 512 + t] = __float2bfloat16(b);
    if (t == 0) {
        float u = 0.f, v = 0.f;
        for (int d = 0; d < D_; d++) { u = fmaf(xs[d], __bfloat162float(gw[d]), u); v = fmaf(xs[d], __bfloat162float(wr[d]), v); }
        g_fb_gate[s] = sigmoidf_(u);
        g_fb_keys[s] = router_key(v, s);
    }
}
__device__ uint32_t fb_best() {
    uint32_t k = 0;
    for (int i = 0; i < S_; i++) k = max(k, g_fb_keys[i]);
    return k;
}
__global__ void fb_ffn1(const bf16* x, const bf16* wg, const bf16* wu) {
    const int f = blockIdx.x * blockDim.x + threadIdx.x, idx = 0x7fff - (int)(fb_best() & 0x7fffu);
    float a = 0.f, b = 0.f;
    for (int d = 0; d < D_; d++) {
        const float xv = __bfloat162float(x[idx * D_ + d]);
        a = fmaf(xv, __bfloat162float(wg[d * F_ + f]), a); b = fmaf(xv, __bfloat162float(wu[d * F_ + f]), b);
    }
    g_fb_h[f] = a * sigmoidf_(a) * b;
}
__global__ void fb_ffn2(const bf16* wd) {
    const int e = blockIdx.x * blockDim.x + threadIdx.x;
    const uint32_t u = fb_best() >> 16, rb = (u & 0x8000u) ? (u & 0x7fffu) : (~u & 0xffffu);
    float a = 0.f;
    for (int f = 0; f < F_; f++) a = fmaf(g_fb_h[f], __bfloat162float(wd[f * D_ + e]), a);
    g_fb_upd[e] = a * sigmoidf_(__uint_as_float(rb << 16));
}
__global__ void fb_seq(const bf16* x, const bf16* cre, const bf16* cim, bf16* out) {
    __shared__ float c[2][S_];
    __shared__ int idx;
    const int t = blockIdx.x, e = threadIdx.x;
    for (int i = e; i < S_; i += D_) { c[0][i] = __bfloat162float(cre[t * S_ + i]); c[1][i] = __bfloat162float(cim[t * S_ + i]); }
    if (e == 0) idx = 0x7fff - (int)(fb_best() & 0x7fffu);
    __syncthreads();
    float y = 0.f;
    for (int s = 0; s < S_; s++)
        y += c[0][s] * __bfloat162float(((const bf16*)g_s.ab)[s * 1024 + e]) - c[1][s] * __bfloat162float(((const bf16*)g_s.ab)[s * 1024 + 512 + e]);
    const float g = g_fb_gate[t];
    out[t * D_ + e] = __float2bfloat16(g * y + (1.f - g) * (__bfloat162float(x[t * D_ + e]) + (t == idx ? g_fb_upd[e] : 0.f)));
}

__device__ __forceinline__ void spare_job(const Params& p, unsigned char* smem, int sp, uint32_t tstart) {
    const int tid = threadIdx.x, warp = tid >> 5, lane = tid & 31;
    const uint32_t e1 = *(volatile unsigned int*)&p.s->pair[64 * 32 + sp] + 1u;
    const uint32_t par = e1 & 1u;
    uint32_t* sel = (uint32_t*)smem;
    float* acc = (float*)(smem + 1024);
    __syncthreads();
    if (tid == 0) *(volatile unsigned int*)&p.s->pair[64 * 32 + sp] = e1;
    sleep_until<500>(tstart + SUM_T0);
    if (warp < 14) {
        uint32_t n = 0;
        while ((int)(ld_relaxed(p.s->phint + (sp * 16 + warp) * 8) - e1 * 8u) < 0) {
            __nanosleep(100);
            if (++n > SPIN_LIMIT) __trap();
        }
        const unsigned int* src = p.s->part + warp * 4 * D_ + sp * 128 + lane * 4;
        uint4 v[4];
        while (true) {
            uint32_t bad = 0;
#pragma unroll
            for (int i = 0; i < 4; i++) v[i] = ld_relaxed4(src + i * D_);
#pragma unroll
            for (int i = 0; i < 4; i++) bad |= (v[i].x ^ par) | (v[i].y ^ par) | (v[i].z ^ par) | (v[i].w ^ par);
            if (!__any_sync(0xffffffffu, bad & 1u)) break;
            if (++n > SPIN_LIMIT) __trap();
        }
        float4 s = make_float4(0.f, 0.f, 0.f, 0.f);
#pragma unroll
        for (int i = 0; i < 4; i++) {
            s.x += __uint_as_float(v[i].x); s.y += __uint_as_float(v[i].y);
            s.z += __uint_as_float(v[i].z); s.w += __uint_as_float(v[i].w);
        }
        *(float4*)&acc[warp * 128 + lane * 4] = s;
    } else if (warp == 14) {
        const uint4 k4 = wait_tags(p.s->keys + lane * 4, 15, par);
        const uint32_t k = __reduce_max_sync(0xffffffffu, max(max(k4.x, k4.y), max(k4.z, k4.w)));
        const int idx = 0x7fff - (int)(k & 0x7fffu);
        const uint4 g4 = wait_tags(p.s->gate + (idx & ~3), 0, par);
        const uint32_t gw = (idx & 2) ? ((idx & 1) ? g4.w : g4.z) : ((idx & 1) ? g4.y : g4.x);
        const uint32_t u = k >> 16;
        const uint32_t rb = (u & 0x8000u) ? (u & 0x7fffu) : (~u & 0xffffu);
        const float og = 1.f - __uint_as_float(gw & ~1u), rs = sigmoidf_(__uint_as_float(rb << 16));
        if (lane == 0) { sel[0] = idx; sel[1] = pack_bf16(og, og); sel[2] = pack_bf16(rs, rs); }
        sleep_until<500>(tstart + SUM_T0 + 3000);
        wait_counter(p.s->ready + (idx >> 7) * 32, e1 * 8u);
    }
    __syncthreads();
    if (tid < 64) {
        float t0 = 0.f, t1 = 0.f;
#pragma unroll
        for (int i = 0; i < 14; i++) {
            const float2 z = *(const float2*)&acc[i * 128 + tid * 2];
            t0 += z.x; t1 += z.y;
        }
        asm volatile("red.relaxed.gpu.global.add.noftz.bf16x2 [%0], %1;" ::"l"(p.out + sel[0] * D_ + sp * 128 + tid * 2),
                     "r"(hmul2_bf16(sel[1], hmul2_bf16(sel[2], pack_bf16(t0, t1)))) : "memory");
    }
}

__host__ __device__ constexpr int off_d(int c) { return (c < 2 ? 1 : c / 2 + 2) * REGION + (c & 1) * 16384; }
__host__ __device__ constexpr int off_xe(int c) { return (c < 2 ? 6 * REGION : c < 4 ? 16384 : c < 6 ? 0 : 6 * REGION + 16384) + (c & 1) * 8192; }
__host__ __device__ constexpr int off_xl(int c) { return c < 4 ? 2 * REGION + c * 8192 : off_xe(c - 4); }

__global__ void __cluster_dims__(2, 1, 1) __launch_bounds__(NTHREADS, 1)
fused_kernel(const __grid_constant__ Params p) {
    extern __shared__ __align__(1024) unsigned char smem[];
    const uint32_t sb = smem_u32(smem);
    const int tid = threadIdx.x, lane = tid & 31;
    const int rank = blockIdx.x & 1;
    if (__all_sync(0xffffffffu, tid != 0)) {
        spin_until(clk() + HOLD);
        const int w = __shfl_sync(0xffffffffu, tid >> 5, 0);
        const uint32_t b1 = sb + B_F + 8 * w;
        if (w >= 2) mbar_init_elect(b1, 1);
        if (w < 5) mbar_init_elect(b1 + 360, w < 4 ? 1 : 4);
        mbar_init_elect(b1 + 120, w < 7 ? 5 : w < 14 ? 4 : w - 12);
        mbar_init_elect(b1 + 240, 1);
        if (w == 9 || w == 15) mbar_expect_tx_elect(b1 + 240, w == 9 ? 2048 : 4);
        asm volatile("fence.mbarrier_init.release.cluster;" ::: "memory");
        cta_bar();
        cluster_arrive();
    } else {
        uint32_t s0, t1 = 0;
        const uint32_t r0 = get_role(s0);
        const int xrow = (r0 & 3) * 256 + (r0 & 32) * 4 + rank * 64;
        mbar_init_elect(sb + B_F, 1);
        if (r0 >= 64) {
            cta_bar();
            cluster_arrive();
        } else {
#pragma unroll
            for (int c = 0; c < 8; c++) {
                if (c == 2) { cta_bar(); cluster_arrive(); }
                if (c) spin_until(t1 + c * PACE);
                if (c == 1) mbar_init_elect(sb + B_F + 8, 1);
                tma2d_elect(sb + off_xe(c), &p.mX1, c * 64, xrow, sb + B_F + 8 * c);
                tma2d_elect(sb + off_d(c), &p.mDre + ((r0 >> 2) & 1), c * 64, (r0 & 24) * 16, sb + B_F + 8 * c);
                mbar_expect_tx_elect(sb + B_F + 8 * c, 24576);
                if (!c) {
                    t1 = clk() + PACE0;
                    sched_cut();
                    mbar_init_elect(sb + B_G0, 1);
                    tma2d_elect(sb + off_xl(0), &p.mX1, 0, xrow + 1024, sb + B_G0);
                    mbar_expect_tx_elect(sb + B_G0, 8192);
                }
            }
            tma2d_elect(sb + off_xl(1), &p.mX1, 64, xrow + 1024, sb + B_G1);
            mbar_expect_tx_elect(sb + B_G1, 8192);
            spin_until(t1 + 8 * PACE);
            tma3d_elect(sb + off_xl(2), &p.mX2, xrow + 1024, 2, sb + B_G2);
            mbar_expect_tx_elect(sb + B_G2, 16384);
            if (!(r0 & 16))
                asm volatile(ELECT "cp.async.bulk.prefetch.tensor.3d.L2.global [%0, {%1,%2,%3}];}"
                             ::"l"(&p.mX2), "r"(0), "r"(xrow + 1024), "r"(4 + ((r0 >> 2) & 2)) : "memory");
        }
    }
    uint32_t tstart = clk() - 1000;
    const int warp = __shfl_sync(0xffffffffu, tid >> 5, 0);
    uint32_t smid;
    const uint32_t role = get_role(smid);
    if (role >= 64) {
        spare_job(p, smem, smid & 3, tstart);
        return;
    }
    const int gpc = role & 7;
    const int tn = (role >> 3) & 3;
    const int comp = gpc >> 2;
    const int own = (gpc & 3) * 4 + ((role >> 5) & 1) * 2 + rank;
    const int blk = comp * 4 + tn;
    const int cta = gpc * 16 + (role >> 3) * 2 + rank;
    constexpr unsigned long long FFN_PAIRS = 0xffff3f3f7fffff1full;
    const bool ffn = (FFN_PAIRS >> (cta >> 1)) & 1;
    const int fp = __popcll(FFN_PAIRS & ((1ull << (cta >> 1)) - 1));

    if (warp < 4) {
        const int tab = tile_of_step(lane, own);
        const uint32_t bdst = sb + 16384 + rank * 8192;
        const int brow = blk * 4096 + rank * 64;
        if (warp == 0) {
            mbar_spin(sb + B_XE, 0);
            tma3d_elect(sb + off_xl(4), &p.mX2, own * 64 + 1024, 4, sb + B_G4);
            tma3d_elect(sb + off_xl(6), &p.mX2, own * 64 + 1024, 6, sb + B_G4);
            mbar_expect_tx_elect(sb + B_G4, 32768);
#define LOAD_A() const int e = __shfl_sync(0xffffffffu, tab, step);                                             \
                 const uint32_t bar = sb + 8 * slot;                                                            \
                 mbar_spin(bar + B_EMPTY, ph);                                                                  \
                 tma2d_elect(sb + slot * REGION, &p.mCre + comp, e * 64, own * 128, bar + B_FULL);              \
                 mbar_expect_tx_elect(bar + B_FULL, 16384)
            uint32_t slot = 0, ph = 0;
            int step = 0;
#pragma unroll 1
            for (int i = 0; i < NSTAGE; i++) {
                step = slot = i < 2 ? i ^ 1 : i;
                LOAD_A();
                if (i == 2 || i == 3) spin_until(clk() + A_GAP);
            }
            step = NSTAGE;
            slot = 0; ph = 1;
#pragma unroll 1
            for (int h = 0; h < 3; h++) {
                const int last = h == 0 ? 16 : h == 1 ? PS1 : 32 - NA;
#pragma unroll 1
                for (; step < last; step++) {
                    LOAD_A();
                    tma2d_pair_elect(bdst + slot * REGION, &p.mAB, 0, brow + e * 128, bar + B_BL);
                    mbar_expect_tx_elect(bar + B_BL, 16384);
                    if (++slot == NSTAGE) { slot = 0; ph ^= 1; }
                }
                if (h == 2) break;
                LOAD_A();
                tma2d_elect(bdst + slot * REGION, &p.mAB, 0, brow + e * 128, bar + B_BL);
                tma2d_elect((bdst ^ 8192) + slot * REGION, &p.mAB, 0, (brow ^ 64) + e * 128, bar + B_BL);
                mbar_expect_tx_elect(bar + B_BL, 16384);
                step++;
                if (++slot == NSTAGE) { slot = 0; ph ^= 1; }
            }
            mbar_spin(sb + B_LOW, 0);
            uint32_t aslot = 6;
#pragma unroll 1
            for (; step < 32; step++) {
                const int e = __shfl_sync(0xffffffffu, tab, step);
                const uint32_t bar = sb + 8 * slot;
                tma2d_elect(sb + aslot * REGION, &p.mCre + comp, e * 64, own * 128, bar + B_FULL);
                mbar_expect_tx_elect(bar + B_FULL, 16384);
                mbar_expect_tx_elect(bar + B_BL, 16384);
                mbar_spin(bar + B_EMPTY, ph);
                tma2d_pair_elect(bdst + slot * REGION, &p.mAB, 0, brow + e * 128, bar + B_BL);
                aslot = slot;
                if (++slot == NSTAGE) { slot = 0; ph ^= 1; }
            }
        } else if (warp == 1) {
            cluster_wait();
            if (lane == 0)
                asm volatile("st.async.weak.shared::cluster.mbarrier::complete_tx::bytes.u32 [%0], %1, [%2];"
                             ::"r"(mapa(sb + M_ROLE, rank ^ 1)), "r"(role), "r"(mapa(sb + B_ROLE, rank ^ 1)) : "memory");
            mbar_wait_cluster(sb + B_ROLE, 0);
            if (*(volatile uint32_t*)(smem + M_ROLE) != role) __trap();
            mbar_wait(sb + B_EPOCH, 0);
            const uint32_t want = (*(volatile uint32_t*)(smem + M_EPOCH) + 1u) * 4u;
            const int eh = __shfl_sync(0xffffffffu, tab, 2 + (lane & 3));
            const unsigned int* hp = p.s->pair + (blk * 8 + (eh >> 1)) * 32 + 2 + (eh & 1);
            uint32_t seen = 0;
            int rows[4];
#pragma unroll
            for (int i = 0; i < 4; i++) {
                rows[i] = brow + __shfl_sync(0xffffffffu, tab, 2 + i) * 128;
                mbar_expect_tx_elect(sb + B_BL + 8 * (2 + i), 16384);
            }
            mbar_wait(sb + B_GO1, 0);
            asm volatile(ELECT "prefetch.tensormap [%0];}" ::"l"(&p.mAB) : "memory");
            mbar_wait(sb + B_EMPTY + 8 * 3, 0);
            mbar_spin(sb + B_EMPTY + 8 * 2, 0);
            uint32_t t3 = 0;
#pragma unroll
            for (int i = 0; i < 4; i++) {
                while (!((seen >> i) & 1u)) seen = __ballot_sync(0xffffffffu, ld_relaxed(hp) == want);
                if (i) spin_until(t3 + B_GAP);
                t3 = clk();
                if (i >= 2) mbar_spin(sb + B_EMPTY + 8 * (2 + i), 0);
                tma2d_pair_elect(bdst + (2 + i) * REGION, &p.mAB, 0, rows[i], sb + B_BL + 8 * (2 + i));
            }
            mbar_wait(sb + B_FREE, 0);
            unsigned char* gdst = p.s->ab + (blk * 32 + own + 16) * 16384;
            t3 = clk();
#pragma unroll 1
            for (int i = 0; i < 16; i++) {
                sleep_until<20>(t3);
                t3 += LATE_GAP;
                asm volatile(ELECT "cp.async.bulk.global.shared::cta.bulk_group [%0], [%1], 1024;}"
                             ::"l"(gdst + i * 1024), "r"(sb + 6 * REGION + i * 1024) : "memory");
            }
            bulk_wait_read();
            mbar_arrive_elect(sb + B_FREE + 8);
            mbar_wait(sb + B_PUB, 0);
            if (lane == 0) {
                asm volatile("fence.proxy.async.global;" ::: "memory");
                asm volatile("red.release.gpu.global.add.u32 [%0], 1;" ::"l"(p.s->ready + (cta >> 3) * 32) : "memory");
            }
            __syncwarp();
            __nanosleep(INIT_NS);
            wait_counter(p.s->ready + own * 32, want * 2u);
            mbar_arrive_elect(sb + B_INIT);
            asm volatile(ELECT "prefetch.tensormap [%0];}" ::"l"(&p.mOut) : "memory");
        } else {
            mbar_arrive_elect(sb + B_BL + 8 * (warp & 1));
            uint32_t k = warp == 3 ? 0 : 12;
#define PREFETCH_W() {                                                                                          \
                const char* src = (k >= 8 ? (const char*)p.wd + ((cta >> 5) * 2 + (k >> 1) - 4) * 229376        \
                                          : (const char*)((cta & 32) ? p.wu : p.wg) + ((cta >> 6) * 4 + (k >> 1)) * 229376) \
                                  + ((cta & 31) * 2 + (k & 1)) * 3584;                                          \
                asm volatile(ELECT "cp.async.bulk.prefetch.L2.global [%0], 3584;}" ::"l"(src) : "memory");      \
                k++; }
#pragma unroll 1
            while (k < PF_N0) {
                sleep_until<50>(tstart + PF_T0 + k * PF_GAP);
                __syncwarp();
                PREFETCH_W();
            }
            mbar_wait(sb + B_EPOCH, 0);
            const uint32_t par = (*(volatile uint32_t*)(smem + M_EPOCH) + 1u) & 1u;
            const uint32_t a0 = sb + 16384 + (lane >> 3) * 1028 + ((lane >> 2) & 1) * 144 + (lane & 3) * 32;
            const uint32_t retry = sb + B_RETRY + (warp & 1) * 240;
            uint32_t slot = warp, ph = 0, rph = 0;
            uint32_t j = ffn ? warp & 1 : 12;
#pragma unroll 1
            for (int step = warp; step < 32 || j < 12;) {
                const bool go = step < (j < 8 ? 32 - NA : 32);
                if (go) {
                    const uint32_t bar = sb + 8 * slot;
                    mbar_wait(bar + B_BL, ph);
#pragma unroll 1
                    while (__any_sync(0xffffffffu, stale_tags(a0 + slot * REGION, par) & 1u)) {
                        const int row = blk * 4096 + __shfl_sync(0xffffffffu, tab, step) * 128;
                        mbar_expect_tx_elect(retry, 16384);
                        tma2d_elect(sb + slot * REGION + 16384, &p.mAB, 0, row, retry);
                        tma2d_elect(sb + slot * REGION + 24576, &p.mAB, 0, row + 64, retry);
                        mbar_spin(retry, rph);
                        rph ^= 1u;
                    }
                    mbar_arrive_elect<4>(bar + B_FULL);
                }
                if (j < 12 && step >= FFN_S0 + j * FFN_W / 4 && __any_sync(0xffffffffu, mbar_test(sb + B_FREE + 2 * (j & 12), 0))) {
                    const uint32_t fb = sb + B_FFN + 4 * (j & 6);
                    if (!(j & 1)) mbar_expect_tx_elect(fb, 8192);
                    tma2d_elect(sb + 6 * REGION + ((j + 4) & 7) * 4096, j < 8 ? &p.mWg + (j & 1) : &p.mWd,
                                j < 8 ? fp * 32 : rank * 256, j < 8 ? rank * 256 + (j >> 1) * 64 : fp * 32 + j * 8 - 64, fb);
                    j += 2;
                }
                if (k < 12) PREFETCH_W();
                if (go) {
                    step += 2;
                    slot += 2;
                    if (slot >= NSTAGE) { slot -= NSTAGE; ph ^= 1; }
                }
            }
        }
    } else if (warp < 8) {
        const int t = tid - 128, w = warp - 4;
        if (t == 0) {
            volatile unsigned int* ep = &p.s->pair[(blk * 8 + (own >> 1)) * 32 + rank];
            const uint32_t epoch = *ep;
            *(volatile uint32_t*)(smem + M_EPOCH) = epoch;
            *ep = epoch + 1;
        }
        mbar_arrive_if(sb + B_EPOCH, t == 0);
        const uint4 gw0 = ldg_nc<0>(p.gate_w + lane * 8), gw1 = ldg_nc<512>(p.gate_w + lane * 8);
        const uint4 rw0 = ldg_nc<0>(p.w_r + lane * 8), rw1 = ldg_nc<512>(p.w_r + lane * 8);
        mbar_wait(sb + B_EPOCH, 0);
        const uint32_t par = (*(volatile uint32_t*)(smem + M_EPOCH) + 1u) & 1u;
        mbar_wait(sb + B_F + 8 * ROUTER_C, 0);
        const int row0 = cta * 16 + w * 4;
        uint4 xr[8];
        {
            const char* xp = (const char*)p.x + (uint32_t)row0 * (D_ * 2) + lane * 16;
            xr[0] = ldg_nc<0>(xp);    xr[1] = ldg_nc<512>(xp);  xr[2] = ldg_nc<1024>(xp); xr[3] = ldg_nc<1536>(xp);
            xr[4] = ldg_nc<2048>(xp); xr[5] = ldg_nc<2560>(xp); xr[6] = ldg_nc<3072>(xp); xr[7] = ldg_nc<3584>(xp);
            float a[8];
#pragma unroll
            for (int i = 0; i < 4; i++) {
                const uint32_t xv[8] = {xr[2 * i].x, xr[2 * i].y, xr[2 * i].z, xr[2 * i].w,
                                        xr[2 * i + 1].x, xr[2 * i + 1].y, xr[2 * i + 1].z, xr[2 * i + 1].w};
                const uint32_t gv[8] = {gw0.x, gw0.y, gw0.z, gw0.w, gw1.x, gw1.y, gw1.z, gw1.w};
                const uint32_t rv[8] = {rw0.x, rw0.y, rw0.z, rw0.w, rw1.x, rw1.y, rw1.z, rw1.w};
                float u = 0.f, v = 0.f;
#pragma unroll
                for (int j = 0; j < 8; j++) {
                    const uint32_t pr = hmul2_bf16(xv[j], gv[j]);
                    u += bflo(pr); u += bfhi(pr);
                    v = fmaf(bflo(xv[j]), bflo(rv[j]), v); v = fmaf(bfhi(xv[j]), bfhi(rv[j]), v);
                }
                a[i] = u; a[4 + i] = v;
            }
            mbar_wait(sb + B_EARLY, 0);
            halve<4, 16>(a); halve<2, 8>(a); halve<1, 4>(a);
            a[0] += __shfl_xor_sync(0xffffffffu, a[0], 1);
            a[0] += __shfl_xor_sync(0xffffffffu, a[0], 2);
            const int row = row0 + ((lane >> 2) & 3);
            const float gate = rbf(sigmoidf_(rbf(a[0])));
            if (lane < 16 && (lane & 3) == 0)
                asm volatile("st.relaxed.gpu.global.u32 [%0], %1;" ::"l"(&p.s->gate[row]), "r"(tagf(gate, par)) : "memory");
            const uint32_t best = __reduce_max_sync(0xffffffffu, lane >= 16 ? router_key(a[0], row) : 0u);
            if (lane == 0) *(volatile uint32_t*)(smem + M_KEY + w * 4) = best;
            side_bar();
            if (t < 8) {
                const uint4 k = *(const uint4*)(smem + M_KEY);
                asm volatile("{.reg .b32 old; atom.relaxed.gpu.global.exch.b32 old, [%0], %1;}" ::"l"(&p.s->keys[t * NCTA + cta]),
                             "r"(max(max(k.x, k.y), max(k.z, k.w)) | (par << 15)) : "memory");
            }
            const uint32_t og = pack_bf16(1.f - gate, 1.f - gate);
#pragma unroll
            for (int i = 0; i < 8; i++) {
                const uint32_t o = __shfl_sync(0xffffffffu, og, 4 * (i >> 1));
                xr[i] = make_uint4(hmul2_bf16(o, xr[i].x), hmul2_bf16(o, xr[i].y), hmul2_bf16(o, xr[i].z), hmul2_bf16(o, xr[i].w));
            }
        }
        mbar_wait(sb + B_FREE, 0);
        __nanosleep(KEY_NS);
        if (w == 0) {
            const uint4 k4 = wait_tags(p.s->keys + gpc * NCTA + lane * 4, 15, par);
            const uint32_t k = __reduce_max_sync(0xffffffffu, max(max(k4.x, k4.y), max(k4.z, k4.w)));
            sts128<M_XS>(sb + lane * 16, ldg_nc<0>(p.x + (0x7fff - (k & 0x7fffu)) * D_ + rank * 256 + lane * 8));
        } else if (w == 1) {
            const uint4 g4 = wait_tags(p.s->gate + own * 128 + lane * 4, 0, par);
            const uint32_t sg = comp ? 0x80000000u : 0u;
            sts128<M_G>(sb + lane * 16, make_uint4((g4.x & ~1u) ^ sg, (g4.y & ~1u) ^ sg, (g4.z & ~1u) ^ sg, (g4.w & ~1u) ^ sg));
            mbar_arrive_warp(sb + B_GATE);
        }
        side_bar();
        char* op = (char*)p.out + (uint32_t)row0 * (D_ * 2) + lane * 16;
        float a[16];
#pragma unroll
        for (int i = 0; i < 16; i++) a[i] = 0.f;
#pragma unroll 1
        for (int i = 0; i < 4; i++) {
            if (i == 2) {
                mbar_wait(sb + B_FREE + 8, 0);
                const uint32_t t2 = clk() + w * (INIT_GAP / 4);
#pragma unroll
                for (int j = 0; j < 8; j++) {
                    sleep_until<20>(t2 + j * INIT_GAP);
                    *(uint4*)(op + j * 512) = xr[j];
                }
                mbar_arrive_warp(sb + B_PUB);
            }
            if (ffn) {
                const float xs0 = __bfloat162float(((const bf16*)(smem + M_XS))[64 * i + (t >> 2)]);
                const float xs1 = __bfloat162float(((const bf16*)(smem + M_XS))[64 * i + 32 + (t >> 2)]);
                const uint32_t wa = sb + 6 * REGION + (i ^ 2) * 8192 + t * 16;
                mbar_wait(sb + B_FFN + 8 * i, 0);
                const uint4 v0 = lds128(wa), v1 = lds128(wa + 4096), v2 = lds128(wa + 2048), v3 = lds128(wa + 6144);
                const uint32_t w0[8] = {v0.x, v0.y, v0.z, v0.w, v1.x, v1.y, v1.z, v1.w};
                const uint32_t w1[8] = {v2.x, v2.y, v2.z, v2.w, v3.x, v3.y, v3.z, v3.w};
#pragma unroll
                for (int k = 0; k < 8; k++) {
                    a[2 * k] = fmaf(xs1, bflo(w1[k]), fmaf(xs0, bflo(w0[k]), a[2 * k]));
                    a[2 * k + 1] = fmaf(xs1, bfhi(w1[k]), fmaf(xs0, bfhi(w0[k]), a[2 * k + 1]));
                }
                if (i == 1) {
                    side_bar();
                    mbar_arrive_if(sb + B_FREE + 16, t == 0);
                }
            }
        }
        if (!ffn) {
            mbar_arrive_warp(sb + B_LOW);
            return;
        }
        halve<8, 16>(a); halve<4, 8>(a); halve<2, 4>(a);
        const uint32_t ho = (lane >> 4) * 128 + (lane & 3) * 32 + ((lane >> 2) & 3) * 8;
        cluster_wait();
#pragma unroll
        for (int k = 0; k < 2; k++)
            asm volatile("st.async.weak.shared::cluster.mbarrier::complete_tx::bytes.v2.f32 [%0], {%1,%2}, [%3];"
                         ::"r"(mapa(sb + (k ? 6 * REGION + w * 512 : M_HX + w * 256) + ho, rank ^ k ^ 1)), "f"(a[0]), "f"(a[1]),
                           "r"(mapa(sb + B_HX, rank ^ k ^ 1)) : "memory");
        mbar_wait_cluster(sb + B_HX, 0);
        const float *hx = (const float*)(smem + M_HX) + lane, *hy = (const float*)(smem + 6 * REGION) + lane;
        const float gs = rbf(((hx[0] + hy[0]) + (hx[64] + hy[128])) + ((hx[128] + hy[256]) + (hx[192] + hy[384])));
        const float us = rbf(((hx[32] + hy[32]) + (hx[96] + hy[160])) + ((hx[160] + hy[288]) + (hx[224] + hy[416])));
        float* hrow = (float*)(smem + M_XS) + w * 32;
        hrow[lane] = rbf(rbf(gs * sigmoidf_(gs)) * us);
        fence_proxy_async_smem();
        mbar_arrive_warp(sb + B_LOW);
        float o0 = 0.f, o1 = 0.f;
#pragma unroll 1
        for (int i = 0; i < 2; i++) {
            float4 hv[4];
            uint32_t vd[16];
#pragma unroll
            for (int k = 0; k < 4; k++) hv[k] = *(const float4*)&hrow[i * 16 + k * 4];
            mbar_wait(sb + B_FFN + 8 * i, 1);
#pragma unroll
            for (int k = 0; k < 16; k++) vd[k] = *(const volatile uint32_t*)(smem + 6 * REGION + 16384 + i * 8192 + k * 512 + t * 4);
#pragma unroll
            for (int k = 0; k < 4; k++) {
                o0 = fmaf(hv[k].x, bflo(vd[4 * k]), o0);     o1 = fmaf(hv[k].x, bfhi(vd[4 * k]), o1);
                o0 = fmaf(hv[k].y, bflo(vd[4 * k + 1]), o0); o1 = fmaf(hv[k].y, bfhi(vd[4 * k + 1]), o1);
                o0 = fmaf(hv[k].z, bflo(vd[4 * k + 2]), o0); o1 = fmaf(hv[k].z, bfhi(vd[4 * k + 2]), o1);
                o0 = fmaf(hv[k].w, bflo(vd[4 * k + 3]), o0); o1 = fmaf(hv[k].w, bfhi(vd[4 * k + 3]), o1);
            }
        }
        asm volatile("st.relaxed.gpu.global.v2.u32 [%0], {%1,%2};" ::"l"(&p.s->part[fp * D_ + rank * 256 + t * 2]),
                     "r"(tagf(o0, par)), "r"(tagf(o1, par)) : "memory");
        red_inc_if(p.s->phint + ((rank * 2 + (w >> 1)) * 16 + (fp >> 2)) * 8 + lane, lane == 0);
    } else {
        const int wg = (warp >> 2) - 2, wq = warp & 3;
        const uint32_t sbd = ((sb & 0x3FFFF) >> 4) + 0x10000;
        const bool lead = (tid & 127) == 0;
        const bool lead0 = lead && !wg, lead1 = lead && wg;
        const int q = lane & 3;
        float acc[64];
        const uint32_t rE = mapa(sb + B_EMPTY, rank ^ 1);
#define RELEASE(n, slot, pred) release_pair<n>(sb + B_EMPTY + 8 * (slot), rE + 8 * (slot), pred)
        const uint32_t ioff = wq * 4096 + (lane >> 2) * 64 + ((q ^ (lane >> 3)) << 4);
        const uint32_t sdst = pin(sb + 6 * REGION + (wg ? 0 : 16384) + ioff);
        unsigned char* gdst = pin(p.s->ab + (blk * 32 + own) * 16384 + ioff);
        unsigned int* hint = pin(p.s->pair + (blk * 8 + (own >> 1)) * 32 + 2 + rank + lane);
        uint32_t par = 0;
#define GET_PAR() mbar_spin(sb + B_EPOCH, 0); par = (*(volatile uint32_t*)(smem + M_EPOCH) + 1u) & 1u
        cluster_wait();
        if (wg) mbar_spin(sb + B_G0, 0);
#pragma unroll
        for (int c = 0; c < 8; c++) {
            if (c == 1 && wg) {
                wg_wait<0>();
                RELEASE(1, 1, lead);
                GET_PAR();
                mbar_spin(sb + B_G1, 0);
            }
            if (!wg || c < 3 || c == 4) mbar_spin(sb + (!wg || c == 0 ? B_F + 8 * c : c == 1 ? B_GO1 : c == 2 ? B_G2 : B_G4), 0);
            const uint32_t xa = sbd + wg * ((off_xl(c) - off_xe(c)) / 16);
            wg_fence();
#pragma unroll
            for (int kk = 0; kk < 4; kk++) {
                wgmma128<0>(acc, desc128(xa + off_xe(c) / 16 + 2 * kk), desc128(sbd + off_d(c) / 16 + 2 * kk), (c | kk) != 0);
                if (c == 7 && kk == 0) wg_commit();
            }
            wg_commit();
            if (c == 5 && !wg) { GET_PAR(); }
            if (c == 7) {
                if (wg) mbar_spin(sb + B_FULL, 0);
                wg_wait<2>();
                mbar_arrive_if(sb + B_GO1, lead0);
            }
            if (c == 4 || c >= 6) wg_wait<1>();
            if (c == 4) { mbar_arrive_if(sb + B_XE, lead0); RELEASE(1, 1, lead0); RELEASE(2, 2, lead1); RELEASE(2, 3, lead1); }
            if (c == 6) RELEASE(2, 4 * wg, lead);
            if (c == 7) mbar_arrive_if(sb + B_GO0, lead1);
        }
        const int rh = wg ^ comp;
        const uint32_t da0 = sbd + rh * 512, db0 = sbd - 0x10000 + 0x400000 + 1024;
        const uint32_t dbe = db0 + 6 * (REGION / 16), dbl = dbe - 1024;
#define STEP(da, db, first) wg_fence();                                                                     \
        _Pragma("unroll") for (int kk = 0; kk < 4; kk++)                                                    \
            wgmma128<1>(acc, desc128((da) + kk * 2), desc64((db) + kk * 256), !((first) && kk == 0));       \
        wg_commit()
#define ACC(i, j) (16 * ((i) >> 1) + 2 * ((i) & 1) + 4 * (j))
#define PW(i, j) pack_bf16(acc[ACC(i, j)], acc[ACC(i, j) + 1])
#define PT(i, j) ((j) == ((i) >> 1) ? (PW(i, j) & ~1u) | par : PW(i, j))
#define PIECE(i) make_uint4(PT(i, 0), PT(i, 1), PT(i, 2), PT(i, 3))
#define PIECES(F) F(0); F(1); sched_cut(); F(2); F(3); F(4); F(5); F(6); F(7)
        if (wg) {
            wg_wait<0>();
            fence_regs(acc);
#define STS1(i) sts128<(i) * 512>(sdst, PIECE(i))
            PIECES(STS1);
            STEP(da0, dbe, true);
            fence_proxy_async_smem();
            mbar_arrive_warp(sb + B_FULL + 8);
            RELEASE(1, 5, lead);
        } else {
            wg_wait<0>();
            fence_regs(acc);
            uint4 v[8];
#define STG0(i) v[i] = PIECE(i); stg128<(i) * 512>(gdst, v[i]); if (HINT_AT == (i) + 1) red_inc_if(hint, (own ^ T0) < 6 && lane == 0)
            PIECES(STG0);
            mbar_spin(sb + B_EPOCH, 0);
            asm volatile("bar.sync 2, 128;" ::: "memory");
#define STS0(i) if ((i) % 2 == 0) mbar_spin(sb + B_EPOCH, 0); sts128<(i) * 512>(sdst, v[i])
            STS0(0); STS0(1); STS0(2); STS0(3); STS0(4); STS0(5); STS0(6); STS0(7);
            fence_proxy_async_smem();
            mbar_arrive_warp(sb + B_FULL);
            RELEASE(1, 5, lead);
            mbar_arrive_if(sb + B_EARLY, lead);
            mbar_spin(sb + B_FULL, 0);
            mbar_spin(sb + B_GO0, 0);
            STEP(da0, dbe, true);
        }
#pragma unroll
        for (int step = 1; step < 3; step++) {
            mbar_spin(sb + B_FULL + 8 * step, 0);
            STEP(da0 + step * (REGION / 16), step == 1 ? dbl : db0 + step * (REGION / 16), false);
            wg_wait<1>();
            RELEASE(1, step - 1, lead);
            mbar_arrive_if(sb + B_FREE + 8 * (step - 1), lead);
        }
        int slot = 3, ph = 0, pslot = 2;
        float g0 = 0.f, g1 = 0.f;
        uint32_t oa = 0;
#pragma unroll 1
        for (int step = 3; step < 26; step++) {
            mbar_wait(sb + B_FULL + 8 * slot, ph);
            STEP(da0 + slot * (REGION / 16), db0 + slot * (REGION / 16), false);
            if (step == SETUP + wg) {
                const int r0 = rh * 64 + wq * 16 + (lane >> 2), sr = ((lane >> 2) & 1) * 4 + (lane >> 3);
                mbar_wait(sb + B_GATE, 0);
                g0 = ((const volatile float*)(smem + M_G))[r0];
                g1 = ((const volatile float*)(smem + M_G))[r0 + 8];
                oa = pin(wg ? ((own * 128 + (r0 & ~1)) * D_ + tn * 128 + (lane & 7) * 8) * 2u
                            : sb + rh * 8192 + wq * 2048 + sr * 128 + ((q ^ sr) << 4));
            }
            wg_wait<1>();
            RELEASE(1, pslot, lead);
            pslot = slot;
            if (++slot == NSTAGE) { slot = 0; ph ^= 1; }
        }
        mbar_wait(sb + B_FULL + 8 * 2, 0);
        wg_fence();
#pragma unroll
        for (int kk = 0; kk < 4; kk++) {
            if (kk == HSK) {
                wg_commit();
                if (wg) {
                    wg_wait<1>();
                    RELEASE(1, 1, lead);
                    mbar_wait(sb + B_INIT, 0);
                    mbar_wait(sb + B_TAIL, 0);
                }
                wg_fence();
            }
            wgmma128<1>(acc, desc128(da0 + 2 * (REGION / 16) + kk * 2), desc64(db0 + 2 * (REGION / 16) + kk * 256), 1);
        }
        wg_commit();
        if (!wg) {
            wg_wait<2>();
            RELEASE(1, 1, lead);
        }
        slot = 3;
#pragma unroll 1
        for (int step = 27; step < 32; step++) {
            if (!wg) mbar_wait(sb + B_FULL + 8 * slot, ph);
            STEP(da0 + (step < 32 - NA ? slot : step == 32 - NA ? 6 : pslot) * (REGION / 16), db0 + slot * (REGION / 16), false);
            pslot = slot;
            if (++slot == NSTAGE) { slot = 0; ph ^= 1; }
        }
#define OW(i, j) pack_bf16((((i) & 1) ? g1 : g0) * acc[ACC(i, j)], (((i) & 1) ? g1 : g0) * acc[ACC(i, j) + 1])
        if (!wg) {
            wg_wait<1>();
            mbar_arrive_if(sb + B_TAIL, lead);
            const uint32_t st0 = sb + rh * 8192 + wq * 2048;
            mbar_wait(sb + B_INIT, 0);
            wg_wait<0>();
            fence_regs(acc);
#define OSTS(i) sts128<((i) >> 2) * REGION + ((i) & 1) * 1024>(((i) & 2) ? oa ^ 64 : oa, make_uint4(OW(i, 0), OW(i, 1), OW(i, 2), OW(i, 3)))
#define ORED(h) fence_proxy_async_smem(); __syncwarp();                                                     \
            asm volatile(ELECT "cp.reduce.async.bulk.tensor.4d.global.shared::cta.add.tile.bulk_group [%0, {%2,%3,%3,%4}], [%1];}" \
                         ::"l"(&p.mOut), "r"(st0 + (h) * REGION), "r"(tn * 128 + (h) * 64), "r"(0), "r"(own * 16 + rh * 8 + wq * 2) : "memory")
            OSTS(0); OSTS(1); OSTS(2); OSTS(3);
            ORED(0);
            sched_cut();
            OSTS(4); OSTS(5); OSTS(6); OSTS(7);
            ORED(1);
            bulk_wait_read();
        } else {
            const bool odd = lane & 4;
            char *op = pin((char*)p.out + oa), *opb = pin((char*)p.out + (oa ^ 64) + 1024);
            sched_cut();
            wg_wait<0>();
            fence_regs(acc);
#define REDLINE(i) {                                                                                        \
                uint32_t k[4], r[4];                                                                        \
                _Pragma("unroll") for (int j = 0; j < 4; j++) {                                             \
                    r[j] = __shfl_xor_sync(0xffffffffu, OW((i) + 2, j), 4);                                 \
                    k[j] = OW(i, j);                                                                        \
                }                                                                                           \
                red_bf16x8<((i) & 1) * 8192 + ((i) >> 2) * 128>(op, odd ? r[0] : k[0], odd ? r[1] : k[1], odd ? r[2] : k[2], odd ? r[3] : k[3]);  \
                red_bf16x8<((i) & 1) * 8192 + ((i) >> 2) * 128>(opb, odd ? k[0] : r[0], odd ? k[1] : r[1], odd ? k[2] : r[2], odd ? k[3] : r[3]); }
            REDLINE(0)
            sched_cut();
            REDLINE(4) REDLINE(1) REDLINE(5)
        }
    }
}

typedef CUresult (*EncodeTiledFn)(CUtensorMap*, CUtensorMapDataType, cuuint32_t, void*, const cuuint64_t*, const cuuint64_t*,
                                  const cuuint32_t*, const cuuint32_t*, CUtensorMapInterleave, CUtensorMapSwizzle,
                                  CUtensorMapL2promotion, CUtensorMapFloatOOBfill);

static void make_map(EncodeTiledFn enc, CUtensorMap* m, const void* base, uint64_t cols, uint64_t rows, uint32_t box_rows,
                     CUtensorMapSwizzle sw = CU_TENSOR_MAP_SWIZZLE_128B, uint32_t box_cols = 64) {
    cuuint64_t dims[2] = {cols, rows};
    cuuint64_t str[1] = {cols * 2};
    cuuint32_t box[2] = {box_cols, box_rows};
    cuuint32_t es[2] = {1, 1};
    enc(m, CU_TENSOR_MAP_DATA_TYPE_BFLOAT16, 2, (void*)base, dims, str, box, es, CU_TENSOR_MAP_INTERLEAVE_NONE,
        sw, CU_TENSOR_MAP_L2_PROMOTION_L2_128B, CU_TENSOR_MAP_FLOAT_OOB_FILL_NONE);
}

static void make_map_x2(EncodeTiledFn enc, CUtensorMap* m, const void* base) {
    cuuint64_t dims[3] = {64, S_, 8};
    cuuint64_t str[2] = {D_ * 2, 128};
    cuuint32_t box[3] = {64, 64, 2};
    cuuint32_t es[3] = {1, 1, 1};
    enc(m, CU_TENSOR_MAP_DATA_TYPE_BFLOAT16, 3, (void*)base, dims, str, box, es, CU_TENSOR_MAP_INTERLEAVE_NONE,
        CU_TENSOR_MAP_SWIZZLE_128B, CU_TENSOR_MAP_L2_PROMOTION_L2_128B, CU_TENSOR_MAP_FLOAT_OOB_FILL_NONE);
}

static void make_map_out(EncodeTiledFn enc, CUtensorMap* m, const void* base) {
    cuuint64_t dims[4] = {D_, 4, 2, S_ / 8};
    cuuint64_t str[3] = {2 * D_ * 2, D_ * 2, 8 * D_ * 2};
    cuuint32_t box[4] = {64, 4, 2, 2};
    cuuint32_t es[4] = {1, 1, 1, 1};
    enc(m, CU_TENSOR_MAP_DATA_TYPE_BFLOAT16, 4, (void*)base, dims, str, box, es, CU_TENSOR_MAP_INTERLEAVE_NONE,
        CU_TENSOR_MAP_SWIZZLE_128B, CU_TENSOR_MAP_L2_PROMOTION_NONE, CU_TENSOR_MAP_FLOAT_OOB_FILL_NONE);
}

extern "C" void kernel_launch(void* const* d_in, const int* in_sizes, int n_in, void* d_out, int out_size) {
    (void)in_sizes; (void)n_in; (void)out_size;
    static EncodeTiledFn enc = nullptr;
    static bool fused_ok = false;
    static void* scratch = nullptr;
    if (!enc) {
        void* fn = nullptr;
        cudaDriverEntryPointQueryResult q;
        cudaGetDriverEntryPoint("cuTensorMapEncodeTiled", &fn, cudaEnableDefault, &q);
        enc = (EncodeTiledFn)fn;
        cudaGetSymbolAddress(&scratch, g_s);
        cudaFuncSetAttribute(fused_kernel, cudaFuncAttributeMaxDynamicSharedMemorySize, SMEM_BYTES);
        int dev = 0, nsm = 0, ncl = 0;
        cudaGetDevice(&dev);
        cudaDeviceGetAttribute(&nsm, cudaDevAttrMultiProcessorCount, dev);
        cudaLaunchConfig_t cfg = {};
        cfg.gridDim = dim3(132); cfg.blockDim = dim3(NTHREADS); cfg.dynamicSmemBytes = SMEM_BYTES;
        cudaLaunchAttribute at;
        at.id = cudaLaunchAttributeClusterDimension;
        at.val.clusterDim.x = 2; at.val.clusterDim.y = 1; at.val.clusterDim.z = 1;
        cfg.attrs = &at; cfg.numAttrs = 1;
        fused_ok = cudaOccupancyMaxActiveClusters(&ncl, fused_kernel, &cfg) == cudaSuccess && nsm == 132 && ncl == 66;
        (void)cudaGetLastError();
    }
    if (!fused_ok) {
        const bf16* const* in = (const bf16* const*)d_in;
        fb_hidden<<<S_, D_, 0, cudaStreamPerThread>>>(in[0], in[3], in[4], in[10], in[6]);
        fb_ffn1<<<F_ / 128, 128, 0, cudaStreamPerThread>>>(in[0], in[7], in[8]);
        fb_ffn2<<<D_ / 64, 64, 0, cudaStreamPerThread>>>(in[9]);
        fb_seq<<<S_, D_, 0, cudaStreamPerThread>>>(in[0], in[1], in[2], (bf16*)d_out);
        return;
    }
    Params p;
    p.s = (Scratch*)scratch;
    p.x = (const bf16*)d_in[0];
    p.w_r = (const bf16*)d_in[6];
    p.wg = (const bf16*)d_in[7];
    p.wu = (const bf16*)d_in[8];
    p.wd = (const bf16*)d_in[9];
    p.gate_w = (const bf16*)d_in[10];
    p.out = (bf16*)d_out;
    make_map(enc, &p.mX1, d_in[0], D_, S_, 64);
    make_map_x2(enc, &p.mX2, d_in[0]);
    make_map(enc, &p.mCre, d_in[1], S_, S_, 128);
    make_map(enc, &p.mCim, d_in[2], S_, S_, 128);
    make_map(enc, &p.mDre, d_in[3], D_, D_, 128);
    make_map(enc, &p.mDim, d_in[4], D_, D_, 128);
    make_map(enc, &p.mAB, scratch, 64, 8 * 32 * 128, 64, CU_TENSOR_MAP_SWIZZLE_NONE);
    make_map_out(enc, &p.mOut, d_out);
    make_map(enc, &p.mWg, d_in[7], F_, D_, 64, CU_TENSOR_MAP_SWIZZLE_NONE, 32);
    make_map(enc, &p.mWu, d_in[8], F_, D_, 64, CU_TENSOR_MAP_SWIZZLE_NONE, 32);
    make_map(enc, &p.mWd, d_in[9], D_, F_, 8, CU_TENSOR_MAP_SWIZZLE_NONE, 256);
    fused_kernel<<<132, NTHREADS, SMEM_BYTES, cudaStreamPerThread>>>(p);
}
```

```cpp
#include <cuda_runtime.h>
#include <cuda.h>
#include <cuda_bf16.h>
#include <stdint.h>

typedef __nv_bfloat16 bf16;

constexpr int S_ = 2048, D_ = 512, F_ = 1792;
constexpr int NCTA = 128;
constexpr int NTHREADS = 512;
constexpr int NSTAGE = 6;
constexpr int REGION = 32768;
constexpr int FFN_CTAS = F_ / 16;
constexpr uint32_t SPIN_LIMIT = 1u << 22;
constexpr int HOLD = 200;
constexpr int PACE = 270;
constexpr int PACE0 = 100;
constexpr int A_GAP = 230;
constexpr int B_GAP = 240;
constexpr int LATE_GAP = 240;
constexpr int INIT_GAP = 360;
constexpr int INIT_NS = 300;
constexpr int PF_T0 = 3000;
constexpr int PF_GAP = 850;
constexpr int PF_N0 = 4;
constexpr int FFN_S0 = 4;
constexpr int FFN_W = 7;
constexpr int ROUTER_C = 4;
constexpr int HINT_AT = 5;
constexpr int SUM_T0 = 15000;
constexpr int PS1 = 24;
constexpr int NA = 3;
constexpr int KEY_NS = 300;
constexpr int SETUP = 13;
constexpr int T0 = 8;
constexpr int HSK = 1;

constexpr int OFF_MISC = 7 * REGION;
constexpr int B_F = OFF_MISC;
constexpr int B_G1 = B_F + 64;
constexpr int B_G4 = B_G1 + 8;
constexpr int B_XE = B_G4 + 8;
constexpr int B_GO1 = B_XE + 8;
constexpr int B_GO0 = B_GO1 + 8;
constexpr int B_EPOCH = B_GO0 + 8;
constexpr int B_RETRY = B_EPOCH + 8;
constexpr int B_INIT = B_RETRY + 8;
constexpr int B_FULL = B_INIT + 8;
constexpr int B_EMPTY = B_FULL + 48;
constexpr int B_PUB = B_EMPTY + 48;
constexpr int B_FREE = B_PUB + 8;
constexpr int B_BL = B_FREE + 24;
constexpr int B_TAIL = B_BL + 48;
constexpr int B_HX = B_TAIL + 8;
constexpr int B_FFN = B_HX + 8;
constexpr int B_ROLE = B_FFN + 40;
constexpr int B_EARLY = B_ROLE + 8;
constexpr int B_GATE = B_EARLY + 8;
constexpr int B_G2 = B_GATE + 8;
constexpr int B_LOW = B_G2 + 8;
constexpr int B_G0 = B_LOW + 8;
constexpr int M_EPOCH = B_G0 + 8;
constexpr int M_ROLE = M_EPOCH + 4;
constexpr int M_KEY = OFF_MISC + 416;
constexpr int M_HX = OFF_MISC + 512;
constexpr int M_G = M_HX + 1024;
constexpr int M_XS = M_G + 512;
constexpr int SMEM_BYTES = 232448;
static_assert(NA >= 3 && M_ROLE + 4 <= M_KEY && M_XS + 512 <= SMEM_BYTES, "smem");

struct Scratch {
    unsigned char ab[8 * 32 * 16384];
    unsigned int pair[65 * 32];
    unsigned int ready[16 * 32];
    unsigned int gate[S_];
    unsigned int part[FFN_CTAS / 2 * D_];
    unsigned int phint[4 * 16 * 8];
    unsigned int keys[8 * NCTA];
};
__device__ __align__(1024) Scratch g_s;

struct Params {
    Scratch* s;
    bf16* out;
    const bf16 *x, *gate_w, *w_r, *wg, *wu, *wd;
    CUtensorMap mDre, mDim, mX1, mX2, mCre, mCim, mAB, mOut, mWg, mWu, mWd;
};

#define ELECT "{.reg .pred p; elect.sync _|p, 0xffffffff; @p "
__device__ __forceinline__ uint32_t smem_u32(const void* p) { return (uint32_t)__cvta_generic_to_shared(p); }
__device__ __forceinline__ uint32_t clk() { return (uint32_t)clock64(); }
__device__ __forceinline__ void spin_until(uint32_t t) { while ((int)(clk() - t) < 0) {} }
template <int NS>
__device__ __forceinline__ void sleep_until(uint32_t t) { while ((int)(clk() - t) < 0) __nanosleep(NS); }
__device__ __forceinline__ void mbar_init_elect(uint32_t bar, uint32_t cnt) {
    asm volatile(ELECT "mbarrier.init.shared::cta.b64 [%0], %1;}" ::"r"(bar), "r"(cnt) : "memory");
}
__device__ __forceinline__ void mbar_expect_tx_elect(uint32_t bar, uint32_t bytes) {
    asm volatile(ELECT "mbarrier.arrive.expect_tx.shared::cta.b64 _, [%0], %1;}" ::"r"(bar), "r"(bytes) : "memory");
}
template <int N = 1>
__device__ __forceinline__ void mbar_arrive_elect(uint32_t bar) {
    asm volatile(ELECT "mbarrier.arrive.shared::cta.b64 _, [%0], %1;}" ::"r"(bar), "n"(N) : "memory");
}
__device__ __forceinline__ void mbar_arrive_if(uint32_t bar, bool pred) {
    asm volatile("{.reg .pred p; setp.ne.b32 p, %1, 0; @p mbarrier.arrive.shared::cta.b64 _, [%0];}" ::"r"(bar), "r"((int)pred) : "memory");
}
__device__ __forceinline__ void mbar_arrive_warp(uint32_t bar) {
    __syncwarp();
    mbar_arrive_if(bar, (threadIdx.x & 31) == 0);
}
template <int N>
__device__ __forceinline__ void release_pair(uint32_t bar, uint32_t rbar, bool pred) {
    asm volatile("{.reg .pred p; setp.ne.b32 p, %2, 0; @p mbarrier.arrive.shared::cta.b64 _, [%0], %3;"
                 " @p mbarrier.arrive.shared::cluster.b64 _, [%1], %3;}" ::"r"(bar), "r"(rbar), "r"((int)pred), "n"(N) : "memory");
}
__device__ __forceinline__ uint32_t mapa(uint32_t a, uint32_t cta) {
    uint32_t r;
    asm volatile("mapa.shared::cluster.u32 %0, %1, %2;" : "=r"(r) : "r"(a), "r"(cta));
    return r;
}
__device__ __forceinline__ bool mbar_test(uint32_t bar, uint32_t parity) {
    uint32_t ok;
    asm volatile("{.reg .pred p; mbarrier.test_wait.parity.shared::cta.b64 p, [%1], %2; selp.u32 %0,1,0,p;}"
                 : "=r"(ok) : "r"(bar), "r"(parity) : "memory");
    return ok;
}
__device__ __forceinline__ void mbar_wait(uint32_t bar, uint32_t parity) {
    asm volatile("{.reg .pred p, q; .reg .u32 n; mov.u32 n, 0;\n"
                 "W%=: mbarrier.try_wait.parity.shared::cta.b64 p, [%0], %1;\n"
                 "add.u32 n, n, 1; setp.lt.and.u32 q, n, %2, !p; @q bra W%=; @!p trap;}" ::"r"(bar), "r"(parity), "n"(SPIN_LIMIT) : "memory");
}
__device__ __forceinline__ void mbar_wait_cluster(uint32_t bar, uint32_t parity) {
    asm volatile("{.reg .pred p, q; .reg .u32 n; mov.u32 n, 0;\n"
                 "W%=: mbarrier.try_wait.parity.acquire.cluster.shared::cta.b64 p, [%0], %1;\n"
                 "add.u32 n, n, 1; setp.lt.and.u32 q, n, %2, !p; @q bra W%=; @!p trap;}" ::"r"(bar), "r"(parity), "n"(SPIN_LIMIT) : "memory");
}
__device__ __forceinline__ void mbar_spin(uint32_t bar, uint32_t parity) {
    asm volatile("{.reg .pred p;\nW%=: mbarrier.try_wait.parity.shared::cta.b64 p, [%0], %1; @!p bra W%=;}" ::"r"(bar), "r"(parity) : "memory");
}
__device__ __forceinline__ void cluster_arrive() { asm volatile("barrier.cluster.arrive.relaxed.aligned;" ::: "memory"); }
__device__ __forceinline__ void cluster_wait() { asm volatile("barrier.cluster.wait.acquire.aligned;" ::: "memory"); }
__device__ __forceinline__ void cta_bar() { asm volatile("bar.sync 0, 512;" ::: "memory"); }
__device__ __forceinline__ void side_bar() { asm volatile("bar.sync 1, 128;" ::: "memory"); }
__device__ __forceinline__ void tma2d_elect(uint32_t dst, const CUtensorMap* m, int c0, int c1, uint32_t bar) {
    asm volatile(ELECT "cp.async.bulk.tensor.2d.shared::cluster.global.mbarrier::complete_tx::bytes [%0], [%1, {%3,%4}], [%2];}"
                 ::"r"(dst), "l"(m), "r"(bar), "r"(c0), "r"(c1) : "memory");
}
__device__ __forceinline__ void tma2d_pair_elect(uint32_t dst, const CUtensorMap* m, int c0, int c1, uint32_t bar) {
    asm volatile(ELECT "cp.async.bulk.tensor.2d.shared::cluster.global.mbarrier::complete_tx::bytes.multicast::cluster"
                 " [%0], [%1, {%3,%4}], [%2], %5;}" ::"r"(dst), "l"(m), "r"(bar), "r"(c0), "r"(c1), "h"((uint16_t)3) : "memory");
}
__device__ __forceinline__ void tma3d_elect(uint32_t dst, const CUtensorMap* m, int row, int chunk, uint32_t bar) {
    asm volatile(ELECT "cp.async.bulk.tensor.3d.shared::cluster.global.mbarrier::complete_tx::bytes [%0], [%1, {%3,%4,%5}], [%2];}"
                 ::"r"(dst), "l"(m), "r"(bar), "r"(0), "r"(row), "r"(chunk) : "memory");
}
__device__ __forceinline__ void bulk_wait_read() {
    asm volatile("cp.async.bulk.commit_group; cp.async.bulk.wait_group.read 0;" ::: "memory");
    __syncwarp();
}
__device__ __forceinline__ void fence_proxy_async_smem() { asm volatile("fence.proxy.async.shared::cta;" ::: "memory"); }
__device__ __forceinline__ uint32_t ld_relaxed(const void* p) {
    uint32_t v;
    asm volatile("ld.relaxed.gpu.global.u32 %0, [%1];" : "=r"(v) : "l"(p) : "memory");
    return v;
}
__device__ __forceinline__ uint4 ld_relaxed4(const void* p) {
    uint4 v;
    asm volatile("ld.relaxed.gpu.global.v4.u32 {%0,%1,%2,%3}, [%4];" : "=r"(v.x), "=r"(v.y), "=r"(v.z), "=r"(v.w) : "l"(p) : "memory");
    return v;
}
__device__ __forceinline__ void red_inc_if(unsigned int* p, bool pred) {
    asm volatile("{.reg .pred p; setp.ne.b32 p, %1, 0; @p red.relaxed.gpu.global.add.u32 [%0], 1;}" ::"l"(p), "r"((int)pred) : "memory");
}
__device__ __forceinline__ uint32_t tagf(float v, uint32_t par) { return (__float_as_uint(v) & ~1u) | par; }
__device__ __forceinline__ uint4 wait_tags(const unsigned int* p, int bit, uint32_t par) {
    uint32_t n = 0;
    while (true) {
        const uint4 v = ld_relaxed4(p);
        const uint32_t m = par ? (v.x & v.y & v.z & v.w) : ~(v.x | v.y | v.z | v.w);
        if (__all_sync(0xffffffffu, (m >> bit) & 1u)) return v;
        __nanosleep(100);
        if (++n > SPIN_LIMIT) __trap();
    }
}
__device__ __forceinline__ void wait_counter(const unsigned int* p, uint32_t want) {
    uint32_t n = 0;
    while (!__all_sync(0xffffffffu, (int)(ld_relaxed(p) - want) >= 0)) {
        __nanosleep(200);
        if (++n > SPIN_LIMIT) __trap();
    }
    asm volatile("fence.acquire.gpu;" ::: "memory");
}
__device__ __forceinline__ uint32_t stale_tags(uint32_t a, uint32_t par) {
    uint32_t r;
    asm volatile("{.reg .b32 v<16>;\n"
                 "ld.shared.u32 v0, [%1]; ld.shared.u32 v1, [%1+256]; ld.shared.u32 v2, [%1+512]; ld.shared.u32 v3, [%1+768];\n"
                 "ld.shared.u32 v4, [%1+4096]; ld.shared.u32 v5, [%1+4352]; ld.shared.u32 v6, [%1+4608]; ld.shared.u32 v7, [%1+4864];\n"
                 "ld.shared.u32 v8, [%1+8192]; ld.shared.u32 v9, [%1+8448]; ld.shared.u32 v10, [%1+8704]; ld.shared.u32 v11, [%1+8960];\n"
                 "ld.shared.u32 v12, [%1+12288]; ld.shared.u32 v13, [%1+12544]; ld.shared.u32 v14, [%1+12800]; ld.shared.u32 v15, [%1+13056];\n"
                 "lop3.b32 v0, v0, v1, %2, 0x7e; lop3.b32 v2, v2, v3, %2, 0x7e; lop3.b32 v4, v4, v5, %2, 0x7e; lop3.b32 v6, v6, v7, %2, 0x7e;\n"
                 "lop3.b32 v8, v8, v9, %2, 0x7e; lop3.b32 v10, v10, v11, %2, 0x7e; lop3.b32 v12, v12, v13, %2, 0x7e; lop3.b32 v14, v14, v15, %2, 0x7e;\n"
                 "lop3.b32 v0, v0, v2, v4, 0xfe; lop3.b32 v6, v6, v8, v10, 0xfe; lop3.b32 v0, v0, v6, v12, 0xfe; or.b32 %0, v0, v14;}"
                 : "=r"(r) : "r"(a), "r"(par) : "memory");
    return r;
}
template <int OFF>
__device__ __forceinline__ uint4 ldg_nc(const void* p) {
    uint4 v;
    asm volatile("ld.global.nc.v4.u32 {%0,%1,%2,%3}, [%4+%5];" : "=r"(v.x), "=r"(v.y), "=r"(v.z), "=r"(v.w) : "l"(p), "n"(OFF));
    return v;
}
template <int OFF>
__device__ __forceinline__ void stg128(void* p, const uint4& v) {
    asm volatile("st.global.v4.u32 [%0+%5], {%1,%2,%3,%4};" ::"l"(p), "r"(v.x), "r"(v.y), "r"(v.z), "r"(v.w), "n"(OFF) : "memory");
}
template <int OFF>
__device__ __forceinline__ void sts128(uint32_t a, const uint4& v) {
    asm volatile("st.shared.v4.u32 [%0+%5], {%1,%2,%3,%4};" ::"r"(a), "r"(v.x), "r"(v.y), "r"(v.z), "r"(v.w), "n"(OFF) : "memory");
}
__device__ __forceinline__ uint4 lds128(uint32_t a) {
    uint4 v;
    asm volatile("ld.shared.v4.u32 {%0,%1,%2,%3}, [%4];" : "=r"(v.x), "=r"(v.y), "=r"(v.z), "=r"(v.w) : "r"(a) : "memory");
    return v;
}
template <int OFF>
__device__ __forceinline__ void red_bf16x8(void* p, uint32_t x, uint32_t y, uint32_t z, uint32_t w) {
    asm volatile("red.relaxed.gpu.global.add.noftz.v4.bf16x2 [%0+%5], {%1,%2,%3,%4};"
                 ::"l"(p), "r"(x), "r"(y), "r"(z), "r"(w), "n"(OFF) : "memory");
}
__device__ __forceinline__ void sched_cut() {
    asm volatile("{.reg .pred p; .reg .u64 t; .reg .u32 a, b;\n"
                 "C%=: mov.u64 t, %%clock64; mov.b64 {a, b}, t; setp.eq.u32 p, a, %0; @p bra C%=;}" ::"n"(0) : "memory");
}
__device__ __forceinline__ uint32_t pin(uint32_t v) { return __shfl_xor_sync(0xffffffffu, v, 0); }
template <class T>
__device__ __forceinline__ T* pin(T* p) { return (T*)__shfl_xor_sync(0xffffffffu, (unsigned long long)p, 0); }
__device__ __forceinline__ float selpf(float a, float b, bool p) {
    float r;
    asm("{.reg .pred q; setp.ne.b32 q, %3, 0; selp.f32 %0, %1, %2, q;}" : "=f"(r) : "f"(a), "f"(b), "r"((int)p));
    return r;
}
template <int N, int MASK, int SZ>
__device__ __forceinline__ void halve(float (&a)[SZ]) {
    const bool up = threadIdx.x & MASK;
#pragma unroll
    for (int j = 0; j < N; j++) a[j] = selpf(a[N + j], a[j], up) + __shfl_xor_sync(0xffffffffu, selpf(a[j], a[N + j], up), MASK);
}
__device__ __forceinline__ float bflo(uint32_t u) { return __uint_as_float(u << 16); }
__device__ __forceinline__ float bfhi(uint32_t u) { return __uint_as_float(u & 0xffff0000u); }
__device__ __forceinline__ uint32_t pack_bf16(float lo, float hi) {
    uint32_t r;
    asm("cvt.rn.bf16x2.f32 %0, %1, %2;" : "=r"(r) : "f"(hi), "f"(lo));
    return r;
}
__device__ __forceinline__ uint32_t hmul2_bf16(uint32_t a, uint32_t b) {
    uint32_t r;
    asm("mul.rn.bf16x2 %0, %1, %2;" : "=r"(r) : "r"(a), "r"(b));
    return r;
}
__device__ __forceinline__ float rbf(float v) { return bflo(pack_bf16(v, 0.f)); }
__device__ __forceinline__ float sigmoidf_(float v) { return __fdividef(1.0f, 1.0f + __expf(-v)); }

__device__ __forceinline__ void wg_fence() { asm volatile("wgmma.fence.sync.aligned;" ::: "memory"); }
__device__ __forceinline__ void wg_commit() { asm volatile("wgmma.commit_group.sync.aligned;" ::: "memory"); }
template <int N> __device__ __forceinline__ void wg_wait() { asm volatile("wgmma.wait_group.sync.aligned %0;" ::"n"(N) : "memory"); }
__device__ __forceinline__ uint64_t desc128(uint32_t lo) { return (uint64_t)lo | (0x40000040ull << 32); }
__device__ __forceinline__ uint64_t desc64(uint32_t lo) { return (uint64_t)lo | (0x80000020ull << 32); }
template <int N>
__device__ __forceinline__ void fence_regs(float (&d)[N]) {
#pragma unroll
    for (int i = 0; i < N; i++) asm volatile("" : "+f"(d[i])::"memory");
}
template <int TB>
__device__ __forceinline__ void wgmma128(float (&d)[64], uint64_t da, uint64_t db, int scaleD) {
    asm volatile(
        "{ .reg .pred p; setp.ne.b32 p, %66, 0;\n"
        "wgmma.mma_async.sync.aligned.m64n128k16.f32.bf16.bf16 "
        "{%0,%1,%2,%3,%4,%5,%6,%7,%8,%9,%10,%11,%12,%13,%14,%15,%16,%17,%18,%19,%20,%21,%22,%23,%24,%25,%26,%27,%28,%29,%30,%31,"
        "%32,%33,%34,%35,%36,%37,%38,%39,%40,%41,%42,%43,%44,%45,%46,%47,%48,%49,%50,%51,%52,%53,%54,%55,%56,%57,%58,%59,%60,%61,%62,%63}, "
        "%64, %65, p, 1, 1, 0, %67;\n}"
        : "+f"(d[0]), "+f"(d[1]), "+f"(d[2]), "+f"(d[3]), "+f"(d[4]), "+f"(d[5]), "+f"(d[6]), "+f"(d[7]),
          "+f"(d[8]), "+f"(d[9]), "+f"(d[10]), "+f"(d[11]), "+f"(d[12]), "+f"(d[13]), "+f"(d[14]), "+f"(d[15]),
          "+f"(d[16]), "+f"(d[17]), "+f"(d[18]), "+f"(d[19]), "+f"(d[20]), "+f"(d[21]), "+f"(d[22]), "+f"(d[23]),
          "+f"(d[24]), "+f"(d[25]), "+f"(d[26]), "+f"(d[27]), "+f"(d[28]), "+f"(d[29]), "+f"(d[30]), "+f"(d[31]),
          "+f"(d[32]), "+f"(d[33]), "+f"(d[34]), "+f"(d[35]), "+f"(d[36]), "+f"(d[37]), "+f"(d[38]), "+f"(d[39]),
          "+f"(d[40]), "+f"(d[41]), "+f"(d[42]), "+f"(d[43]), "+f"(d[44]), "+f"(d[45]), "+f"(d[46]), "+f"(d[47]),
          "+f"(d[48]), "+f"(d[49]), "+f"(d[50]), "+f"(d[51]), "+f"(d[52]), "+f"(d[53]), "+f"(d[54]), "+f"(d[55]),
          "+f"(d[56]), "+f"(d[57]), "+f"(d[58]), "+f"(d[59]), "+f"(d[60]), "+f"(d[61]), "+f"(d[62]), "+f"(d[63])
        : "l"(da), "l"(db), "r"(scaleD), "n"(TB));
}

template <int N>
__device__ __forceinline__ void wgmma64_rs(float (&d)[N], const uint32_t* a, uint64_t db, int scaleD) {
    asm volatile(
        "{ .reg .pred p; setp.ne.b32 p, %37, 0;\n"
        "wgmma.mma_async.sync.aligned.m64n64k16.f32.bf16.bf16 "
        "{%0,%1,%2,%3,%4,%5,%6,%7,%8,%9,%10,%11,%12,%13,%14,%15,%16,%17,%18,%19,%20,%21,%22,%23,%24,%25,%26,%27,%28,%29,%30,%31}, "
        "{%32,%33,%34,%35}, %36, p, 1, 1, 1;\n}"
        : "+f"(d[0]), "+f"(d[1]), "+f"(d[2]), "+f"(d[3]), "+f"(d[4]), "+f"(d[5]), "+f"(d[6]), "+f"(d[7]),
          "+f"(d[8]), "+f"(d[9]), "+f"(d[10]), "+f"(d[11]), "+f"(d[12]), "+f"(d[13]), "+f"(d[14]), "+f"(d[15]),
          "+f"(d[16]), "+f"(d[17]), "+f"(d[18]), "+f"(d[19]), "+f"(d[20]), "+f"(d[21]), "+f"(d[22]), "+f"(d[23]),
          "+f"(d[24]), "+f"(d[25]), "+f"(d[26]), "+f"(d[27]), "+f"(d[28]), "+f"(d[29]), "+f"(d[30]), "+f"(d[31])
        : "r"(a[0]), "r"(a[1]), "r"(a[2]), "r"(a[3]), "l"(db), "r"(scaleD));
}
__device__ __forceinline__ void ldsm4(uint32_t* r, uint32_t a) {
    asm volatile("ldmatrix.sync.aligned.m8n8.x4.shared.b16 {%0,%1,%2,%3}, [%4];" : "=r"(r[0]), "=r"(r[1]), "=r"(r[2]), "=r"(r[3]) : "r"(a) : "memory");
}

__device__ __forceinline__ uint32_t get_role(uint32_t& smid) {
    uint32_t role;
    asm volatile("mov.u32 %0, %%smid;" : "=r"(smid));
    asm("{.reg .pred p, q; .reg .u32 t, a, b; shr.u32 t, %1, 1; mad.lo.u32 a, t, 293, -928; shr.u32 a, a, 8; mad.lo.u32 b, t, 8, -464;"
        " setp.lt.u32 p, t, 32; setp.lt.u32 q, t, 62; selp.u32 a, a, b, q; selp.u32 %0, t, a, p;}" : "=r"(role) : "r"(smid));
    return role;
}
__device__ __forceinline__ int tile_of_step(int step, int own) {
    const int u = step >= 17 ? step - 17 - (step > PS1) : step - 2;
    int e = (u + (u >= ((own ^ T0) & 14) ? 2 : 0)) ^ T0;
    if (step == 16 || step == PS1) e = own ^ 1;
    if (step < 2) e = own;
    return e + (step >= 17 || step == 1 ? 16 : 0);
}
__device__ __forceinline__ uint32_t router_key(float score, int row) {
    const float r = score + 0.0f;
    uint32_t u = pack_bf16(r, 0.f) & 0xffffu;
    u = (u & 0x8000u) ? (~u & 0xffffu) : (u | 0x8000u);
    if (r != r) u = 0;
    return (u << 16) | (uint32_t)(0x7fff - row);
}

#define g_fb_h ((float*)g_s.part)
#define g_fb_upd (g_fb_h + 2048)
#define g_fb_gate (g_fb_h + 4096)
#define g_fb_keys (g_s.part + 8192)
__global__ void fb_hidden(const bf16* x, const bf16* dre, const bf16* dim, const bf16* gw, const bf16* wr) {
    __shared__ float xs[D_];
    const int s = blockIdx.x, t = threadIdx.x;
    xs[t] = __bfloat162float(x[s * D_ + t]);
    __syncthreads();
    float a = 0.f, b = 0.f;
    for (int d = 0; d < D_; d++) { a = fmaf(xs[d], __bfloat162float(dre[t * D_ + d]), a); b = fmaf(xs[d], __bfloat162float(dim[t * D_ + d]), b); }
    ((bf16*)g_s.ab)[s * 1024 + t] = __float2bfloat16(a);
    ((bf16*)g_s.ab)[s * 1024 + 512 + t] = __float2bfloat16(b);
    if (t == 0) {
        float u = 0.f, v = 0.f;
        for (int d = 0; d < D_; d++) { u = fmaf(xs[d], __bfloat162float(gw[d]), u); v = fmaf(xs[d], __bfloat162float(wr[d]), v); }
        g_fb_gate[s] = sigmoidf_(u);
        g_fb_keys[s] = router_key(v, s);
    }
}
__device__ uint32_t fb_best() {
    uint32_t k = 0;
    for (int i = 0; i < S_; i++) k = max(k, g_fb_keys[i]);
    return k;
}
__global__ void fb_ffn1(const bf16* x, const bf16* wg, const bf16* wu) {
    const int f = blockIdx.x * blockDim.x + threadIdx.x, idx = 0x7fff - (int)(fb_best() & 0x7fffu);
    float a = 0.f, b = 0.f;
    for (int d = 0; d < D_; d++) {
        const float xv = __bfloat162float(x[idx * D_ + d]);
        a = fmaf(xv, __bfloat162float(wg[d * F_ + f]), a); b = fmaf(xv, __bfloat162float(wu[d * F_ + f]), b);
    }
    g_fb_h[f] = a * sigmoidf_(a) * b;
}
__global__ void fb_ffn2(const bf16* wd) {
    const int e = blockIdx.x * blockDim.x + threadIdx.x;
    const uint32_t u = fb_best() >> 16, rb = (u & 0x8000u) ? (u & 0x7fffu) : (~u & 0xffffu);
    float a = 0.f;
    for (int f = 0; f < F_; f++) a = fmaf(g_fb_h[f], __bfloat162float(wd[f * D_ + e]), a);
    g_fb_upd[e] = a * sigmoidf_(__uint_as_float(rb << 16));
}
__global__ void fb_seq(const bf16* x, const bf16* cre, const bf16* cim, bf16* out) {
    __shared__ float c[2][S_];
    __shared__ int idx;
    const int t = blockIdx.x, e = threadIdx.x;
    for (int i = e; i < S_; i += D_) { c[0][i] = __bfloat162float(cre[t * S_ + i]); c[1][i] = __bfloat162float(cim[t * S_ + i]); }
    if (e == 0) idx = 0x7fff - (int)(fb_best() & 0x7fffu);
    __syncthreads();
    float y = 0.f;
    for (int s = 0; s < S_; s++)
        y += c[0][s] * __bfloat162float(((const bf16*)g_s.ab)[s * 1024 + e]) - c[1][s] * __bfloat162float(((const bf16*)g_s.ab)[s * 1024 + 512 + e]);
    const float g = g_fb_gate[t];
    out[t * D_ + e] = __float2bfloat16(g * y + (1.f - g) * (__bfloat162float(x[t * D_ + e]) + (t == idx ? g_fb_upd[e] : 0.f)));
}

__device__ __forceinline__ void spare_job(const Params& p, unsigned char* smem, int sp, uint32_t tstart) {
    const int tid = threadIdx.x, warp = tid >> 5, lane = tid & 31;
    const uint32_t e1 = *(volatile unsigned int*)&p.s->pair[64 * 32 + sp] + 1u;
    const uint32_t par = e1 & 1u;
    uint32_t* sel = (uint32_t*)smem;
    float* acc = (float*)(smem + 1024);
    __syncthreads();
    if (tid == 0) *(volatile unsigned int*)&p.s->pair[64 * 32 + sp] = e1;
    sleep_until<500>(tstart + SUM_T0);
    if (warp < 14) {
        uint32_t n = 0;
        while ((int)(ld_relaxed(p.s->phint + (sp * 16 + warp) * 8) - e1 * 8u) < 0) {
            __nanosleep(100);
            if (++n > SPIN_LIMIT) __trap();
        }
        const unsigned int* src = p.s->part + warp * 4 * D_ + sp * 128 + lane * 4;
        uint4 v[4];
        while (true) {
            uint32_t bad = 0;
#pragma unroll
            for (int i = 0; i < 4; i++) v[i] = ld_relaxed4(src + i * D_);
#pragma unroll
            for (int i = 0; i < 4; i++) bad |= (v[i].x ^ par) | (v[i].y ^ par) | (v[i].z ^ par) | (v[i].w ^ par);
            if (!__any_sync(0xffffffffu, bad & 1u)) break;
            if (++n > SPIN_LIMIT) __trap();
        }
        float4 s = make_float4(0.f, 0.f, 0.f, 0.f);
#pragma unroll
        for (int i = 0; i < 4; i++) {
            s.x += __uint_as_float(v[i].x); s.y += __uint_as_float(v[i].y);
            s.z += __uint_as_float(v[i].z); s.w += __uint_as_float(v[i].w);
        }
        *(float4*)&acc[warp * 128 + lane * 4] = s;
    } else if (warp == 14) {
        const uint4 k4 = wait_tags(p.s->keys + lane * 4, 15, par);
        const uint32_t k = __reduce_max_sync(0xffffffffu, max(max(k4.x, k4.y), max(k4.z, k4.w)));
        const int idx = 0x7fff - (int)(k & 0x7fffu);
        const uint4 g4 = wait_tags(p.s->gate + (idx & ~3), 0, par);
        const uint32_t gw = (idx & 2) ? ((idx & 1) ? g4.w : g4.z) : ((idx & 1) ? g4.y : g4.x);
        const uint32_t u = k >> 16;
        const uint32_t rb = (u & 0x8000u) ? (u & 0x7fffu) : (~u & 0xffffu);
        const float og = 1.f - __uint_as_float(gw & ~1u), rs = sigmoidf_(__uint_as_float(rb << 16));
        if (lane == 0) { sel[0] = idx; sel[1] = pack_bf16(og, og); sel[2] = pack_bf16(rs, rs); }
        sleep_until<500>(tstart + SUM_T0 + 3000);
        wait_counter(p.s->ready + (idx >> 7) * 32, e1 * 8u);
    }
    __syncthreads();
    if (tid < 64) {
        float t0 = 0.f, t1 = 0.f;
#pragma unroll
        for (int i = 0; i < 14; i++) {
            const float2 z = *(const float2*)&acc[i * 128 + tid * 2];
            t0 += z.x; t1 += z.y;
        }
        asm volatile("red.relaxed.gpu.global.add.noftz.bf16x2 [%0], %1;" ::"l"(p.out + sel[0] * D_ + sp * 128 + tid * 2),
                     "r"(hmul2_bf16(sel[1], hmul2_bf16(sel[2], pack_bf16(t0, t1)))) : "memory");
    }
}

__host__ __device__ constexpr int off_d(int c) { return (c < 2 ? 1 : c / 2 + 2) * REGION + (c & 1) * 16384; }
__host__ __device__ constexpr int off_xe(int c) { return (c < 2 ? 6 * REGION : c < 4 ? 16384 : c < 6 ? 0 : 6 * REGION + 16384) + (c & 1) * 8192; }
__host__ __device__ constexpr int off_xl(int c) { return c < 4 ? 2 * REGION + c * 8192 : off_xe(c - 4); }

__global__ void __cluster_dims__(2, 1, 1) __launch_bounds__(NTHREADS, 1)
fused_kernel(const __grid_constant__ Params p) {
    extern __shared__ __align__(1024) unsigned char smem[];
    const uint32_t sb = smem_u32(smem);
    const int tid = threadIdx.x, lane = tid & 31;
    const int rank = blockIdx.x & 1;
    if (__all_sync(0xffffffffu, tid != 0)) {
        spin_until(clk() + HOLD);
        const int w = __shfl_sync(0xffffffffu, tid >> 5, 0);
        const uint32_t b1 = sb + B_F + 8 * w;
        if (w >= 2) mbar_init_elect(b1, 1);
        if (w < 5) mbar_init_elect(b1 + 360, w < 4 ? 1 : 4);
        mbar_init_elect(b1 + 120, w < 7 ? 5 : w < 14 ? 4 : w - 12);
        mbar_init_elect(b1 + 240, 1);
        if (w == 9 || w == 15) mbar_expect_tx_elect(b1 + 240, w == 9 ? 2048 : 4);
        asm volatile("fence.mbarrier_init.release.cluster;" ::: "memory");
        cta_bar();
        cluster_arrive();
    } else {
        uint32_t s0, t1 = 0;
        const uint32_t r0 = get_role(s0);
        const int xrow = (r0 & 3) * 256 + (r0 & 32) * 4 + rank * 64;
        mbar_init_elect(sb + B_F, 1);
        if (r0 >= 64) {
            cta_bar();
            cluster_arrive();
        } else {
#pragma unroll
            for (int c = 0; c < 8; c++) {
                if (c == 2) { cta_bar(); cluster_arrive(); }
                if (c) spin_until(t1 + c * PACE);
                if (c == 1) mbar_init_elect(sb + B_F + 8, 1);
                tma2d_elect(sb + off_xe(c), &p.mX1, c * 64, xrow, sb + B_F + 8 * c);
                tma2d_elect(sb + off_d(c), &p.mDre + ((r0 >> 2) & 1), c * 64, (r0 & 24) * 16, sb + B_F + 8 * c);
                mbar_expect_tx_elect(sb + B_F + 8 * c, 24576);
                if (!c) {
                    t1 = clk() + PACE0;
                    sched_cut();
                    mbar_init_elect(sb + B_G0, 1);
                    tma2d_elect(sb + off_xl(0), &p.mX1, 0, xrow + 1024, sb + B_G0);
                    mbar_expect_tx_elect(sb + B_G0, 8192);
                }
            }
            tma2d_elect(sb + off_xl(1), &p.mX1, 64, xrow + 1024, sb + B_G1);
            mbar_expect_tx_elect(sb + B_G1, 8192);
            spin_until(t1 + 8 * PACE);
            tma3d_elect(sb + off_xl(2), &p.mX2, xrow + 1024, 2, sb + B_G2);
            mbar_expect_tx_elect(sb + B_G2, 16384);
            if (!(r0 & 16))
                asm volatile(ELECT "cp.async.bulk.prefetch.tensor.3d.L2.global [%0, {%1,%2,%3}];}"
                             ::"l"(&p.mX2), "r"(0), "r"(xrow + 1024), "r"(4 + ((r0 >> 2) & 2)) : "memory");
        }
    }
    uint32_t tstart = clk() - 1000;
    const int warp = __shfl_sync(0xffffffffu, tid >> 5, 0);
    uint32_t smid;
    const uint32_t role = get_role(smid);
    if (role >= 64) {
        spare_job(p, smem, smid & 3, tstart);
        return;
    }
    const int gpc = role & 7;
    const int tn = (role >> 3) & 3;
    const int comp = gpc >> 2;
    const int own = (gpc & 3) * 4 + ((role >> 5) & 1) * 2 + rank;
    const int blk = comp * 4 + tn;
    const int cta = gpc * 16 + (role >> 3) * 2 + rank;
    constexpr unsigned long long FFN_PAIRS = 0xffff3f3f7fffff1full;
    const bool ffn = (FFN_PAIRS >> (cta >> 1)) & 1;
    const int fp = __popcll(FFN_PAIRS & ((1ull << (cta >> 1)) - 1));

    if (warp < 4) {
        asm volatile("setmaxnreg.dec.sync.aligned.u32 64;");
        const int tab = tile_of_step(lane, own);
        const uint32_t bdst = sb + 16384 + rank * 8192;
        const int brow = blk * 4096 + rank * 64;
        if (warp == 0) {
            mbar_spin(sb + B_XE, 0);
            tma3d_elect(sb + off_xl(4), &p.mX2, own * 64 + 1024, 4, sb + B_G4);
            tma3d_elect(sb + off_xl(6), &p.mX2, own * 64 + 1024, 6, sb + B_G4);
            mbar_expect_tx_elect(sb + B_G4, 32768);
#define LOAD_A() const int e = __shfl_sync(0xffffffffu, tab, step);                                             \
                 const uint32_t bar = sb + 8 * slot;                                                            \
                 mbar_spin(bar + B_EMPTY, ph);                                                                  \
                 tma2d_elect(sb + slot * REGION, &p.mCre + comp, e * 64, own * 128, bar + B_FULL);              \
                 mbar_expect_tx_elect(bar + B_FULL, 16384)
            uint32_t slot = 0, ph = 0;
            int step = 0;
#pragma unroll 1
            for (int i = 0; i < NSTAGE; i++) {
                step = slot = i < 2 ? i ^ 1 : i;
                LOAD_A();
                if (i == 2 || i == 3) spin_until(clk() + A_GAP);
            }
            step = NSTAGE;
            slot = 0; ph = 1;
#pragma unroll 1
            for (int h = 0; h < 3; h++) {
                const int last = h == 0 ? 16 : h == 1 ? PS1 : 32 - NA;
#pragma unroll 1
                for (; step < last; step++) {
                    LOAD_A();
                    tma2d_pair_elect(bdst + slot * REGION, &p.mAB, 0, brow + e * 128, bar + B_BL);
                    mbar_expect_tx_elect(bar + B_BL, 16384);
                    if (++slot == NSTAGE) { slot = 0; ph ^= 1; }
                }
                if (h == 2) break;
                LOAD_A();
                tma2d_elect(bdst + slot * REGION, &p.mAB, 0, brow + e * 128, bar + B_BL);
                tma2d_elect((bdst ^ 8192) + slot * REGION, &p.mAB, 0, (brow ^ 64) + e * 128, bar + B_BL);
                mbar_expect_tx_elect(bar + B_BL, 16384);
                step++;
                if (++slot == NSTAGE) { slot = 0; ph ^= 1; }
            }
            mbar_spin(sb + B_LOW, 0);
            uint32_t aslot = 6;
#pragma unroll 1
            for (; step < 32; step++) {
                const int e = __shfl_sync(0xffffffffu, tab, step);
                const uint32_t bar = sb + 8 * slot;
                tma2d_elect(sb + aslot * REGION, &p.mCre + comp, e * 64, own * 128, bar + B_FULL);
                mbar_expect_tx_elect(bar + B_FULL, 16384);
                mbar_expect_tx_elect(bar + B_BL, 16384);
                mbar_spin(bar + B_EMPTY, ph);
                tma2d_pair_elect(bdst + slot * REGION, &p.mAB, 0, brow + e * 128, bar + B_BL);
                aslot = slot;
                if (++slot == NSTAGE) { slot = 0; ph ^= 1; }
            }
        } else if (warp == 1) {
            cluster_wait();
            if (lane == 0)
                asm volatile("st.async.weak.shared::cluster.mbarrier::complete_tx::bytes.u32 [%0], %1, [%2];"
                             ::"r"(mapa(sb + M_ROLE, rank ^ 1)), "r"(role), "r"(mapa(sb + B_ROLE, rank ^ 1)) : "memory");
            mbar_wait_cluster(sb + B_ROLE, 0);
            if (*(volatile uint32_t*)(smem + M_ROLE) != role) __trap();
            mbar_wait(sb + B_EPOCH, 0);
            const uint32_t want = (*(volatile uint32_t*)(smem + M_EPOCH) + 1u) * 4u;
            const int eh = __shfl_sync(0xffffffffu, tab, 2 + (lane & 3));
            const unsigned int* hp = p.s->pair + (blk * 8 + (eh >> 1)) * 32 + 2 + (eh & 1);
            uint32_t seen = 0;
            int rows[4];
#pragma unroll
            for (int i = 0; i < 4; i++) {
                rows[i] = brow + __shfl_sync(0xffffffffu, tab, 2 + i) * 128;
                mbar_expect_tx_elect(sb + B_BL + 8 * (2 + i), 16384);
            }
            mbar_wait(sb + B_GO1, 0);
            asm volatile(ELECT "prefetch.tensormap [%0];}" ::"l"(&p.mAB) : "memory");
            mbar_wait(sb + B_EMPTY + 8 * 3, 0);
            mbar_spin(sb + B_EMPTY + 8 * 2, 0);
            uint32_t t3 = 0;
#pragma unroll
            for (int i = 0; i < 4; i++) {
                while (!((seen >> i) & 1u)) seen = __ballot_sync(0xffffffffu, ld_relaxed(hp) == want);
                if (i) spin_until(t3 + B_GAP);
                t3 = clk();
                if (i >= 2) mbar_spin(sb + B_EMPTY + 8 * (2 + i), 0);
                tma2d_pair_elect(bdst + (2 + i) * REGION, &p.mAB, 0, rows[i], sb + B_BL + 8 * (2 + i));
            }
            mbar_wait(sb + B_FREE, 0);
            unsigned char* gdst = p.s->ab + (blk * 32 + own + 16) * 16384;
            t3 = clk();
#pragma unroll 1
            for (int i = 0; i < 16; i++) {
                sleep_until<20>(t3);
                t3 += LATE_GAP;
                asm volatile(ELECT "cp.async.bulk.global.shared::cta.bulk_group [%0], [%1], 1024;}"
                             ::"l"(gdst + i * 1024), "r"(sb + 6 * REGION + i * 1024) : "memory");
            }
            bulk_wait_read();
            mbar_arrive_elect(sb + B_FREE + 8);
            mbar_wait(sb + B_PUB, 0);
            if (lane == 0) {
                asm volatile("fence.proxy.async.global;" ::: "memory");
                asm volatile("red.release.gpu.global.add.u32 [%0], 1;" ::"l"(p.s->ready + (cta >> 3) * 32) : "memory");
            }
            __syncwarp();
            __nanosleep(INIT_NS);
            wait_counter(p.s->ready + own * 32, want * 2u);
            mbar_arrive_elect(sb + B_INIT);
            asm volatile(ELECT "prefetch.tensormap [%0];}" ::"l"(&p.mOut) : "memory");
        } else {
            mbar_arrive_elect(sb + B_BL + 8 * (warp & 1));
            uint32_t k = warp == 3 ? 0 : 12;
#define PREFETCH_W() {                                                                                          \
                const char* src = (k >= 8 ? (const char*)p.wd + ((cta >> 5) * 2 + (k >> 1) - 4) * 229376        \
                                          : (const char*)((cta & 32) ? p.wu : p.wg) + ((cta >> 6) * 4 + (k >> 1)) * 229376) \
                                  + ((cta & 31) * 2 + (k & 1)) * 3584;                                          \
                asm volatile(ELECT "cp.async.bulk.prefetch.L2.global [%0], 3584;}" ::"l"(src) : "memory");      \
                k++; }
#pragma unroll 1
            while (k < PF_N0) {
                sleep_until<50>(tstart + PF_T0 + k * PF_GAP);
                __syncwarp();
                PREFETCH_W();
            }
            mbar_wait(sb + B_EPOCH, 0);
            const uint32_t par = (*(volatile uint32_t*)(smem + M_EPOCH) + 1u) & 1u;
            const uint32_t a0 = sb + 16384 + (lane >> 3) * 1028 + ((lane >> 2) & 1) * 144 + (lane & 3) * 32;
            const uint32_t retry = sb + B_RETRY + (warp & 1) * 240;
            uint32_t slot = warp, ph = 0, rph = 0;
            uint32_t j = ffn ? warp & 1 : 12;
#pragma unroll 1
            for (int step = warp; step < 32 || j < 12;) {
                const bool go = step < (j < 8 ? 32 - NA : 32);
                if (go) {
                    const uint32_t bar = sb + 8 * slot;
                    mbar_wait(bar + B_BL, ph);
#pragma unroll 1
                    while (__any_sync(0xffffffffu, stale_tags(a0 + slot * REGION, par) & 1u)) {
                        const int row = blk * 4096 + __shfl_sync(0xffffffffu, tab, step) * 128;
                        mbar_expect_tx_elect(retry, 16384);
                        tma2d_elect(sb + slot * REGION + 16384, &p.mAB, 0, row, retry);
                        tma2d_elect(sb + slot * REGION + 24576, &p.mAB, 0, row + 64, retry);
                        mbar_spin(retry, rph);
                        rph ^= 1u;
                    }
                    mbar_arrive_elect<4>(bar + B_FULL);
                }
                if (j < 12 && step >= FFN_S0 + j * FFN_W / 4 && __any_sync(0xffffffffu, mbar_test(sb + B_FREE + 2 * (j & 12), 0))) {
                    const uint32_t fb = sb + B_FFN + 4 * (j & 6);
                    if (!(j & 1)) mbar_expect_tx_elect(fb, 8192);
                    tma2d_elect(sb + 6 * REGION + ((j + 4) & 7) * 4096, j < 8 ? &p.mWg + (j & 1) : &p.mWd,
                                j < 8 ? fp * 32 : rank * 256, j < 8 ? rank * 256 + (j >> 1) * 64 : fp * 32 + j * 8 - 64, fb);
                    j += 2;
                }
                if (k < 12) PREFETCH_W();
                if (go) {
                    step += 2;
                    slot += 2;
                    if (slot >= NSTAGE) { slot -= NSTAGE; ph ^= 1; }
                }
            }
        }
    } else if (warp < 8) {
        const int t = tid - 128, w = warp - 4;
        if (t == 0) {
            volatile unsigned int* ep = &p.s->pair[(blk * 8 + (own >> 1)) * 32 + rank];
            const uint32_t epoch = *ep;
            *(volatile uint32_t*)(smem + M_EPOCH) = epoch;
            *ep = epoch + 1;
        }
        mbar_arrive_if(sb + B_EPOCH, t == 0);
        const uint4 gw0 = ldg_nc<0>(p.gate_w + lane * 8), gw1 = ldg_nc<512>(p.gate_w + lane * 8);
        const uint4 rw0 = ldg_nc<0>(p.w_r + lane * 8), rw1 = ldg_nc<512>(p.w_r + lane * 8);
        mbar_wait(sb + B_EPOCH, 0);
        const uint32_t par = (*(volatile uint32_t*)(smem + M_EPOCH) + 1u) & 1u;
        mbar_wait(sb + B_F + 8 * ROUTER_C, 0);
        const int row0 = cta * 16 + w * 4;
        uint4 xr[8];
        {
            const char* xp = (const char*)p.x + (uint32_t)row0 * (D_ * 2) + lane * 16;
            xr[0] = ldg_nc<0>(xp);    xr[1] = ldg_nc<512>(xp);  xr[2] = ldg_nc<1024>(xp); xr[3] = ldg_nc<1536>(xp);
            xr[4] = ldg_nc<2048>(xp); xr[5] = ldg_nc<2560>(xp); xr[6] = ldg_nc<3072>(xp); xr[7] = ldg_nc<3584>(xp);
            float a[8];
#pragma unroll
            for (int i = 0; i < 4; i++) {
                const uint32_t xv[8] = {xr[2 * i].x, xr[2 * i].y, xr[2 * i].z, xr[2 * i].w,
                                        xr[2 * i + 1].x, xr[2 * i + 1].y, xr[2 * i + 1].z, xr[2 * i + 1].w};
                const uint32_t gv[8] = {gw0.x, gw0.y, gw0.z, gw0.w, gw1.x, gw1.y, gw1.z, gw1.w};
                const uint32_t rv[8] = {rw0.x, rw0.y, rw0.z, rw0.w, rw1.x, rw1.y, rw1.z, rw1.w};
                float u = 0.f, v = 0.f;
#pragma unroll
                for (int j = 0; j < 8; j++) {
                    const uint32_t pr = hmul2_bf16(xv[j], gv[j]);
                    u += bflo(pr); u += bfhi(pr);
                    v = fmaf(bflo(xv[j]), bflo(rv[j]), v); v = fmaf(bfhi(xv[j]), bfhi(rv[j]), v);
                }
                a[i] = u; a[4 + i] = v;
            }
            mbar_wait(sb + B_EARLY, 0);
            halve<4, 16>(a); halve<2, 8>(a); halve<1, 4>(a);
            a[0] += __shfl_xor_sync(0xffffffffu, a[0], 1);
            a[0] += __shfl_xor_sync(0xffffffffu, a[0], 2);
            const int row = row0 + ((lane >> 2) & 3);
            const float gate = rbf(sigmoidf_(rbf(a[0])));
            if (lane < 16 && (lane & 3) == 0)
                asm volatile("st.relaxed.gpu.global.u32 [%0], %1;" ::"l"(&p.s->gate[row]), "r"(tagf(gate, par)) : "memory");
            const uint32_t best = __reduce_max_sync(0xffffffffu, lane >= 16 ? router_key(a[0], row) : 0u);
            if (lane == 0) *(volatile uint32_t*)(smem + M_KEY + w * 4) = best;
            side_bar();
            if (t < 8) {
                const uint4 k = *(const uint4*)(smem + M_KEY);
                asm volatile("{.reg .b32 old; atom.relaxed.gpu.global.exch.b32 old, [%0], %1;}" ::"l"(&p.s->keys[t * NCTA + cta]),
                             "r"(max(max(k.x, k.y), max(k.z, k.w)) | (par << 15)) : "memory");
            }
            const uint32_t og = pack_bf16(1.f - gate, 1.f - gate);
#pragma unroll
            for (int i = 0; i < 8; i++) {
                const uint32_t o = __shfl_sync(0xffffffffu, og, 4 * (i >> 1));
                xr[i] = make_uint4(hmul2_bf16(o, xr[i].x), hmul2_bf16(o, xr[i].y), hmul2_bf16(o, xr[i].z), hmul2_bf16(o, xr[i].w));
            }
        }
        mbar_wait(sb + B_FREE, 0);
        __nanosleep(KEY_NS);
        if (w == 0) {
            const uint4 k4 = wait_tags(p.s->keys + gpc * NCTA + lane * 4, 15, par);
            const uint32_t k = __reduce_max_sync(0xffffffffu, max(max(k4.x, k4.y), max(k4.z, k4.w)));
            sts128<M_XS>(sb + lane * 16, ldg_nc<0>(p.x + (0x7fff - (k & 0x7fffu)) * D_ + rank * 256 + lane * 8));
        } else if (w == 1) {
            const uint4 g4 = wait_tags(p.s->gate + own * 128 + lane * 4, 0, par);
            const uint32_t sg = comp ? 0x80008000u : 0u;
            sts128<M_G>(sb + lane * 16, make_uint4(__byte_perm(g4.x, 0, 0x3232) ^ sg, __byte_perm(g4.y, 0, 0x3232) ^ sg,
                                                   __byte_perm(g4.z, 0, 0x3232) ^ sg, __byte_perm(g4.w, 0, 0x3232) ^ sg));
            mbar_arrive_warp(sb + B_GATE);
        }
        side_bar();
        char* op = (char*)p.out + (uint32_t)row0 * (D_ * 2) + lane * 16;
        float a[16];
#pragma unroll
        for (int i = 0; i < 16; i++) a[i] = 0.f;
#pragma unroll 1
        for (int i = 0; i < 4; i++) {
            if (i == 2) {
                mbar_wait(sb + B_FREE + 8, 0);
                const uint32_t t2 = clk() + w * (INIT_GAP / 4);
#pragma unroll
                for (int j = 0; j < 8; j++) {
                    sleep_until<20>(t2 + j * INIT_GAP);
                    *(uint4*)(op + j * 512) = xr[j];
                }
                mbar_arrive_warp(sb + B_PUB);
            }
            if (ffn) {
                const float xs0 = __bfloat162float(((const bf16*)(smem + M_XS))[64 * i + (t >> 2)]);
                const float xs1 = __bfloat162float(((const bf16*)(smem + M_XS))[64 * i + 32 + (t >> 2)]);
                const uint32_t wa = sb + 6 * REGION + (i ^ 2) * 8192 + t * 16;
                mbar_wait(sb + B_FFN + 8 * i, 0);
                const uint4 v0 = lds128(wa), v1 = lds128(wa + 4096), v2 = lds128(wa + 2048), v3 = lds128(wa + 6144);
                const uint32_t w0[8] = {v0.x, v0.y, v0.z, v0.w, v1.x, v1.y, v1.z, v1.w};
                const uint32_t w1[8] = {v2.x, v2.y, v2.z, v2.w, v3.x, v3.y, v3.z, v3.w};
#pragma unroll
                for (int k = 0; k < 8; k++) {
                    a[2 * k] = fmaf(xs1, bflo(w1[k]), fmaf(xs0, bflo(w0[k]), a[2 * k]));
                    a[2 * k + 1] = fmaf(xs1, bfhi(w1[k]), fmaf(xs0, bfhi(w0[k]), a[2 * k + 1]));
                }
                if (i == 1) {
                    side_bar();
                    mbar_arrive_if(sb + B_FREE + 16, t == 0);
                }
            }
        }
        if (!ffn) {
            mbar_arrive_warp(sb + B_LOW);
            return;
        }
        halve<8, 16>(a); halve<4, 8>(a); halve<2, 4>(a);
        const uint32_t ho = (lane >> 4) * 128 + (lane & 3) * 32 + ((lane >> 2) & 3) * 8;
        cluster_wait();
#pragma unroll
        for (int k = 0; k < 2; k++)
            asm volatile("st.async.weak.shared::cluster.mbarrier::complete_tx::bytes.v2.f32 [%0], {%1,%2}, [%3];"
                         ::"r"(mapa(sb + (k ? 6 * REGION + w * 512 : M_HX + w * 256) + ho, rank ^ k ^ 1)), "f"(a[0]), "f"(a[1]),
                           "r"(mapa(sb + B_HX, rank ^ k ^ 1)) : "memory");
        mbar_wait_cluster(sb + B_HX, 0);
        const float *hx = (const float*)(smem + M_HX) + lane, *hy = (const float*)(smem + 6 * REGION) + lane;
        const float gs = rbf(((hx[0] + hy[0]) + (hx[64] + hy[128])) + ((hx[128] + hy[256]) + (hx[192] + hy[384])));
        const float us = rbf(((hx[32] + hy[32]) + (hx[96] + hy[160])) + ((hx[160] + hy[288]) + (hx[224] + hy[416])));
        float* hrow = (float*)(smem + M_XS) + w * 32;
        hrow[lane] = rbf(rbf(gs * sigmoidf_(gs)) * us);
        fence_proxy_async_smem();
        mbar_arrive_warp(sb + B_LOW);
        float o0 = 0.f, o1 = 0.f;
#pragma unroll 1
        for (int i = 0; i < 2; i++) {
            float4 hv[4];
            uint32_t vd[16];
#pragma unroll
            for (int k = 0; k < 4; k++) hv[k] = *(const float4*)&hrow[i * 16 + k * 4];
            mbar_wait(sb + B_FFN + 8 * i, 1);
#pragma unroll
            for (int k = 0; k < 16; k++) vd[k] = *(const volatile uint32_t*)(smem + 6 * REGION + 16384 + i * 8192 + k * 512 + t * 4);
#pragma unroll
            for (int k = 0; k < 4; k++) {
                o0 = fmaf(hv[k].x, bflo(vd[4 * k]), o0);     o1 = fmaf(hv[k].x, bfhi(vd[4 * k]), o1);
                o0 = fmaf(hv[k].y, bflo(vd[4 * k + 1]), o0); o1 = fmaf(hv[k].y, bfhi(vd[4 * k + 1]), o1);
                o0 = fmaf(hv[k].z, bflo(vd[4 * k + 2]), o0); o1 = fmaf(hv[k].z, bfhi(vd[4 * k + 2]), o1);
                o0 = fmaf(hv[k].w, bflo(vd[4 * k + 3]), o0); o1 = fmaf(hv[k].w, bfhi(vd[4 * k + 3]), o1);
            }
        }
        asm volatile("st.relaxed.gpu.global.v2.u32 [%0], {%1,%2};" ::"l"(&p.s->part[fp * D_ + rank * 256 + t * 2]),
                     "r"(tagf(o0, par)), "r"(tagf(o1, par)) : "memory");
        red_inc_if(p.s->phint + ((rank * 2 + (w >> 1)) * 16 + (fp >> 2)) * 8 + lane, lane == 0);
    } else {
        const int wg = (warp >> 2) - 2, wq = warp & 3;
        const uint32_t sbd = ((sb & 0x3FFFF) >> 4) + 0x10000;
        const bool lead = (tid & 127) == 0;
        const bool lead0 = lead && !wg, lead1 = lead && wg;
        const int q = lane & 3;
        float acc[64];
        const uint32_t rE = mapa(sb + B_EMPTY, rank ^ 1);
#define RELEASE(n, slot, pred) release_pair<n>(sb + B_EMPTY + 8 * (slot), rE + 8 * (slot), pred)
        const uint32_t ioff = wq * 4096 + (lane >> 2) * 64 + ((q ^ (lane >> 3)) << 4);
        const uint32_t sdst = pin(sb + 6 * REGION + (wg ? 0 : 16384) + ioff);
        unsigned char* gdst = pin(p.s->ab + (blk * 32 + own) * 16384 + ioff);
        unsigned int* hint = pin(p.s->pair + (blk * 8 + (own >> 1)) * 32 + 2 + rank + lane);
        uint32_t par = 0;
#define GET_PAR() mbar_spin(sb + B_EPOCH, 0); par = (*(volatile uint32_t*)(smem + M_EPOCH) + 1u) & 1u
        cluster_wait();
        if (wg) mbar_spin(sb + B_G0, 0);
#pragma unroll
        for (int c = 0; c < 8; c++) {
            if (c == 1 && wg) {
                wg_wait<0>();
                RELEASE(1, 1, lead);
                GET_PAR();
                mbar_spin(sb + B_G1, 0);
            }
            if (!wg || c < 3 || c == 4) mbar_spin(sb + (!wg || c == 0 ? B_F + 8 * c : c == 1 ? B_GO1 : c == 2 ? B_G2 : B_G4), 0);
            const uint32_t xa = sbd + wg * ((off_xl(c) - off_xe(c)) / 16);
            wg_fence();
#pragma unroll
            for (int kk = 0; kk < 4; kk++) {
                wgmma128<0>(acc, desc128(xa + off_xe(c) / 16 + 2 * kk), desc128(sbd + off_d(c) / 16 + 2 * kk), (c | kk) != 0);
                if (c == 7 && kk == 0) wg_commit();
            }
            wg_commit();
            if (c == 5 && !wg) { GET_PAR(); }
            if (c == 7) {
                if (wg) mbar_spin(sb + B_FULL, 0);
                wg_wait<2>();
                mbar_arrive_if(sb + B_GO1, lead0);
            }
            if (c == 4 || c >= 6) wg_wait<1>();
            if (c == 4) { mbar_arrive_if(sb + B_XE, lead0); RELEASE(1, 1, lead0); RELEASE(2, 2, lead1); RELEASE(2, 3, lead1); }
            if (c == 6) RELEASE(2, 4 * wg, lead);
            if (c == 7) mbar_arrive_if(sb + B_GO0, lead1);
        }
        const int rh = wg ^ comp;
        const uint32_t da0 = sbd + rh * 512, db0 = sbd - 0x10000 + 0x400000 + 1024;
        const uint32_t dbe = db0 + 6 * (REGION / 16), dbl = dbe - 1024;
#define STEP(da, db, first) wg_fence();                                                                     \
        _Pragma("unroll") for (int kk = 0; kk < 4; kk++)                                                    \
            wgmma128<1>(acc, desc128((da) + kk * 2), desc64((db) + kk * 256), !((first) && kk == 0));       \
        wg_commit()
#define ACC(i, j) (16 * ((i) >> 1) + 2 * ((i) & 1) + 4 * (j))
#define PW(i, j) pack_bf16(acc[ACC(i, j)], acc[ACC(i, j) + 1])
#define PT(i, j) ((j) == ((i) >> 1) ? (PW(i, j) & ~1u) | par : PW(i, j))
#define PIECE(i) make_uint4(PT(i, 0), PT(i, 1), PT(i, 2), PT(i, 3))
#define PIECES(F) F(0); F(1); sched_cut(); F(2); F(3); F(4); F(5); F(6); F(7)
        if (wg) {
            wg_wait<0>();
            fence_regs(acc);
#define STS1(i) sts128<(i) * 512>(sdst, PIECE(i))
            PIECES(STS1);
            STEP(da0, dbe, true);
            fence_proxy_async_smem();
            mbar_arrive_warp(sb + B_FULL + 8);
            RELEASE(1, 5, lead);
        } else {
            wg_wait<0>();
            fence_regs(acc);
            uint4 v[8];
#define STG0(i) v[i] = PIECE(i); stg128<(i) * 512>(gdst, v[i]); if (HINT_AT == (i) + 1) red_inc_if(hint, (own ^ T0) < 6 && lane == 0)
            PIECES(STG0);
            mbar_spin(sb + B_EPOCH, 0);
            asm volatile("bar.sync 2, 128;" ::: "memory");
#define STS0(i) if ((i) % 2 == 0) mbar_spin(sb + B_EPOCH, 0); sts128<(i) * 512>(sdst, v[i])
            STS0(0); STS0(1); STS0(2); STS0(3); STS0(4); STS0(5); STS0(6); STS0(7);
            fence_proxy_async_smem();
            mbar_arrive_warp(sb + B_FULL);
            RELEASE(1, 5, lead);
            mbar_arrive_if(sb + B_EARLY, lead);
            mbar_spin(sb + B_FULL, 0);
            mbar_spin(sb + B_GO0, 0);
            STEP(da0, dbe, true);
        }
#pragma unroll
        for (int step = 1; step < 3; step++) {
            mbar_spin(sb + B_FULL + 8 * step, 0);
            STEP(da0 + step * (REGION / 16), step == 1 ? dbl : db0 + step * (REGION / 16), false);
            wg_wait<1>();
            RELEASE(1, step - 1, lead);
            mbar_arrive_if(sb + B_FREE + 8 * (step - 1), lead);
        }
        int slot = 3, ph = 0, pslot = 2;
        uint32_t g0 = 0, g1 = 0;
        uint32_t oa = 0;
#pragma unroll 1
        for (int step = 3; step < 26; step++) {
            mbar_wait(sb + B_FULL + 8 * slot, ph);
            STEP(da0 + slot * (REGION / 16), db0 + slot * (REGION / 16), false);
            if (step == SETUP + wg) {
                const int r0 = rh * 64 + wq * 16 + (lane >> 2), sr = ((lane >> 2) & 1) * 4 + (lane >> 3);
                mbar_wait(sb + B_GATE, 0);
                g0 = ((const volatile uint32_t*)(smem + M_G))[r0];
                g1 = ((const volatile uint32_t*)(smem + M_G))[r0 + 8];
                oa = pin(wg ? ((own * 128 + (r0 & ~1)) * D_ + tn * 128 + (lane & 7) * 8) * 2u
                            : sb + rh * 8192 + wq * 2048 + sr * 128 + ((q ^ sr) << 4));
            }
            wg_wait<1>();
            RELEASE(1, pslot, lead);
            pslot = slot;
            if (++slot == NSTAGE) { slot = 0; ph ^= 1; }
        }
#define W26(kk) wgmma128<1>(acc, desc128(da0 + 2 * (REGION / 16) + (kk) * 2), desc64(db0 + 2 * (REGION / 16) + (kk) * 256), 1)
#define TAIL_STEPS(end, WAIT) slot = 3;                                                                     \
        _Pragma("unroll 1") for (int step = 27; step < (end); step++) {                                     \
            if (WAIT) mbar_wait(sb + B_FULL + 8 * slot, ph);                                                \
            STEP(da0 + (step < 32 - NA ? slot : step == 32 - NA ? 6 : pslot) * (REGION / 16), db0 + slot * (REGION / 16), false); \
            pslot = slot;                                                                                   \
            if (++slot == NSTAGE) { slot = 0; ph ^= 1; }                                                    \
        }
#define OW(i, j) hmul2_bf16(((i) & 1) ? g1 : g0, PW(i, j))
        mbar_wait(sb + B_FULL + 8 * 2, 0);
        if (!wg) {
            wg_fence();
            W26(0); W26(1); W26(2); W26(3);
            wg_commit();
            wg_wait<1>();
            RELEASE(1, 1, lead);
            TAIL_STEPS(32, true)
            wg_wait<1>();
            mbar_wait(sb + B_INIT, 0);
            mbar_arrive_if(sb + B_TAIL, lead);
            const uint32_t st0 = sb + rh * 8192 + wq * 2048;
            wg_wait<0>();
            fence_regs(acc);
#define OSTS(i) sts128<((i) >> 2) * REGION + ((i) & 1) * 1024>(((i) & 2) ? oa ^ 64 : oa, make_uint4(OW(i, 0), OW(i, 1), OW(i, 2), OW(i, 3)))
#define TMALINE(i) OSTS(i); OSTS((i) + 2); fence_proxy_async_smem(); __syncwarp();                          \
            asm volatile(ELECT "cp.reduce.async.bulk.tensor.4d.global.shared::cta.add.tile.bulk_group [%0, {%2,%3,%3,%4}], [%1];}" \
                         ::"l"(&p.mOut), "r"(st0 + ((i) >> 2) * REGION + ((i) & 1) * 1024), "r"(tn * 128 + ((i) >> 2) * 64), "r"(0), \
                           "r"(own * 16 + rh * 8 + wq * 2 + ((i) & 1)) : "memory")
            TMALINE(0); sched_cut(); TMALINE(1); sched_cut(); TMALINE(4); sched_cut(); TMALINE(5);
            bulk_wait_read();
        } else {
            wg_fence();
#pragma unroll
            for (int kk = 0; kk < HSK; kk++) W26(kk);
            wg_commit();
            wg_wait<1>();
            RELEASE(1, 1, lead);
            wg_wait<0>();
            asm volatile("setmaxnreg.inc.sync.aligned.u32 192;");
            const bool odd = lane & 4;
            char *op = pin((char*)p.out + oa), *opb = pin((char*)p.out + (oa ^ 64) + 1024);
            const uint32_t la = sb + rh * 8192 + (wq * 16 + (lane & 15)) * 128 + (((lane >> 4) ^ (lane & 7)) << 4);
            uint32_t af[32];
#pragma unroll
            for (int i = 0; i < 8; i++) {
                if (!(i & 3)) mbar_wait(sb + B_FULL + 2 * i, 1);
                ldsm4(af + 4 * i, (la ^ ((i & 3) * 32)) + (i < 4 ? 5 * REGION : 0));
            }
            mbar_wait(sb + B_TAIL, 0);
            wg_fence();
#pragma unroll
            for (int kk = HSK; kk < 4; kk++) W26(kk);
            wg_commit();
            TAIL_STEPS(30, false)
            float ach[32];
            wg_wait<0>();
            wg_fence();
#pragma unroll
            for (int i = 0; i < 8; i++) wgmma64_rs(acc, af + 4 * i, desc64(db0 + (i >> 2) * (REGION / 16) + (i & 3) * 256), 1);
            wg_commit();
#pragma unroll
            for (int i = 0; i < 8; i++) wgmma64_rs(ach, af + 4 * i, desc64(db0 + (i >> 2) * (REGION / 16) + (i & 3) * 256 + 128), i != 0);
            wg_commit();
            wg_wait<1>();
            fence_regs(acc);
#define REDLINE(i) {                                                                                        \
                uint32_t k[4], r[4];                                                                        \
                _Pragma("unroll") for (int j = 0; j < 4; j++) {                                             \
                    r[j] = __shfl_xor_sync(0xffffffffu, OW((i) + 2, j), 4);                                 \
                    k[j] = OW(i, j);                                                                        \
                }                                                                                           \
                red_bf16x8<((i) & 1) * 8192 + ((i) >> 2) * 128>(op, odd ? r[0] : k[0], odd ? r[1] : k[1], odd ? r[2] : k[2], odd ? r[3] : k[3]);  \
                red_bf16x8<((i) & 1) * 8192 + ((i) >> 2) * 128>(opb, odd ? k[0] : r[0], odd ? k[1] : r[1], odd ? k[2] : r[2], odd ? k[3] : r[3]); }
            REDLINE(0) sched_cut(); REDLINE(1) sched_cut();
            wg_wait<0>();
            fence_regs(ach);
#pragma unroll
            for (int i = 0; i < 32; i++) acc[32 + i] += ach[i];
            REDLINE(4) sched_cut(); REDLINE(5)
        }
    }
}

typedef CUresult (*EncodeTiledFn)(CUtensorMap*, CUtensorMapDataType, cuuint32_t, void*, const cuuint64_t*, const cuuint64_t*,
                                  const cuuint32_t*, const cuuint32_t*, CUtensorMapInterleave, CUtensorMapSwizzle,
                                  CUtensorMapL2promotion, CUtensorMapFloatOOBfill);

static void make_map(EncodeTiledFn enc, CUtensorMap* m, const void* base, uint64_t cols, uint64_t rows, uint32_t box_rows,
                     CUtensorMapSwizzle sw = CU_TENSOR_MAP_SWIZZLE_128B, uint32_t box_cols = 64) {
    cuuint64_t dims[2] = {cols, rows};
    cuuint64_t str[1] = {cols * 2};
    cuuint32_t box[2] = {box_cols, box_rows};
    cuuint32_t es[2] = {1, 1};
    enc(m, CU_TENSOR_MAP_DATA_TYPE_BFLOAT16, 2, (void*)base, dims, str, box, es, CU_TENSOR_MAP_INTERLEAVE_NONE,
        sw, CU_TENSOR_MAP_L2_PROMOTION_L2_128B, CU_TENSOR_MAP_FLOAT_OOB_FILL_NONE);
}

static void make_map_x2(EncodeTiledFn enc, CUtensorMap* m, const void* base) {
    cuuint64_t dims[3] = {64, S_, 8};
    cuuint64_t str[2] = {D_ * 2, 128};
    cuuint32_t box[3] = {64, 64, 2};
    cuuint32_t es[3] = {1, 1, 1};
    enc(m, CU_TENSOR_MAP_DATA_TYPE_BFLOAT16, 3, (void*)base, dims, str, box, es, CU_TENSOR_MAP_INTERLEAVE_NONE,
        CU_TENSOR_MAP_SWIZZLE_128B, CU_TENSOR_MAP_L2_PROMOTION_L2_128B, CU_TENSOR_MAP_FLOAT_OOB_FILL_NONE);
}

static void make_map_out(EncodeTiledFn enc, CUtensorMap* m, const void* base) {
    cuuint64_t dims[4] = {D_, 4, 2, S_ / 8};
    cuuint64_t str[3] = {2 * D_ * 2, D_ * 2, 8 * D_ * 2};
    cuuint32_t box[4] = {64, 4, 2, 1};
    cuuint32_t es[4] = {1, 1, 1, 1};
    enc(m, CU_TENSOR_MAP_DATA_TYPE_BFLOAT16, 4, (void*)base, dims, str, box, es, CU_TENSOR_MAP_INTERLEAVE_NONE,
        CU_TENSOR_MAP_SWIZZLE_128B, CU_TENSOR_MAP_L2_PROMOTION_NONE, CU_TENSOR_MAP_FLOAT_OOB_FILL_NONE);
}

extern "C" void kernel_launch(void* const* d_in, const int* in_sizes, int n_in, void* d_out, int out_size) {
    (void)in_sizes; (void)n_in; (void)out_size;
    static EncodeTiledFn enc = nullptr;
    static bool fused_ok = false;
    static void* scratch = nullptr;
    if (!enc) {
        void* fn = nullptr;
        cudaDriverEntryPointQueryResult q;
        cudaGetDriverEntryPoint("cuTensorMapEncodeTiled", &fn, cudaEnableDefault, &q);
        enc = (EncodeTiledFn)fn;
        cudaGetSymbolAddress(&scratch, g_s);
        cudaFuncSetAttribute(fused_kernel, cudaFuncAttributeMaxDynamicSharedMemorySize, SMEM_BYTES);
        int dev = 0, nsm = 0, ncl = 0;
        cudaGetDevice(&dev);
        cudaDeviceGetAttribute(&nsm, cudaDevAttrMultiProcessorCount, dev);
        cudaLaunchConfig_t cfg = {};
        cfg.gridDim = dim3(132); cfg.blockDim = dim3(NTHREADS); cfg.dynamicSmemBytes = SMEM_BYTES;
        cudaLaunchAttribute at;
        at.id = cudaLaunchAttributeClusterDimension;
        at.val.clusterDim.x = 2; at.val.clusterDim.y = 1; at.val.clusterDim.z = 1;
        cfg.attrs = &at; cfg.numAttrs = 1;
        fused_ok = cudaOccupancyMaxActiveClusters(&ncl, fused_kernel, &cfg) == cudaSuccess && nsm == 132 && ncl == 66;
        (void)cudaGetLastError();
    }
    if (!fused_ok) {
        const bf16* const* in = (const bf16* const*)d_in;
        fb_hidden<<<S_, D_, 0, cudaStreamPerThread>>>(in[0], in[3], in[4], in[10], in[6]);
        fb_ffn1<<<F_ / 128, 128, 0, cudaStreamPerThread>>>(in[0], in[7], in[8]);
        fb_ffn2<<<D_ / 64, 64, 0, cudaStreamPerThread>>>(in[9]);
        fb_seq<<<S_, D_, 0, cudaStreamPerThread>>>(in[0], in[1], in[2], (bf16*)d_out);
        return;
    }
    Params p;
    p.s = (Scratch*)scratch;
    p.x = (const bf16*)d_in[0];
    p.w_r = (const bf16*)d_in[6];
    p.wg = (const bf16*)d_in[7];
    p.wu = (const bf16*)d_in[8];
    p.wd = (const bf16*)d_in[9];
    p.gate_w = (const bf16*)d_in[10];
    p.out = (bf16*)d_out;
    make_map(enc, &p.mX1, d_in[0], D_, S_, 64);
    make_map_x2(enc, &p.mX2, d_in[0]);
    make_map(enc, &p.mCre, d_in[1], S_, S_, 128);
    make_map(enc, &p.mCim, d_in[2], S_, S_, 128);
    make_map(enc, &p.mDre, d_in[3], D_, D_, 128);
    make_map(enc, &p.mDim, d_in[4], D_, D_, 128);
    make_map(enc, &p.mAB, scratch, 64, 8 * 32 * 128, 64, CU_TENSOR_MAP_SWIZZLE_NONE);
    make_map_out(enc, &p.mOut, d_out);
    make_map(enc, &p.mWg, d_in[7], F_, D_, 64, CU_TENSOR_MAP_SWIZZLE_NONE, 32);
    make_map(enc, &p.mWu, d_in[8], F_, D_, 64, CU_TENSOR_MAP_SWIZZLE_NONE, 32);
    make_map(enc, &p.mWd, d_in[9], D_, F_, 8, CU_TENSOR_MAP_SWIZZLE_NONE, 256);
    fused_kernel<<<132, NTHREADS, SMEM_BYTES, cudaStreamPerThread>>>(p);
}
```
